```python
import torch

def _softmax(x, axis=-1):
    return torch.softmax(x, dim=axis)

def _gelu(x):
    return torch.nn.functional.gelu(x, approximate='tanh')

def _silu(x):
    return torch.nn.functional.silu(x)

def _sigmoid(x):
    return torch.sigmoid(x)

def _layernorm(x, axis=-1, eps=1e-05):
    m = x.mean(dim=axis, keepdim=True)
    v = x.var(dim=axis, keepdim=True, unbiased=False)
    return (x - m) / torch.sqrt(v + eps)

def _scatter_add(tgt, idx, src, axis=0):
    return tgt.clone().index_add_(axis, idx, src)

def _segment_sum(src, seg, n):
    out = torch.zeros((n,) + src.shape[1:], dtype=src.dtype)
    return out.index_add_(0, seg, src)

def _pad(x, pw):
    flat = tuple((v for pair in reversed(pw) for v in pair))
    return torch.nn.functional.pad(x, flat)
kernel_name = 'gated_mix__memory_aug_recurrent_mem_tr__ssm_conv_s4__prompt'

def setup_inputs():

    _w = lambda a: (lambda t: t.to(torch.bfloat16) if t.is_floating_point() else t)(torch.as_tensor(a))

    def _A_setup():
        B, S, Dm = (1, 2048, 640)
        H, Dh = (32, 128)
        M, seg = (8, 32)
        seg = min(seg, S)
        S = S // seg * seg
        return {'x': _w((lambda *s: torch.randn(*s, dtype=torch.bfloat16) * 0.05)(B, S, Dm)), 'mem0': _w((lambda *s: torch.randn(*s, dtype=torch.bfloat16) * 0.4)(B, M, Dm)), 'Wq': _w((lambda *s: torch.randn(*s, dtype=torch.bfloat16) * 6.4)(Dm, H, Dh) * Dm ** (-0.5)), 'Wk': _w((lambda *s: torch.randn(*s, dtype=torch.bfloat16) * 6.4)(Dm, H, Dh) * Dm ** (-0.5)), 'Wv': _w((lambda *s: torch.randn(*s, dtype=torch.bfloat16) * 0.4)(Dm, H, Dh) * Dm ** (-0.5)), 'Wo': _w((lambda *s: torch.randn(*s, dtype=torch.bfloat16) * 0.4)(H, Dh, Dm) * (H * Dh) ** (-0.5)), 'seg_len': seg}
    _A_in = _A_setup()

    def _B_setup():
        B, L, D, N = (1, 2048, 640, 128)
        A_re = -(lambda _x: torch.exp(torch.as_tensor(_x)))((lambda *s: torch.randn(*s, dtype=torch.bfloat16) * 6.4)(D, N))
        A_im = torch.pi * (lambda *s: torch.randn(*s, dtype=torch.bfloat16) * 0.05)(D, N)
        B_re = (lambda *s: torch.randn(*s, dtype=torch.bfloat16) * 0.1)(D, N)
        B_im = (lambda *s: torch.randn(*s, dtype=torch.bfloat16) * 0.1)(D, N)
        C_re = (lambda *s: torch.randn(*s, dtype=torch.bfloat16) * 0.1)(D, N)
        C_im = (lambda *s: torch.randn(*s, dtype=torch.bfloat16) * 0.1)(D, N)
        log_dt = (lambda *s: torch.randn(*s, dtype=torch.bfloat16) * 0.05)(D) * 0.5 - 4.0
        Dskip = (lambda *s: torch.randn(*s, dtype=torch.bfloat16) * 0.05)(D)
        return {'u': _w((lambda *s: torch.randn(*s, dtype=torch.bfloat16) * 0.05)(B, L, D)), 'A_re': _w(A_re), 'A_im': _w(A_im), 'B_re': _w(B_re), 'B_im': _w(B_im), 'C_re': _w(C_re), 'C_im': _w(C_im), 'log_dt': _w(log_dt), 'Dskip': _w(Dskip)}
    _B_in = _B_setup()
    return {'A_x': _A_in['x'], 'A_mem0': _A_in['mem0'], 'A_Wq': _A_in['Wq'], 'A_Wk': _A_in['Wk'], 'A_Wv': _A_in['Wv'], 'A_Wo': _A_in['Wo'], 'A_seg_len': _A_in['seg_len'], 'B_u': _B_in['u'], 'B_A_re': _B_in['A_re'], 'B_A_im': _B_in['A_im'], 'B_B_re': _B_in['B_re'], 'B_B_im': _B_in['B_im'], 'B_C_re': _B_in['C_re'], 'B_C_im': _B_in['C_im'], 'B_log_dt': _B_in['log_dt'], 'B_Dskip': _B_in['Dskip'], 'gate_w': _w((lambda *s: torch.randn(*s, dtype=torch.bfloat16) * 0.05)(640) * 16.0)}

def reference(A_x, A_mem0, A_Wq, A_Wk, A_Wv, A_Wo, A_seg_len, B_u, B_A_re, B_A_im, B_B_re, B_B_im, B_C_re, B_C_im, B_log_dt, B_Dskip, gate_w):

    def _A_ref(x, mem0, Wq, Wk, Wv, Wo, seg_len):
        B, S, Dm = x.shape
        H, Dh = (Wq.shape[1], Wq.shape[2])
        M = mem0.shape[1]
        scale = Dh ** (-0.5)
        n_seg = S // seg_len
        L = M + seg_len
        idx = torch.arange(L)
        mask = (idx[:, None] < M) | (idx[:, None] >= idx[None, :])
        mem = mem0
        outs = []
        for s in range(n_seg):
            xs = x[:, s * seg_len:(s + 1) * seg_len, :].clone()
            h = torch.concatenate([mem, xs], axis=1)
            q = torch.einsum('btd,dhe->bhte', h, Wq)
            k = torch.einsum('btd,dhe->bhte', h, Wk)
            v = torch.einsum('btd,dhe->bhte', h, Wv)
            scores = torch.einsum('bhqe,bhke->bhqk', q, k) * scale
            scores = torch.where(mask[None, None], scores, -1000000000.0)
            p = _softmax(scores, axis=-1)
            o = torch.einsum('bhqk,bhke->bhqe', p, v)
            o = torch.einsum('bhte,hed->btd', o, Wo)
            mem = o[:, :M, :].clone()
            outs.append(o[:, M:, :])
        return torch.concatenate(outs, axis=1)

    def _B_ref(u, A_re, A_im, B_re, B_im, C_re, C_im, log_dt, Dskip):
        Bsz, L, D = u.shape
        dt = torch.exp(log_dt)[:, None]
        A = A_re + 1j * A_im
        Bc = B_re + 1j * B_im
        Cc = C_re + 1j * C_im
        logdA = dt * A
        dB = dt * Bc
        l = (lambda x, dt: x.to(dt))(torch.arange(L), A_re.dtype)
        P = torch.exp(logdA[:, :, None] * l[None, None, :])
        K = torch.einsum('dn,dnl,dn->dl', Cc, P, dB).real
        L2 = 2 * L
        Kp = _pad(K, ((0, 0), (0, L)))
        up = (lambda x, *d: x.permute(*d))(u, 0, 2, 1)
        up = _pad(up, ((0, 0), (0, 0), (0, L)))
        Kf = (lambda x, axes=(-2, -1): torch.fft.rfft2(x.float(), dim=axes))(Kp[:, None, :], axes=(-2, -1))
        Uf = (lambda x, axes=(-2, -1): torch.fft.rfft2(x.float(), dim=axes))(up[:, :, None, :], axes=(-2, -1))
        Yf = Uf * Kf[None, :, :, :]
        y = (lambda x, s, axes=(-2, -1): torch.fft.irfft2(x, s=s, dim=axes).to(torch.bfloat16))(Yf, (1, L2), axes=(-2, -1))[:, :, 0, :L]
        y = (lambda x, *d: x.permute(*d))(y, 0, 2, 1) + u * Dskip[None, None, :]
        return y
    x = A_x
    g = _sigmoid((x * gate_w).sum(-1, keepdims=True))
    a = _A_ref(x, A_mem0, A_Wq, A_Wk, A_Wv, A_Wo, A_seg_len)
    b = _B_ref(x, B_A_re, B_A_im, B_B_re, B_B_im, B_C_re, B_C_im, B_log_dt, B_Dskip)
    return g * a + (1 - g) * b
```

```cpp
#include <cuda_runtime.h>
#include <cuda_bf16.h>
#include <stdint.h>
#include <cuda.h>

typedef __nv_bfloat16 bf16;

#define SEQ 2048
#define DM 640
#define NH 32
#define DH 128
#define NM 8
#define SEG 32
#define NSEG 64
#define NST 128
#define HD 4096

__device__ bf16  g_b[SEQ * DM];
__device__ float g_g[SEQ];

__device__ __forceinline__ float bf2f(bf16 v) { return __bfloat162float(v); }
__device__ __forceinline__ uint32_t pack_bf16(float lo, float hi) {
    uint32_t r; asm("cvt.rn.bf16x2.f32 %0, %1, %2;" : "=r"(r) : "f"(hi), "f"(lo)); return r;
}
__device__ __forceinline__ uint32_t f2tf32(float x) { uint32_t r; asm("cvt.rna.tf32.f32 %0, %1;" : "=r"(r) : "f"(x)); return r; }
__device__ __forceinline__ void mma_tf32(float (&d)[4], uint32_t a0, uint32_t a1, uint32_t a2, uint32_t a3, uint32_t b0, uint32_t b1) {
    asm volatile("mma.sync.aligned.m16n8k8.row.col.f32.tf32.tf32.f32 {%0,%1,%2,%3}, {%4,%5,%6,%7}, {%8,%9}, {%0,%1,%2,%3};\n"
        : "+f"(d[0]), "+f"(d[1]), "+f"(d[2]), "+f"(d[3]) : "r"(a0), "r"(a1), "r"(a2), "r"(a3), "r"(b0), "r"(b1));
}
__device__ __forceinline__ void mma_bf16(float (&d)[4], uint32_t a0, uint32_t a1, uint32_t a2, uint32_t a3, uint32_t b0, uint32_t b1) {
    asm volatile("mma.sync.aligned.m16n8k16.row.col.f32.bf16.bf16.f32 {%0,%1,%2,%3}, {%4,%5,%6,%7}, {%8,%9}, {%0,%1,%2,%3};\n"
        : "+f"(d[0]), "+f"(d[1]), "+f"(d[2]), "+f"(d[3]) : "r"(a0), "r"(a1), "r"(a2), "r"(a3), "r"(b0), "r"(b1));
}
struct cf { float re, im; };
__device__ __forceinline__ cf cmul(cf a, cf b) { cf r; r.re = a.re * b.re - a.im * b.im; r.im = a.re * b.im + a.im * b.re; return r; }
__device__ __forceinline__ cf csq(cf a) { cf r; r.re = a.re * a.re - a.im * a.im; r.im = 2.f * a.re * a.im; return r; }
__device__ __forceinline__ cf cexpL(float zr, float zi, float L) {
    float e = __expf(zr * L);
    float ang = zi * L;
    float k = rintf(ang * 0.15915494309189535f);
    ang = fmaf(-k, 6.2831854820251465f, ang);
    ang = fmaf(-k, -1.7484555314695172e-07f, ang);
    cf r; r.re = e * __cosf(ang); r.im = e * __sinf(ang); return r;
}

#define SSM_CH 8
#define KC_PITCH 648
#define XS_PITCH (2048 + 8)
#define KR_LEN (2048 + 32)
#define PART_PITCH 20
struct SsmSmem {
    float Kc[SSM_CH][KC_PITCH];
    bf16  xs[SSM_CH][XS_PITCH];
    bf16  KR[2][KR_LEN];
    union {
        float part[8][128 * PART_PITCH];
        float st[SSM_CH][NST][8];
    } u;
    bf16  ys[2048][SSM_CH];
};

__device__ __forceinline__ int kc_index(int l) {
    return l < 256 ? l : (l < 512 ? 256 + ((l - 256) >> 1) : (l < 1024 ? 384 + ((l - 512) >> 2) : 512 + ((l - 1024) >> 3)));
}

__device__ __noinline__ void ssm_group(unsigned char* smem_raw, int grp, const bf16* __restrict__ x, const bf16* __restrict__ A_re, const bf16* __restrict__ A_im,
        const bf16* __restrict__ B_re, const bf16* __restrict__ B_im, const bf16* __restrict__ C_re, const bf16* __restrict__ C_im,
        const bf16* __restrict__ log_dt, const bf16* __restrict__ Dskip) {
    SsmSmem& S = *reinterpret_cast<SsmSmem*>(smem_raw);
    const int tid = threadIdx.x, w = tid >> 5, lane = tid & 31, g = lane >> 2, t = lane & 3;
    const int d0 = grp * SSM_CH;
    __syncthreads();
    for (int l = tid; l < 2048; l += 256) {
        uint4 v = *reinterpret_cast<const uint4*>(x + (size_t)l * DM + d0);
        const bf16* p = reinterpret_cast<const bf16*>(&v);
        #pragma unroll
        for (int c = 0; c < 8; c++) S.xs[c][l] = p[c];
    }
    {
        const int d = d0 + w;
        const float dt = bf2f(__float2bfloat16_rn(expf(bf2f(log_dt[d]))));
        for (int n = lane; n < NST; n += 32) {
            float zr = dt * bf2f(A_re[d * NST + n]), zi = dt * bf2f(A_im[d * NST + n]);
            cf dB; dB.re = dt * bf2f(B_re[d * NST + n]); dB.im = dt * bf2f(B_im[d * NST + n]);
            cf C; C.re = bf2f(C_re[d * NST + n]); C.im = bf2f(C_im[d * NST + n]);
            cf wv = cmul(C, dB);
            cf u8 = cexpL(zr, zi, 8.f), u128 = cexpL(zr, zi, 128.f);
            float* st = S.u.st[w][n];
            *reinterpret_cast<float4*>(st) = make_float4(zr, zi, wv.re, wv.im);
            *reinterpret_cast<float4*>(st + 4) = make_float4(u8.re, u8.im, u128.re, u128.im);
        }
        __syncwarp();
        float a0a[4] = {0, 0, 0, 0}, a0b[4] = {0, 0, 0, 0}, a1[4] = {0, 0, 0, 0}, a2a[4] = {0, 0, 0, 0}, a2b[4] = {0, 0, 0, 0};
        float k2048 = 0.f;
        const float Lg = (g < 4) ? (512.f + 4.f * g) : (g < 6 ? 1024.f + 8.f * (g - 4) : 1536.f + 8.f * (g - 6));
        #pragma unroll 2
        for (int kk = 0; kk < 32; kk++) {
            const float* st = S.u.st[w][4 * kk + t];
            float4 s0 = *reinterpret_cast<const float4*>(st), s1 = *reinterpret_cast<const float4*>(st + 4);
            cf wv; wv.re = s0.z; wv.im = s0.w;
            cf u8; u8.re = s1.x; u8.im = s1.y;
            cf u128; u128.re = s1.z; u128.im = s1.w;
            cf e1 = cexpL(s0.x, s0.y, (float)g);
            cf e23 = cexpL(s0.x, s0.y, Lg);
            cf e1b = cmul(e1, u8);
            cf e2 = csq(e1);
            cf p = csq(csq(csq(e2)));
            cf f0 = cmul(wv, p), f1 = cmul(f0, u128), f2 = cmul(f1, u128), f3 = cmul(f2, u128);
            uint32_t A00 = f2tf32(f0.re), A01 = f2tf32(f1.re), A02 = f2tf32(-f0.im), A03 = f2tf32(-f1.im);
            uint32_t A10 = f2tf32(f2.re), A11 = f2tf32(f3.re), A12 = f2tf32(-f2.im), A13 = f2tf32(-f3.im);
            mma_tf32(a0a, A00, A01, A02, A03, f2tf32(e1.re), f2tf32(e1.im));
            mma_tf32(a0b, A00, A01, A02, A03, f2tf32(e1b.re), f2tf32(e1b.im));
            mma_tf32(a1, A10, A11, A12, A13, f2tf32(e2.re), f2tf32(e2.im));
            uint32_t E0 = f2tf32(e23.re), E1 = f2tf32(e23.im);
            mma_tf32(a2a, A00, A01, A02, A03, E0, E1);
            mma_tf32(a2b, A10, A11, A12, A13, E0, E1);
            cf e2048 = csq(e23);
            k2048 += wv.re * e2048.re - wv.im * e2048.im;
        }
        k2048 += __shfl_xor_sync(~0u, k2048, 1);
        k2048 += __shfl_xor_sync(~0u, k2048, 2);
        float* Kc = S.Kc[w];
        Kc[16 * g + 2 * t] = a0a[0]; Kc[16 * g + 2 * t + 1] = a0a[1]; Kc[16 * (g + 8) + 2 * t] = a0a[2]; Kc[16 * (g + 8) + 2 * t + 1] = a0a[3];
        Kc[16 * g + 8 + 2 * t] = a0b[0]; Kc[16 * g + 8 + 2 * t + 1] = a0b[1]; Kc[16 * (g + 8) + 8 + 2 * t] = a0b[2]; Kc[16 * (g + 8) + 8 + 2 * t + 1] = a0b[3];
        Kc[256 + 8 * g + 2 * t] = a1[0]; Kc[256 + 8 * g + 2 * t + 1] = a1[1]; Kc[256 + 8 * (g + 8) + 2 * t] = a1[2]; Kc[256 + 8 * (g + 8) + 2 * t + 1] = a1[3];
        #pragma unroll
        for (int mt = 0; mt < 2; mt++) {
            const float* acc = mt ? a2b : a2a;
            #pragma unroll
            for (int e = 0; e < 4; e++) {
                int A = mt * 16 + g + (e >> 1) * 8, j = 2 * t + (e & 1);
                int Lj = (j < 4) ? 512 + 4 * j : (j < 6 ? 1024 + 8 * (j - 4) : 1536 + 8 * (j - 6));
                Kc[kc_index(Lj + 16 * A)] = acc[e];
            }
        }
        if (lane == 16) Kc[640] = k2048;
    }
    __syncthreads();
    for (int c = 0; c < SSM_CH; c++) {
        __syncthreads();
        for (int m = tid; m < KR_LEN; m += 256) {
            int i0 = 2048 - m, i1 = 2047 - m;
            float v0 = 0.f, v1 = 0.f;
            if (i0 >= 0 && i0 < 2048) v0 = S.Kc[c][kc_index((int)bf2f(__float2bfloat16_rn((float)i0)))];
            if (i1 >= 0 && i1 < 2048) v1 = S.Kc[c][kc_index((int)bf2f(__float2bfloat16_rn((float)i1)))];
            S.KR[0][m] = __float2bfloat16_rn(v0);
            S.KR[1][m] = __float2bfloat16_rn(v1);
        }
        __syncthreads();
        uint32_t B[16][2];
        #pragma unroll
        for (int v = 0; v < 16; v++) {
            const bf16* p = &S.xs[c][16 * (8 * v + g) + 2 * t];
            B[v][0] = *reinterpret_cast<const uint32_t*>(p);
            B[v][1] = *reinterpret_cast<const uint32_t*>(p + 8);
        }
        float acc[16][4];
        #pragma unroll
        for (int v = 0; v < 16; v++) { acc[v][0] = acc[v][1] = acc[v][2] = acc[v][3] = 0.f; }
        const bf16* kr = &S.KR[g & 1][0];
        const int mbase = 2048 - 16 * w - g + 2 * t - (g & 1);
        #pragma unroll
        for (int q = 0; q < 16; q++) {
            int m0 = mbase - 128 * q;
            uint32_t A0 = *reinterpret_cast<const uint32_t*>(kr + m0);
            uint32_t A1 = *reinterpret_cast<const uint32_t*>(kr + m0 - 8);
            uint32_t A2 = *reinterpret_cast<const uint32_t*>(kr + m0 + 8);
            #pragma unroll
            for (int v = q; v < 16; v++) mma_bf16(acc[v], A0, A1, A2, A0, B[v - q][0], B[v - q][1]);
        }
        float* part = S.u.part[w];
        #pragma unroll
        for (int v = 0; v < 16; v++) {
            int a = 8 * v + 2 * t + w;
            if (a < 128) { part[a * PART_PITCH + g] = acc[v][0]; part[a * PART_PITCH + g + 8] = acc[v][2]; }
            if (a + 1 < 128) { part[(a + 1) * PART_PITCH + g] = acc[v][1]; part[(a + 1) * PART_PITCH + g + 8] = acc[v][3]; }
        }
        __syncthreads();
        const float dsk = bf2f(Dskip[d0 + c]);
        for (int l = tid; l < 2048; l += 256) {
            int a = l >> 4, b = l & 15;
            float s = 0.f;
            #pragma unroll
            for (int r = 0; r < 8; r++) if (a >= r) s += S.u.part[r][a * PART_PITCH + b];
            float xv = bf2f(S.xs[c][l]);
            float yv = bf2f(__float2bfloat16_rn(s)) + bf2f(__float2bfloat16_rn(xv * dsk));
            S.ys[l][c] = __float2bfloat16_rn(yv);
        }
    }
    __syncthreads();
    for (int l = tid; l < 2048; l += 256)
        *reinterpret_cast<uint4*>(g_b + (size_t)l * DM + d0) = *reinterpret_cast<const uint4*>(&S.ys[l][0]);
}

__device__ __forceinline__ uint32_t smem_u32(const void* p) { return (uint32_t)__cvta_generic_to_shared(p); }
__device__ __forceinline__ void mbar_init(uint32_t bar, uint32_t cnt) { asm volatile("mbarrier.init.shared::cta.b64 [%0], %1;" :: "r"(bar), "r"(cnt) : "memory"); }
__device__ __forceinline__ void mbar_expect_tx(uint32_t bar, uint32_t bytes) { asm volatile("mbarrier.arrive.expect_tx.shared::cta.b64 _, [%0], %1;" :: "r"(bar), "r"(bytes) : "memory"); }
__device__ __forceinline__ void mbar_arrive(uint32_t bar) { asm volatile("mbarrier.arrive.shared::cta.b64 _, [%0];" :: "r"(bar) : "memory"); }
__device__ __forceinline__ void mbar_wait(uint32_t bar, uint32_t parity) {
    uint32_t ok; int guard = 0;
    do {
        asm volatile("{\n.reg .pred P1;\nmbarrier.test_wait.parity.shared::cta.b64 P1, [%1], %2;\nselp.u32 %0,1,0,P1;\n}" : "=r"(ok) : "r"(bar), "r"(parity) : "memory");
    } while (!ok && ++guard < (1 << 26));
}
__device__ __forceinline__ uint32_t mapa(uint32_t addr, uint32_t rank) { uint32_t r; asm volatile("mapa.shared::cluster.u32 %0, %1, %2;" : "=r"(r) : "r"(addr), "r"(rank)); return r; }
__device__ __forceinline__ void st_async4(uint32_t addr, float a, float b, float c, float d, uint32_t bar) {
    asm volatile("st.async.weak.shared::cluster.mbarrier::complete_tx::bytes.v4.f32 [%0], {%1,%2,%3,%4}, [%5];" :: "r"(addr), "f"(a), "f"(b), "f"(c), "f"(d), "r"(bar) : "memory");
}
__device__ __forceinline__ void bulk_s2c(uint32_t dst, uint32_t src, uint32_t bytes, uint32_t bar) {
    asm volatile("cp.async.bulk.shared::cluster.shared::cta.mbarrier::complete_tx::bytes [%0], [%1], %2, [%3];" :: "r"(dst), "r"(src), "r"(bytes), "r"(bar) : "memory");
}
__device__ __forceinline__ void bulk_g2s(uint32_t dst, const void* src, uint32_t bytes, uint32_t bar) {
    asm volatile("cp.async.bulk.shared::cluster.global.mbarrier::complete_tx::bytes [%0], [%1], %2, [%3];" :: "r"(dst), "l"(src), "r"(bytes), "r"(bar) : "memory");
}
__device__ __forceinline__ void bulk_s2g(void* dst, uint32_t src, uint32_t bytes) {
    asm volatile("cp.async.bulk.global.shared::cta.bulk_group [%0], [%1], %2;" :: "l"(dst), "r"(src), "r"(bytes) : "memory");
}
__device__ __forceinline__ void bulk_commit() { asm volatile("cp.async.bulk.commit_group;" ::: "memory"); }
__device__ __forceinline__ void bulk_wait_read0() { asm volatile("cp.async.bulk.wait_group.read 0;" ::: "memory"); }
__device__ __forceinline__ void bulk_wait0() { asm volatile("cp.async.bulk.wait_group 0;" ::: "memory"); }
__device__ __forceinline__ void fence_async() { asm volatile("fence.proxy.async.shared::cta;" ::: "memory"); }
__device__ __forceinline__ void nbar_sync(int id, int n) { asm volatile("bar.sync %0, %1;" :: "r"(id), "r"(n) : "memory"); }
__device__ __forceinline__ void nbar_arrive(int id, int n) { asm volatile("bar.arrive %0, %1;" :: "r"(id), "r"(n) : "memory"); }
__device__ __forceinline__ void cp_async16(uint32_t dst, const void* src) { asm volatile("cp.async.cg.shared.global [%0], [%1], 16;" :: "r"(dst), "l"(src) : "memory"); }
__device__ __forceinline__ void cp_async_wait_all() { asm volatile("cp.async.wait_all;" ::: "memory"); }
__device__ __forceinline__ void ldsm4(uint32_t (&r)[4], uint32_t addr) {
    asm volatile("ldmatrix.sync.aligned.m8n8.x4.shared.b16 {%0,%1,%2,%3}, [%4];" : "=r"(r[0]), "=r"(r[1]), "=r"(r[2]), "=r"(r[3]) : "r"(addr) : "memory");
}
__device__ __forceinline__ void ldsm4t(uint32_t (&r)[4], uint32_t addr) {
    asm volatile("ldmatrix.sync.aligned.m8n8.x4.trans.shared.b16 {%0,%1,%2,%3}, [%4];" : "=r"(r[0]), "=r"(r[1]), "=r"(r[2]), "=r"(r[3]) : "r"(addr) : "memory");
}
__device__ __forceinline__ void stsm2t(uint32_t addr, uint32_t r0, uint32_t r1) {
    asm volatile("stmatrix.sync.aligned.m8n8.x2.trans.shared.b16 [%0], {%1,%2};" :: "r"(addr), "r"(r0), "r"(r1) : "memory");
}
__device__ __forceinline__ uint4 ld_relaxed4(const void* p) { uint4 v; asm volatile("ld.relaxed.gpu.global.v4.u32 {%0,%1,%2,%3}, [%4];" : "=r"(v.x), "=r"(v.y), "=r"(v.z), "=r"(v.w) : "l"(p) : "memory"); return v; }
__device__ __forceinline__ void st_relaxed2(void* p, uint32_t a, uint32_t b) { asm volatile("st.relaxed.gpu.global.v2.u32 [%0], {%1,%2};" :: "l"(p), "r"(a), "r"(b) : "memory"); }
__device__ __forceinline__ void st_relaxed1(void* p, uint32_t a) { asm volatile("st.relaxed.gpu.global.u32 [%0], %1;" :: "l"(p), "r"(a) : "memory"); }
__device__ __forceinline__ float ex2_approx(float x) { float r; asm("ex2.approx.ftz.f32 %0, %1;" : "=f"(r) : "f"(x)); return r; }
__device__ __forceinline__ uint64_t make_desc(uint32_t saddr, uint32_t lbo, uint32_t sbo) {
    return (uint64_t)((saddr & 0x3FFFF) >> 4) | ((uint64_t)((lbo & 0x3FFFF) >> 4) << 16) | ((uint64_t)((sbo & 0x3FFFF) >> 4) << 32) | (1ull << 62);
}
__device__ __forceinline__ void wg_fence() { asm volatile("wgmma.fence.sync.aligned;" ::: "memory"); }
__device__ __forceinline__ void wg_commit() { asm volatile("wgmma.commit_group.sync.aligned;" ::: "memory"); }
__device__ __forceinline__ void wg_wait0() { asm volatile("wgmma.wait_group.sync.aligned 0;" ::: "memory"); }
__device__ __forceinline__ void wgmma_n40_tA(float (&d)[20], uint64_t da, uint64_t db, int scale_d) {
    asm volatile("{\n.reg .pred p;\nsetp.ne.b32 p, %22, 0;\n"
        "wgmma.mma_async.sync.aligned.m64n40k16.f32.bf16.bf16 {%0,%1,%2,%3,%4,%5,%6,%7,%8,%9,%10,%11,%12,%13,%14,%15,%16,%17,%18,%19}, %20, %21, p, 1, 1, 1, 0;\n}\n"
        : "+f"(d[0]), "+f"(d[1]), "+f"(d[2]), "+f"(d[3]), "+f"(d[4]), "+f"(d[5]), "+f"(d[6]), "+f"(d[7]), "+f"(d[8]), "+f"(d[9]),
          "+f"(d[10]), "+f"(d[11]), "+f"(d[12]), "+f"(d[13]), "+f"(d[14]), "+f"(d[15]), "+f"(d[16]), "+f"(d[17]), "+f"(d[18]), "+f"(d[19])
        : "l"(da), "l"(db), "r"(scale_d));
}

#define NREP 8
#define NRED 80
__device__ uint32_t g_pm[2][NRED][NH][64];
__device__ uint32_t g_memx[4][NREP][2560];
__device__ unsigned g_done;
__device__ unsigned g_flag[NSEG][NH];
__device__ __align__(1024) bf16 g_Qimg[NSEG * NH * 2 * 32 * 64];
__device__ __align__(1024) bf16 g_Kimg[NSEG * NH * 2 * 32 * 64];
__device__ __align__(1024) bf16 g_Vimg[NSEG * NH * 2 * 32 * 64];
__device__ __align__(1024) bf16 g_KMimg[NSEG * NH * 2 * 8 * 64];
__device__ __align__(1024) bf16 g_VMimg[NSEG * NH * 2 * 8 * 64];

#define SM_XB    0
#define SM_VT    81920
#define SM_KT    (SM_VT + 20480)
#define SM_QT    (SM_KT + 10240)
#define SM_QS    (SM_QT + 4096)
#define SM_MEMB  (SM_QS + 1024)
#define SM_RED   (SM_MEMB + 10240)
#define SM_SC    (SM_RED + 16384)
#define SM_CRED  (SM_SC + 5120)
#define SM_PB    (SM_CRED + 1024)
#define SM_TRACE (SM_PB + 1024)
#define SM_WO    163840
#define SM_BAR   (SM_WO + 65536)
#define SM_TOTAL (SM_BAR + 256)
#define B_SC   (SM_BAR + 0)
#define B_V    (SM_BAR + 16)
#define B_MEM  (SM_BAR + 32)
#define B_P    (SM_BAR + 48)
#define B_X    (SM_BAR + 56)

#define TR(ev) do {} while (0)
__device__ __forceinline__ uint32_t tag_of(int s) { return s == 61 ? 3u : (uint32_t)(((s >> 1) & 1) + 1); }
__device__ __forceinline__ void cluster_sync_all() { asm volatile("barrier.cluster.arrive.release.aligned;\nbarrier.cluster.wait.acquire.aligned;" ::: "memory"); }
__device__ __forceinline__ void tma_load_2d(uint32_t dst, const void* map, int c0, int c1, uint32_t bar) {
    asm volatile("cp.async.bulk.tensor.2d.shared::cluster.global.mbarrier::complete_tx::bytes [%0], [%1, {%3, %4}], [%2];"
        :: "r"(dst), "l"(map), "r"(bar), "r"(c0), "r"(c1) : "memory");
}
__device__ __forceinline__ void stsm4t(uint32_t addr, uint32_t r0, uint32_t r1, uint32_t r2, uint32_t r3) {
    asm volatile("stmatrix.sync.aligned.m8n8.x4.trans.shared.b16 [%0], {%1,%2,%3,%4};" :: "r"(addr), "r"(r0), "r"(r1), "r"(r2), "r"(r3) : "memory");
}
__device__ __forceinline__ void wgmma_n32_rs(float (&d)[16], const uint32_t (&a)[4], uint64_t db, int scale_d) {
    asm volatile("{\n.reg .pred p;\nsetp.ne.b32 p, %21, 0;\n"
        "wgmma.mma_async.sync.aligned.m64n32k16.f32.bf16.bf16 {%0,%1,%2,%3,%4,%5,%6,%7,%8,%9,%10,%11,%12,%13,%14,%15}, {%16,%17,%18,%19}, %20, p, 1, 1, 0;\n}\n"
        : "+f"(d[0]), "+f"(d[1]), "+f"(d[2]), "+f"(d[3]), "+f"(d[4]), "+f"(d[5]), "+f"(d[6]), "+f"(d[7]),
          "+f"(d[8]), "+f"(d[9]), "+f"(d[10]), "+f"(d[11]), "+f"(d[12]), "+f"(d[13]), "+f"(d[14]), "+f"(d[15])
        : "r"(a[0]), "r"(a[1]), "r"(a[2]), "r"(a[3]), "l"(db), "r"(scale_d));
}

__device__ __forceinline__ void signal_export(unsigned* flag) {
    bulk_wait0();
    asm volatile("fence.proxy.async;" ::: "memory");
    __threadfence();
    atomicAdd(flag, 1u);
}
template <int NT>
__device__ __forceinline__ void u_pass(unsigned char* smem, uint32_t sb, int s, int h, int wg, int warp, int lane, int tile0) {
    const int sl = s & 1;
    float U[NT][20];
    wg_fence();
    #pragma unroll
    for (int q = 0; q < NT; q++) {
        const uint32_t wa = sb + SM_WO + (2 * wg + q) * 16384;
        #pragma unroll
        for (int ks = 0; ks < 8; ks++) {
            uint64_t da = make_desc(wa + ks * 2048, 1024, 1024);
            uint64_t db = make_desc(sb + SM_VT + sl * 10240 + (ks >> 2) * 5120 + (ks & 3) * 32, 16, 1024);
            wgmma_n40_tA(U[q], da, db, ks > 0);
        }
    }
    wg_commit();
    if (wg == 0 && warp == 0) TR(14);
    if (wg == 1 && warp == 0) TR(15);
    mbar_wait(sb + B_P, s & 1);
    uint32_t pb[5];
    {
        const uint32_t* pbs = reinterpret_cast<const uint32_t*>(smem + SM_PB);
        #pragma unroll
        for (int q = 0; q < 5; q++) pb[q] = pbs[q * 32 + lane];
    }
    if (wg == 0 && warp == 0) TR(8);
    wg_wait0();
    if (wg == 0 && warp == 0) TR(6);
    const uint32_t tg = tag_of(s);
    #pragma unroll
    for (int q = 0; q < NT; q++) {
        float o[4] = {0, 0, 0, 0}, o2[4] = {0, 0, 0, 0};
        const float (&u)[20] = U[q];
        mma_bf16(o, pack_bf16(u[0], u[1]), pack_bf16(u[2], u[3]), pack_bf16(u[4], u[5]), pack_bf16(u[6], u[7]), pb[0], pb[1]);
        mma_bf16(o2, pack_bf16(u[8], u[9]), pack_bf16(u[10], u[11]), pack_bf16(u[12], u[13]), pack_bf16(u[14], u[15]), pb[2], pb[3]);
        mma_bf16(o, pack_bf16(u[16], u[17]), pack_bf16(u[18], u[19]), 0u, 0u, pb[4], 0u);
        int sg = 4 * (tile0 + 2 * wg + q) + warp;
        st_relaxed2(&g_pm[sl][2 * sg][h][lane * 2], (__float_as_uint(o[0] + o2[0]) & ~3u) | tg, (__float_as_uint(o[1] + o2[1]) & ~3u) | tg);
        st_relaxed2(&g_pm[sl][2 * sg + 1][h][lane * 2], (__float_as_uint(o[2] + o2[2]) & ~3u) | tg, (__float_as_uint(o[3] + o2[3]) & ~3u) | tg);
    }
}

__global__ void __cluster_dims__(3, 1, 1) __launch_bounds__(384, 1)
k_chain(const __grid_constant__ CUtensorMap xmap, const bf16* __restrict__ mem0, const bf16* __restrict__ Wq, const bf16* __restrict__ Wk,
        const bf16* __restrict__ Wv, const bf16* __restrict__ Wo) {
    extern __shared__ __align__(1024) unsigned char smem[];
    const uint32_t sb = smem_u32(smem);
    const int tid = threadIdx.x, lane = tid & 31;
    const int wg = __shfl_sync(~0u, tid >> 7, 0), warp = __shfl_sync(~0u, (tid >> 5) & 3, 0);
    uint32_t rank; asm volatile("mov.u32 %0, %%cluster_ctarank;" : "=r"(rank));
    const int cta = blockIdx.x, h = cta / 3;
    asm volatile("griddepcontrol.launch_dependents;");
    if (tid == 0) {
        for (int i = 0; i < 2; i++) { mbar_init(sb + B_SC + 8 * i, 1); mbar_init(sb + B_V + 8 * i, 1); mbar_init(sb + B_MEM + 8 * i, 64); mbar_init(sb + B_X + 8 * i, 1); }
        mbar_init(sb + B_P, 32);
        asm volatile("fence.mbarrier_init.release.cluster;" ::: "memory");
    }
    {
        const int ntile = (rank == 2) ? 4 : 3;
        const int tile0 = (rank == 2) ? 0 : (rank == 0 ? 4 : 7);
        const bf16* src0 = (rank == 2) ? Wv + h * DH : Wq + h * DH + rank * 64;
        const bf16* src1 = (rank == 2) ? Wv + h * DH + 64 : Wk + h * DH + rank * 64;
        for (int i = tid; i < 2 * 640 * 8; i += 384) {
            int mt = i / 5120, r = (i % 5120) >> 3, c = i & 7;
            const bf16* s = (mt ? src1 : src0) + (size_t)r * HD + c * 8;
            cp_async16(sb + mt * 81920 + r * 128 + ((c ^ (r & 7)) << 4), s);
        }
        for (int i = tid; i < ntile * 128 * 8; i += 384) {
            int lt = i >> 10, r = (i >> 3) & 127, c = i & 7;
            const bf16* s = Wo + ((size_t)h * DH + r) * DM + (tile0 + lt) * 64 + c * 8;
            cp_async16(sb + SM_WO + lt * 16384 + r * 128 + ((c ^ (r & 7)) << 4), s);
        }
        cp_async_wait_all();
        fence_async();
    }
    __syncthreads();

    if (wg == 2) {
        asm volatile("setmaxnreg.dec.sync.aligned.u32 40;");
        const int ct = tid & 127;
        nbar_sync(5, 384);
        for (int c = ct; c < 640; c += 128) {
            int ks = c >> 4, hf = (c >> 3) & 1, r = c & 7;
            *reinterpret_cast<uint4*>(smem + SM_MEMB + c * 16) = *reinterpret_cast<const uint4*>(mem0 + r * DM + ks * 16 + hf * 8);
        }
        if (ct == 0) {
            for (int sg = 0; sg < 2; sg++) {
                mbar_expect_tx(sb + B_X + 8 * sg, 40960);
                for (int c = 0; c < 10; c++) tma_load_2d(sb + SM_XB + sg * 40960 + c * 4096, &xmap, c * 64, sg * 32, sb + B_X + 8 * sg);
            }
            mbar_expect_tx(sb + B_SC, 2560);
            if (rank < 2) mbar_expect_tx(sb + B_V, 8192 + 2048);
        }
        nbar_sync(5, 384);
        cluster_sync_all();
        for (int s = 0; s < NSEG - 1; s++) {
            if (ct == 0 && s + 1 < NSEG - 1) {
                mbar_expect_tx(sb + B_SC + 8 * ((s + 1) & 1), 2560);
                if (rank < 2) mbar_expect_tx(sb + B_V + 8 * ((s + 1) & 1), 8192 + 2048);
            }
            if (warp == 3) {
                const int g = lane >> 2, t = lane & 3;
                mbar_wait(sb + B_SC + 8 * (s & 1), (s >> 1) & 1);
                TR(5);
                const float* sa = reinterpret_cast<const float*>(smem + SM_SC + (s & 1) * 2560) + g * 40 + 2 * t;
                float v[5][2];
                float mx = -3.0e38f;
                #pragma unroll
                for (int q = 0; q < 5; q++) {
                    float2 x0 = *reinterpret_cast<const float2*>(sa + 8 * q), x1 = *reinterpret_cast<const float2*>(sa + 320 + 8 * q);
                    v[q][0] = (x0.x + x1.x) * (0.08838834764831845f * 1.4426950408889634f);
                    v[q][1] = (x0.y + x1.y) * (0.08838834764831845f * 1.4426950408889634f);
                    mx = fmaxf(mx, fmaxf(v[q][0], v[q][1]));
                }
                mx = fmaxf(mx, __shfl_xor_sync(~0u, mx, 1));
                mx = fmaxf(mx, __shfl_xor_sync(~0u, mx, 2));
                float sum = 0.f;
                #pragma unroll
                for (int q = 0; q < 5; q++) { v[q][0] = ex2_approx(v[q][0] - mx); v[q][1] = ex2_approx(v[q][1] - mx); sum += v[q][0] + v[q][1]; }
                sum += __shfl_xor_sync(~0u, sum, 1);
                sum += __shfl_xor_sync(~0u, sum, 2);
                float inv = __frcp_rn(sum);
                uint32_t* pbs = reinterpret_cast<uint32_t*>(smem + SM_PB);
                #pragma unroll
                for (int q = 0; q < 5; q++) pbs[q * 32 + lane] = pack_bf16(v[q][0] * inv, v[q][1] * inv);
                mbar_arrive(sb + B_P);
            }
            nbar_sync(3, 384);
            const uint32_t tg = tag_of(s);
            if (cta < NRED) {
                const uint32_t* base = &g_pm[s & 1][cta][warp * 8 + (lane >> 4)][(lane & 15) * 4];
                uint4 v[4]; int guard = 0;
                #pragma unroll
                for (int j = 0; j < 4; j++) v[j] = make_uint4(0, 0, 0, 0);
                uint32_t pend = 0xF;
                do {
                    #pragma unroll
                    for (int j = 0; j < 4; j++) if (pend & (1u << j)) v[j] = ld_relaxed4(base + j * 128);
                    #pragma unroll
                    for (int j = 0; j < 4; j++)
                        if (((v[j].x & 3) == tg) && ((v[j].y & 3) == tg) && ((v[j].z & 3) == tg) && ((v[j].w & 3) == tg)) pend &= ~(1u << j);
                } while (__any_sync(~0u, pend != 0) && ++guard < (1 << 20));
                if (warp == 0) TR(9);
                float a0 = 0, a1 = 0, a2 = 0, a3 = 0;
                #pragma unroll
                for (int j = 0; j < 4; j++) { a0 += __uint_as_float(v[j].x); a1 += __uint_as_float(v[j].y); a2 += __uint_as_float(v[j].z); a3 += __uint_as_float(v[j].w); }
                a0 += __shfl_xor_sync(~0u, a0, 16); a1 += __shfl_xor_sync(~0u, a1, 16); a2 += __shfl_xor_sync(~0u, a2, 16); a3 += __shfl_xor_sync(~0u, a3, 16);
                float* cr = reinterpret_cast<float*>(smem + SM_CRED);
                if (lane < 16) *reinterpret_cast<float4*>(cr + warp * 64 + lane * 4) = make_float4(a0, a1, a2, a3);
                nbar_sync(4, 128);
                {
                    int rho = lane >> 2, pp = lane & 3;
                    int i0 = ((2 * pp) * 4 + (rho >> 1)) * 2 + (rho & 1), i1 = i0 + 8;
                    float lo = cr[i0] + cr[64 + i0] + cr[128 + i0] + cr[192 + i0];
                    float hi = cr[i1] + cr[64 + i1] + cr[128 + i1] + cr[192 + i1];
                    uint32_t wv = pack_bf16(lo, hi);
                    if (wv == 0) wv = 0x8000u;
                    if (warp == 0) TR(10);
                    st_relaxed1(&g_memx[(s + 1) & 3][warp][cta * 32 + lane], wv);
                    st_relaxed1(&g_memx[(s + 1) & 3][warp + 4][cta * 32 + lane], wv);
                    st_relaxed1(&g_memx[s & 3][warp][cta * 32 + lane], 0u);
                    st_relaxed1(&g_memx[s & 3][warp + 4][cta * 32 + lane], 0u);
                }
            }
            {
                const int c0 = (ct >> 6) * 320 + (ct & 63);
                const uint32_t* mb = &g_memx[(s + 1) & 3][h & (NREP - 1)][c0 * 4];
                uint4 v[5]; int guard = 0;
                #pragma unroll
                for (int j = 0; j < 5; j++) v[j] = make_uint4(0, 0, 0, 0);
                uint32_t pend = 0x1F;
                do {
                    #pragma unroll
                    for (int j = 0; j < 5; j++) if (pend & (1u << j)) v[j] = ld_relaxed4(mb + j * 256);
                    #pragma unroll
                    for (int j = 0; j < 5; j++) if (v[j].x && v[j].y && v[j].z && v[j].w) pend &= ~(1u << j);
                } while (__any_sync(~0u, pend != 0) && ++guard < (1 << 20));
                #pragma unroll
                for (int j = 0; j < 5; j++) *reinterpret_cast<uint4*>(smem + SM_MEMB + (c0 + 64 * j) * 16) = v[j];
                if (warp == 0) TR(11);
                if (warp == 3) TR(12);
                mbar_arrive(sb + B_MEM + 8 * (ct >> 6));
            }
        }
        nbar_sync(3, 384);
        if (ct == 0) { __threadfence(); unsigned old = atomicAdd(&g_done, 1u); *reinterpret_cast<volatile int*>(smem + SM_CRED) = (old == 95); }
        nbar_sync(4, 128);
        if (*reinterpret_cast<volatile int*>(smem + SM_CRED)) {
            for (int i = ct; i < NREP * 2560; i += 128) (&g_memx[(NSEG - 1) & 3][0][0])[i] = 0u;
            if (ct == 0) g_done = 0;
        }
        __syncwarp();
        cluster_sync_all();
    } else {
        asm volatile("setmaxnreg.inc.sync.aligned.u32 232;");
        const int wtid = tid & 127;
        const int cw = wg * 4 + warp;
        uint32_t areg[2][20][4];
        #pragma unroll
        for (int mt = 0; mt < 2; mt++)
            #pragma unroll
            for (int kk = 0; kk < 20; kk++) {
                int mi = lane >> 3;
                int row = 16 * (20 * wg + kk) + (mi >> 1) * 8 + (lane & 7);
                int chunk = 2 * warp + (mi & 1);
                ldsm4t(areg[mt][kk], sb + mt * 81920 + row * 128 + ((chunk ^ (row & 7)) << 4));
            }
        nbar_sync(5, 384);
        nbar_sync(5, 384);
        cluster_sync_all();

        for (int s = -1; s < NSEG; s++) {
            const int sl = s & 1;
            if (s >= 0) {
            if (s > 0) mbar_wait(sb + B_MEM + 8 * wg, (s - 1) & 1);
            if (cw == 0) TR(0);
            float fin[4];
            {
                float acc[2][2][4];
                #pragma unroll
                for (int i = 0; i < 2; i++)
                    #pragma unroll
                    for (int j = 0; j < 2; j++) { acc[i][j][0] = acc[i][j][1] = acc[i][j][2] = acc[i][j][3] = 0.f; }
                uint32_t b[3][4];
                const uint32_t mb = sb + SM_MEMB + (20 * wg) * 256 + lane * 16;
                ldsm4(b[0], mb); ldsm4(b[1], mb + 512);
                #pragma unroll
                for (int kp = 0; kp < 10; kp++) {
                    if (kp + 2 < 10) ldsm4(b[(kp + 2) % 3], mb + (kp + 2) * 512);
                    const uint32_t (&bb)[4] = b[kp % 3];
                    mma_bf16(acc[0][0], areg[0][2 * kp][0], areg[0][2 * kp][1], areg[0][2 * kp][2], areg[0][2 * kp][3], bb[0], bb[1]);
                    mma_bf16(acc[1][0], areg[1][2 * kp][0], areg[1][2 * kp][1], areg[1][2 * kp][2], areg[1][2 * kp][3], bb[0], bb[1]);
                    mma_bf16(acc[0][1], areg[0][2 * kp + 1][0], areg[0][2 * kp + 1][1], areg[0][2 * kp + 1][2], areg[0][2 * kp + 1][3], bb[2], bb[3]);
                    mma_bf16(acc[1][1], areg[1][2 * kp + 1][0], areg[1][2 * kp + 1][1], areg[1][2 * kp + 1][2], areg[1][2 * kp + 1][3], bb[2], bb[3]);
                }
                float4* red = reinterpret_cast<float4*>(smem + SM_RED);
                float m0[4], m1[4];
                #pragma unroll
                for (int i = 0; i < 4; i++) { m0[i] = acc[0][0][i] + acc[0][1][i]; m1[i] = acc[1][0][i] + acc[1][1][i]; }
                red[(wg ^ 1) * 128 + wtid] = wg == 0 ? make_float4(m1[0], m1[1], m1[2], m1[3]) : make_float4(m0[0], m0[1], m0[2], m0[3]);
                nbar_sync(1, 256);
                float4 r = red[wg * 128 + wtid];
                fin[0] = (wg == 0 ? m0[0] : m1[0]) + r.x; fin[1] = (wg == 0 ? m0[1] : m1[1]) + r.y;
                fin[2] = (wg == 0 ? m0[2] : m1[2]) + r.z; fin[3] = (wg == 0 ? m0[3] : m1[3]) + r.w;
            }
            if (cw == 0) TR(1);
            {
                uint32_t p0 = pack_bf16(fin[0], fin[1]), p1 = pack_bf16(fin[2], fin[3]);
                uint32_t dst = (rank == 2) ? sb + SM_VT + sl * 10240 + wg * 5120 : (wg == 0 ? sb + SM_QS : sb + SM_KT + sl * 5120);
                int r = lane & 7, chunk = 2 * warp + ((lane >> 3) & 1);
                stsm2t(dst + r * 128 + ((chunk ^ r) << 4), p0, p1);
            }
            fence_async();
            nbar_sync(1, 256);
            if (cw == 0) TR(2);
            if (rank == 2) {
                if (lane == 0) {
                    if (cw < 4) {
                        if (s < NSEG - 1) {
                            const uint32_t off = SM_VT + sl * 10240 + (cw & 1) * 5120;
                            const uint32_t rb = mapa(sb, cw >> 1);
                            bulk_s2c(rb + off, sb + off, 1024, rb + B_V + 8 * sl);
                        }
                    } else if (cw < 6) {
                        bulk_s2g(g_VMimg + ((size_t)(s * NH + h) * 2 + (cw & 1)) * 512, sb + SM_VT + sl * 10240 + (cw & 1) * 5120, 1024);
                        bulk_commit();
                    }
                }
            } else {
                if (cw == 7 && lane == 0) { bulk_s2g(g_KMimg + ((size_t)(s * NH + h) * 2 + rank) * 512, sb + SM_KT + sl * 5120, 1024); bulk_commit(); }
                if (s < NSEG - 1 && cw < 5) {
                    float sc[4] = {0, 0, 0, 0};
                    const int r = lane & 7;
                    #pragma unroll
                    for (int j = 0; j < 2; j++) {
                        uint32_t qa[4], kb[4];
                        int chunk = (lane >> 3) + 4 * j;
                        ldsm4(qa, sb + SM_QS + r * 128 + ((chunk ^ r) << 4));
                        ldsm4(kb, sb + SM_KT + sl * 5120 + (8 * cw + r) * 128 + ((chunk ^ r) << 4));
                        mma_bf16(sc, qa[0], 0u, qa[1], 0u, kb[0], kb[1]);
                        mma_bf16(sc, qa[2], 0u, qa[3], 0u, kb[2], kb[3]);
                    }
                    float o0 = __shfl_down_sync(~0u, sc[0], 1), o1 = __shfl_down_sync(~0u, sc[1], 1);
                    if ((lane & 1) == 0) {
                        const uint32_t a = SM_SC + sl * 2560 + rank * 1280 + ((lane >> 2) * 40 + 8 * cw + 2 * (lane & 3)) * 4;
                        const uint32_t bo = B_SC + 8 * sl;
                        #pragma unroll
                        for (int d = 0; d < 3; d++) { const uint32_t rb = mapa(sb, d); st_async4(rb + a, sc[0], sc[1], o0, o1, rb + bo); }
                    }
                }
            }
            if (s == NSEG - 1) break;
            if (cw == 0) TR(3);
            if (rank < 2) mbar_wait(sb + B_V + 8 * sl, (s >> 1) & 1);
            if (cw == 0) TR(4);
            {
                const int tile0 = (rank == 2) ? 0 : (rank == 0 ? 4 : 7);
                if (wg == 0 || rank == 2) u_pass<2>(smem, sb, s, h, wg, warp, lane, tile0);
                else                      u_pass<1>(smem, sb, s, h, wg, warp, lane, tile0);
            }
            if (cw == 0) TR(7);
            nbar_arrive(3, 384);
            if (lane == 0 && cw >= 4 && (rank == 2 ? cw < 6 : cw == 7)) signal_export(&g_flag[s][h]);
            }
            {
                const int sn = s + 1, sln = sn & 1;
                mbar_wait(sb + B_X + 8 * sln, (sn >> 1) & 1);
                float acc[2][16];
                wg_fence();
                #pragma unroll
                for (int mt = 0; mt < 2; mt++)
                    #pragma unroll
                    for (int kk = 0; kk < 20; kk++) {
                        uint64_t db = make_desc(sb + SM_XB + sln * 40960 + (5 * wg + (kk >> 2)) * 4096 + (kk & 3) * 32, 16, 1024);
                        wgmma_n32_rs(acc[mt], areg[mt][kk], db, kk > 0);
                    }
                wg_commit();
                wg_wait0();
                float4* red = reinterpret_cast<float4*>(smem + SM_RED);
                #pragma unroll
                for (int j = 0; j < 4; j++) {
                    red[((wg ^ 1) * 4 + j) * 128 + wtid] = make_float4(wg == 0 ? acc[1][4 * j] : acc[0][4 * j], wg == 0 ? acc[1][4 * j + 1] : acc[0][4 * j + 1],
                                                                       wg == 0 ? acc[1][4 * j + 2] : acc[0][4 * j + 2], wg == 0 ? acc[1][4 * j + 3] : acc[0][4 * j + 3]);
                }
                if (lane == 0 && cw < 2 && sn > 0) signal_export(&g_flag[sn - 1][h]);
                if (lane == 0 && cw < 4) bulk_wait_read0();
                nbar_sync(1, 256);
                if (cw == 0 && lane == 0 && sn + 2 < NSEG) {
                    mbar_expect_tx(sb + B_X + 8 * sln, 40960);
                    for (int c = 0; c < 10; c++) tma_load_2d(sb + SM_XB + sln * 40960 + c * 4096, &xmap, c * 64, (sn + 2) * 32, sb + B_X + 8 * sln);
                }
                uint32_t pk[8];
                #pragma unroll
                for (int j = 0; j < 4; j++) {
                    float4 r = red[(wg * 4 + j) * 128 + wtid];
                    pk[2 * j] = pack_bf16((wg == 0 ? acc[0][4 * j] : acc[1][4 * j]) + r.x, (wg == 0 ? acc[0][4 * j + 1] : acc[1][4 * j + 1]) + r.y);
                    pk[2 * j + 1] = pack_bf16((wg == 0 ? acc[0][4 * j + 2] : acc[1][4 * j + 2]) + r.z, (wg == 0 ? acc[0][4 * j + 3] : acc[1][4 * j + 3]) + r.w);
                }
                const uint32_t dst = (rank == 2) ? sb + SM_VT + sln * 10240 + wg * 5120 + 1024 : (wg == 0 ? sb + SM_QT : sb + SM_KT + sln * 5120 + 1024);
                #pragma unroll
                for (int jj = 0; jj < 2; jj++) {
                    int mi = lane >> 3, tok = 8 * (2 * jj + (mi >> 1)) + (lane & 7), chunk = 2 * warp + (mi & 1);
                    stsm4t(dst + tok * 128 + ((chunk ^ (tok & 7)) << 4), pk[4 * jj], pk[4 * jj + 1], pk[4 * jj + 2], pk[4 * jj + 3]);
                }
                fence_async();
                nbar_sync(1, 256);
                if (lane == 0 && cw < 4) {
                    const size_t img = ((size_t)(sn * NH + h) * 2) * 2048;
                    if (rank == 2) {
                        const uint32_t off = SM_VT + sln * 10240 + (cw & 1) * 5120 + 1024;
                        if (sn < NSEG - 1) { const uint32_t rb = mapa(sb, cw >> 1); bulk_s2c(rb + off, sb + off, 4096, rb + B_V + 8 * sln); }
                        if (cw < 2) { bulk_s2g(g_Vimg + img + cw * 2048, sb + off, 4096); bulk_commit(); }
                    } else if (cw == 0) {
                        bulk_s2g(g_Qimg + img + rank * 2048, sb + SM_QT, 4096); bulk_commit();
                    } else if (cw == 1) {
                        bulk_s2g(g_Kimg + img + rank * 2048, sb + SM_KT + sln * 5120 + 1024, 4096); bulk_commit();
                    }
                }
                if (cw == 0 && s >= 0) TR(13);
            }
        }
        if (lane == 0 && cw < 2) signal_export(&g_flag[NSEG - 1][h]);
        if (lane == 0 && cw >= 4 && (rank == 2 ? cw < 6 : cw == 7)) signal_export(&g_flag[NSEG - 1][h]);
        nbar_arrive(3, 384);
        __syncwarp();
        cluster_sync_all();
    }
}

#define NAUX 36
__device__ __align__(1024) bf16 g_Oimg[16 * 64 * 128 * 64];
__device__ float    g_acc[SEQ * DM];
__device__ unsigned g_ocnt[16];
__device__ unsigned g_gcnt[16][5];
__device__ unsigned g_ssmcnt, g_auxdone, g_epoch;

__device__ __forceinline__ unsigned ld_acquire(const unsigned* p) { unsigned v; asm volatile("ld.acquire.gpu.global.u32 %0, [%1];" : "=r"(v) : "l"(p) : "memory"); return v; }
__device__ __forceinline__ void wait_counter(const unsigned* p, unsigned target) {
    int guard = 0;
    while ((int)(ld_acquire(p) - target) < 0 && ++guard < (1 << 24)) __nanosleep(64);
}
__device__ __forceinline__ void fence_async_all() { asm volatile("fence.proxy.async;" ::: "memory"); }
__device__ __forceinline__ void wgmma_n128_tB(float (&d)[64], uint64_t da, uint64_t db, int scale_d) {
    asm volatile("{\n.reg .pred p;\nsetp.ne.b32 p, %66, 0;\n"
        "wgmma.mma_async.sync.aligned.m64n128k16.f32.bf16.bf16 "
        "{%0,%1,%2,%3,%4,%5,%6,%7,%8,%9,%10,%11,%12,%13,%14,%15,%16,%17,%18,%19,%20,%21,%22,%23,%24,%25,%26,%27,%28,%29,%30,%31,"
        "%32,%33,%34,%35,%36,%37,%38,%39,%40,%41,%42,%43,%44,%45,%46,%47,%48,%49,%50,%51,%52,%53,%54,%55,%56,%57,%58,%59,%60,%61,%62,%63}, %64, %65, p, 1, 1, 0, 1;\n}\n"
        : "+f"(d[0]), "+f"(d[1]), "+f"(d[2]), "+f"(d[3]), "+f"(d[4]), "+f"(d[5]), "+f"(d[6]), "+f"(d[7]),
          "+f"(d[8]), "+f"(d[9]), "+f"(d[10]), "+f"(d[11]), "+f"(d[12]), "+f"(d[13]), "+f"(d[14]), "+f"(d[15]),
          "+f"(d[16]), "+f"(d[17]), "+f"(d[18]), "+f"(d[19]), "+f"(d[20]), "+f"(d[21]), "+f"(d[22]), "+f"(d[23]),
          "+f"(d[24]), "+f"(d[25]), "+f"(d[26]), "+f"(d[27]), "+f"(d[28]), "+f"(d[29]), "+f"(d[30]), "+f"(d[31]),
          "+f"(d[32]), "+f"(d[33]), "+f"(d[34]), "+f"(d[35]), "+f"(d[36]), "+f"(d[37]), "+f"(d[38]), "+f"(d[39]),
          "+f"(d[40]), "+f"(d[41]), "+f"(d[42]), "+f"(d[43]), "+f"(d[44]), "+f"(d[45]), "+f"(d[46]), "+f"(d[47]),
          "+f"(d[48]), "+f"(d[49]), "+f"(d[50]), "+f"(d[51]), "+f"(d[52]), "+f"(d[53]), "+f"(d[54]), "+f"(d[55]),
          "+f"(d[56]), "+f"(d[57]), "+f"(d[58]), "+f"(d[59]), "+f"(d[60]), "+f"(d[61]), "+f"(d[62]), "+f"(d[63])
        : "l"(da), "l"(db), "r"(scale_d));
}
__device__ __forceinline__ void stsm4(uint32_t addr, uint32_t r0, uint32_t r1, uint32_t r2, uint32_t r3) {
    asm volatile("stmatrix.sync.aligned.m8n8.x4.shared.b16 [%0], {%1,%2,%3,%4};" :: "r"(addr), "r"(r0), "r"(r1), "r"(r2), "r"(r3) : "memory");
}

#define AX_BAR   0
#define AX_DATA  1024
#define AX_UNIT  28672
#define AX_STAGE 32768
#define AX_TOTAL (AX_DATA + 4 * AX_STAGE > (int)sizeof(SsmSmem) + AX_DATA ? AX_DATA + 4 * AX_STAGE : (int)sizeof(SsmSmem) + AX_DATA)

__device__ __noinline__ void attn_task(unsigned char* smem, int s, int hg, uint32_t& ph_att, unsigned epoch) {
    const uint32_t sb = smem_u32(smem);
    const int tid = threadIdx.x, warp = tid >> 5, lane = tid & 31, g = lane >> 2, t = lane & 3;
    __syncthreads();
    if (tid < 4) {
        const int h = 4 * hg + tid;
        wait_counter(&g_flag[s][h], (epoch + 1) * 10u);
        fence_async_all();
    }
    __syncthreads();
    if (tid == 0) {
        fence_async_all();
        mbar_expect_tx(sb + AX_BAR, 4 * AX_UNIT);
        for (int u = 0; u < 4; u++) {
            const int h = 4 * hg + u;
            const uint32_t ub = sb + AX_DATA + u * AX_UNIT;
            const size_t img = ((size_t)(s * NH + h) * 2);
            for (int hf = 0; hf < 2; hf++) {
                bulk_g2s(ub + hf * 4096, g_Qimg + (img + hf) * 2048, 4096, sb + AX_BAR);
                bulk_g2s(ub + 8192 + hf * 5120, g_KMimg + (img + hf) * 512, 1024, sb + AX_BAR);
                bulk_g2s(ub + 8192 + hf * 5120 + 1024, g_Kimg + (img + hf) * 2048, 4096, sb + AX_BAR);
                bulk_g2s(ub + 18432 + hf * 5120, g_VMimg + (img + hf) * 512, 1024, sb + AX_BAR);
                bulk_g2s(ub + 18432 + hf * 5120 + 1024, g_Vimg + (img + hf) * 2048, 4096, sb + AX_BAR);
            }
        }
    }
    mbar_wait(sb + AX_BAR, ph_att); ph_att ^= 1;
    const int u = warp >> 1, qh = warp & 1, h = 4 * hg + u;
    const uint32_t ub = sb + AX_DATA + u * AX_UNIT;
    float sc[5][4];
    #pragma unroll
    for (int j = 0; j < 5; j++) { sc[j][0] = sc[j][1] = sc[j][2] = sc[j][3] = 0.f; }
    #pragma unroll
    for (int ks = 0; ks < 8; ks++) {
        const int hf = ks >> 2, c0 = (ks & 3) * 2;
        uint32_t a[4];
        { int mi = lane >> 3, row = 16 * qh + (mi & 1) * 8 + (lane & 7), chunk = c0 + (mi >> 1);
          ldsm4(a, ub + hf * 4096 + row * 128 + ((chunk ^ (row & 7)) << 4)); }
        #pragma unroll
        for (int jp = 0; jp < 3; jp++) {
            uint32_t b[4];
            int mi = lane >> 3, nt = 2 * jp + (mi >> 1); if (nt > 4) nt = 4;
            int row = 8 * nt + (lane & 7), chunk = c0 + (mi & 1);
            ldsm4(b, ub + 8192 + hf * 5120 + row * 128 + ((chunk ^ (row & 7)) << 4));
            mma_bf16(sc[2 * jp], a[0], a[1], a[2], a[3], b[0], b[1]);
            if (jp < 2) mma_bf16(sc[2 * jp + 1], a[0], a[1], a[2], a[3], b[2], b[3]);
        }
    }
    uint32_t pa[3][4];
    {
        const float sc2 = 0.08838834764831845f * 1.4426950408889634f;
        float mx0 = -3.0e38f, mx1 = -3.0e38f;
        const int q0 = 16 * qh + g, q1 = q0 + 8;
        #pragma unroll
        for (int j = 0; j < 5; j++)
            #pragma unroll
            for (int e = 0; e < 2; e++) {
                int key = 8 * j + 2 * t + e - 8;
                sc[j][e] = (key <= q0) ? sc[j][e] * sc2 : -3.0e38f;
                sc[j][2 + e] = (key <= q1) ? sc[j][2 + e] * sc2 : -3.0e38f;
                mx0 = fmaxf(mx0, sc[j][e]); mx1 = fmaxf(mx1, sc[j][2 + e]);
            }
        mx0 = fmaxf(mx0, __shfl_xor_sync(~0u, mx0, 1)); mx0 = fmaxf(mx0, __shfl_xor_sync(~0u, mx0, 2));
        mx1 = fmaxf(mx1, __shfl_xor_sync(~0u, mx1, 1)); mx1 = fmaxf(mx1, __shfl_xor_sync(~0u, mx1, 2));
        float s0 = 0.f, s1 = 0.f;
        #pragma unroll
        for (int j = 0; j < 5; j++)
            #pragma unroll
            for (int e = 0; e < 2; e++) {
                sc[j][e] = ex2_approx(sc[j][e] - mx0); sc[j][2 + e] = ex2_approx(sc[j][2 + e] - mx1);
                s0 += sc[j][e]; s1 += sc[j][2 + e];
            }
        s0 += __shfl_xor_sync(~0u, s0, 1); s0 += __shfl_xor_sync(~0u, s0, 2);
        s1 += __shfl_xor_sync(~0u, s1, 1); s1 += __shfl_xor_sync(~0u, s1, 2);
        const float i0 = __frcp_rn(s0), i1 = __frcp_rn(s1);
        #pragma unroll
        for (int k = 0; k < 3; k++) {
            pa[k][0] = pack_bf16(sc[2 * k][0] * i0, sc[2 * k][1] * i0);
            pa[k][1] = pack_bf16(sc[2 * k][2] * i1, sc[2 * k][3] * i1);
            if (k < 2) { pa[k][2] = pack_bf16(sc[2 * k + 1][0] * i0, sc[2 * k + 1][1] * i0); pa[k][3] = pack_bf16(sc[2 * k + 1][2] * i1, sc[2 * k + 1][3] * i1); }
            else { pa[k][2] = 0u; pa[k][3] = 0u; }
        }
    }
    __syncwarp();
    nbar_sync(1 + u, 64);
    #pragma unroll
    for (int np = 0; np < 8; np++) {
        const int hf = np >> 2, c0 = (np & 3) * 2;
        float o0[4] = {0, 0, 0, 0}, o1[4] = {0, 0, 0, 0};
        #pragma unroll
        for (int k = 0; k < 3; k++) {
            uint32_t b[4];
            int mi = lane >> 3;
            int row = 16 * k + (mi & 1) * 8 + (lane & 7); if (row > 39) row = 39 - 7 + (lane & 7);
            int chunk = c0 + (mi >> 1);
            ldsm4t(b, ub + 18432 + hf * 5120 + row * 128 + ((chunk ^ (row & 7)) << 4));
            mma_bf16(o0, pa[k][0], pa[k][1], pa[k][2], pa[k][3], b[0], k < 2 ? b[1] : 0u);
            mma_bf16(o1, pa[k][0], pa[k][1], pa[k][2], pa[k][3], b[2], k < 2 ? b[3] : 0u);
        }
        int mi = lane >> 3, row = 16 * qh + (mi & 1) * 8 + (lane & 7), chunk = c0 + (mi >> 1);
        stsm4(ub + hf * 4096 + row * 128 + ((chunk ^ (row & 7)) << 4), pack_bf16(o0[0], o0[1]), pack_bf16(o0[2], o0[3]), pack_bf16(o1[0], o1[1]), pack_bf16(o1[2], o1[3]));
    }
    fence_async();
    __syncthreads();
    if (tid < 8) {
        const int uu = tid >> 1, hf = tid & 1, hh = 4 * hg + uu;
        bulk_s2g(g_Oimg + (((size_t)(s >> 2) * 64 + hh * 2 + hf) * 128 + (s & 3) * 32) * 64, sb + AX_DATA + uu * AX_UNIT + hf * 4096, 4096);
        bulk_commit();
        bulk_wait0();
        fence_async_all();
        __threadfence();
    }
    __syncthreads();
    if (tid == 0) atomicAdd(&g_ocnt[s >> 2], 1u);
    (void)h;
}

__device__ __forceinline__ void gemm_task(unsigned char* smem, const CUtensorMap* womap, int m, int c, int kq, uint32_t& ph_g, unsigned epoch,
                                       bf16* __restrict__ out) {
    const uint32_t sb = smem_u32(smem);
    const int tid = threadIdx.x, lane = tid & 31;
    const int wg = __shfl_sync(~0u, tid >> 7, 0), warp = __shfl_sync(~0u, (tid >> 5) & 3, 0);
    __syncthreads();
    if (tid == 0) { wait_counter(&g_ocnt[m], (epoch + 1) * 32u); fence_async_all(); }
    __syncthreads();
    auto load = [&](int kc) {
        const int st = kc & 3;
        const uint32_t a = sb + AX_DATA + st * AX_STAGE, bar = sb + AX_BAR + 8 + 8 * st;
        mbar_expect_tx(bar, AX_STAGE);
        bulk_g2s(a, g_Oimg + ((size_t)m * 64 + kq * 16 + kc) * 8192, 16384, bar);
        tma_load_2d(a + 16384, womap, c * 128, kq * 1024 + kc * 64, bar);
        tma_load_2d(a + 16384 + 8192, womap, c * 128 + 64, kq * 1024 + kc * 64, bar);
    };
    if (tid == 0) { load(0); load(1); load(2); }
    float acc[64];
    #pragma unroll
    for (int i = 0; i < 64; i++) acc[i] = 0.f;
    for (int kc = 0; kc < 16; kc++) {
        const int st = kc & 3;
        mbar_wait(sb + AX_BAR + 8 + 8 * st, (ph_g >> st) & 1);
        ph_g ^= 1u << st;
        const uint32_t a = sb + AX_DATA + st * AX_STAGE;
        wg_fence();
        #pragma unroll
        for (int ks = 0; ks < 4; ks++)
            wgmma_n128_tB(acc, make_desc(a + wg * 8192 + ks * 32, 16, 1024), make_desc(a + 16384 + ks * 2048, 8192, 1024), 1);
        wg_commit();
        asm volatile("wgmma.wait_group.sync.aligned 1;" ::: "memory");
        __syncthreads();
        if (tid == 0 && kc + 3 < 16) load(kc + 3);
    }
    wg_wait0();
    {
        const int g = lane >> 2, t = lane & 3;
        float* base = g_acc + (size_t)(m * 128 + wg * 64 + warp * 16 + g) * DM + c * 128 + 2 * t;
        #pragma unroll
        for (int j = 0; j < 16; j++) {
            asm volatile("red.global.add.v2.f32 [%0], {%1,%2};" :: "l"(base + j * 8), "f"(acc[4 * j]), "f"(acc[4 * j + 1]) : "memory");
            asm volatile("red.global.add.v2.f32 [%0], {%1,%2};" :: "l"(base + 8 * DM + j * 8), "f"(acc[4 * j + 2]), "f"(acc[4 * j + 3]) : "memory");
        }
    }
    __threadfence();
    __syncthreads();
    __shared__ int s_last;
    if (tid == 0) { unsigned old = atomicAdd(&g_gcnt[m][c], 1u); s_last = ((old + 1) == (epoch + 1) * 4u); if (s_last) wait_counter(&g_ssmcnt, (epoch + 1) * NAUX); __threadfence(); }
    __syncthreads();
    if (s_last) {
        for (int i = tid; i < 128 * 32; i += 256) {
            const int r = m * 128 + (i >> 5), cc = c * 128 + (i & 31) * 4;
            float4* pa = reinterpret_cast<float4*>(g_acc + (size_t)r * DM + cc);
            float4 a; asm volatile("ld.relaxed.gpu.global.v4.f32 {%0,%1,%2,%3}, [%4];" : "=f"(a.x), "=f"(a.y), "=f"(a.z), "=f"(a.w) : "l"(pa) : "memory");
            *pa = make_float4(0.f, 0.f, 0.f, 0.f);
            float gt; asm volatile("ld.relaxed.gpu.global.f32 %0, [%1];" : "=f"(gt) : "l"(g_g + r) : "memory");
            uint2 bb; asm volatile("ld.relaxed.gpu.global.v2.u32 {%0,%1}, [%2];" : "=r"(bb.x), "=r"(bb.y) : "l"(g_b + (size_t)r * DM + cc) : "memory");
            const float b0 = __uint_as_float(bb.x << 16), b1 = __uint_as_float(bb.x & 0xffff0000u), b2 = __uint_as_float(bb.y << 16), b3 = __uint_as_float(bb.y & 0xffff0000u);
            uint2 o; o.x = pack_bf16(gt * a.x + (1.f - gt) * b0, gt * a.y + (1.f - gt) * b1); o.y = pack_bf16(gt * a.z + (1.f - gt) * b2, gt * a.w + (1.f - gt) * b3);
            *reinterpret_cast<uint2*>(out + (size_t)r * DM + cc) = o;
        }
    }
}

__global__ void __launch_bounds__(256, 1)
k_aux(const __grid_constant__ CUtensorMap womap, const bf16* __restrict__ x, const bf16* __restrict__ A_re, const bf16* __restrict__ A_im,
      const bf16* __restrict__ B_re, const bf16* __restrict__ B_im, const bf16* __restrict__ C_re, const bf16* __restrict__ C_im,
      const bf16* __restrict__ log_dt, const bf16* __restrict__ Dskip, const bf16* __restrict__ gw, bf16* __restrict__ out) {
    extern __shared__ __align__(1024) unsigned char smem[];
    const uint32_t sb = smem_u32(smem);
    const int tid = threadIdx.x, warp = tid >> 5, lane = tid & 31, cta = blockIdx.x;
    __shared__ unsigned s_epoch;
    if (tid == 0) {
        for (int i = 0; i < 5; i++) mbar_init(sb + AX_BAR + 8 * i, 1);
        asm volatile("fence.mbarrier_init.release.cluster;" ::: "memory");
        s_epoch = *reinterpret_cast<volatile unsigned*>(&g_epoch);
    }
    __syncthreads();
    const unsigned epoch = s_epoch;
    for (int r = cta * 8 + warp; r < SEQ; r += NAUX * 8) {
        float sum = 0.f;
        for (int i = lane * 2; i < DM; i += 64) {
            __nv_bfloat162 xv = *reinterpret_cast<const __nv_bfloat162*>(x + (size_t)r * DM + i), wv = *reinterpret_cast<const __nv_bfloat162*>(gw + i);
            sum += bf2f(xv.x) * bf2f(wv.x) + bf2f(xv.y) * bf2f(wv.y);
        }
        #pragma unroll
        for (int o = 16; o; o >>= 1) sum += __shfl_xor_sync(~0u, sum, o);
        if (lane == 0) g_g[r] = 1.f / (1.f + expf(-sum));
    }
    for (int grp = cta; grp < DM / SSM_CH; grp += NAUX) ssm_group(smem + AX_DATA, grp, x, A_re, A_im, B_re, B_im, C_re, C_im, log_dt, Dskip);
    __threadfence();
    __syncthreads();
    if (tid == 0) atomicAdd(&g_ssmcnt, 1u);
    uint32_t ph_att = 0, ph_g = 0;
    for (int task = cta; task < 16 * 52; task += NAUX) {
        const int m = task / 52, i = task % 52;
        if (i < 32) attn_task(smem, m * 4 + (i >> 3), i & 7, ph_att, epoch);
        else { const int j = i - 32; gemm_task(smem, &womap, m, j % 5, j / 5, ph_g, epoch, out); }
    }
    __syncthreads();
    if (tid == 0) {
        __threadfence();
        unsigned old = atomicAdd(&g_auxdone, 1u);
        if (old == NAUX - 1) { g_auxdone = 0; __threadfence(); atomicAdd(&g_epoch, 1u); }
    }
    asm volatile("griddepcontrol.wait;" ::: "memory");
}

extern "C" void kernel_launch(void* const* d_in, const int* in_sizes, int n_in, void* d_out, int out_size) {
    const bf16* x = (const bf16*)d_in[0];
    const bf16* mem0 = (const bf16*)d_in[1];
    const bf16* Wq = (const bf16*)d_in[2];
    const bf16* Wk = (const bf16*)d_in[3];
    const bf16* Wv = (const bf16*)d_in[4];
    const bf16* Wo = (const bf16*)d_in[5];
    const bf16 *A_re = (const bf16*)d_in[8], *A_im = (const bf16*)d_in[9], *B_re = (const bf16*)d_in[10], *B_im = (const bf16*)d_in[11];
    const bf16 *C_re = (const bf16*)d_in[12], *C_im = (const bf16*)d_in[13], *log_dt = (const bf16*)d_in[14], *Dskip = (const bf16*)d_in[15];
    const bf16* gw = (const bf16*)d_in[16];
    bf16* out = (bf16*)d_out;
    cudaStream_t st = cudaStreamPerThread;
    static bool init = false;
    static CUtensorMap xmap, womap;
    static const void* xmap_ptr = nullptr; static const void* womap_ptr = nullptr;
    if (!init) {
        cudaFuncSetAttribute(k_chain, cudaFuncAttributeMaxDynamicSharedMemorySize, SM_TOTAL);
        cudaFuncSetAttribute(k_aux, cudaFuncAttributeMaxDynamicSharedMemorySize, AX_TOTAL);
        init = true;
    }
    if (xmap_ptr != (const void*)x || womap_ptr != (const void*)Wo) {
        void* fn = nullptr; cudaDriverEntryPointQueryResult qres;
        cudaGetDriverEntryPoint("cuTensorMapEncodeTiled", &fn, cudaEnableDefault, &qres);
        typedef CUresult (*EncFn)(CUtensorMap*, CUtensorMapDataType, cuuint32_t, void*, const cuuint64_t*, const cuuint64_t*, const cuuint32_t*, const cuuint32_t*,
                                  CUtensorMapInterleave, CUtensorMapSwizzle, CUtensorMapL2promotion, CUtensorMapFloatOOBfill);
        cuuint32_t es[2] = {1, 1};
        { cuuint64_t dims[2] = {DM, SEQ}; cuuint64_t strides[1] = {DM * 2}; cuuint32_t box[2] = {64, 32};
          ((EncFn)fn)(&xmap, CU_TENSOR_MAP_DATA_TYPE_BFLOAT16, 2, (void*)x, dims, strides, box, es, CU_TENSOR_MAP_INTERLEAVE_NONE, CU_TENSOR_MAP_SWIZZLE_128B,
                      CU_TENSOR_MAP_L2_PROMOTION_L2_128B, CU_TENSOR_MAP_FLOAT_OOB_FILL_NONE); }
        { cuuint64_t dims[2] = {DM, HD}; cuuint64_t strides[1] = {DM * 2}; cuuint32_t box[2] = {64, 64};
          ((EncFn)fn)(&womap, CU_TENSOR_MAP_DATA_TYPE_BFLOAT16, 2, (void*)Wo, dims, strides, box, es, CU_TENSOR_MAP_INTERLEAVE_NONE, CU_TENSOR_MAP_SWIZZLE_128B,
                      CU_TENSOR_MAP_L2_PROMOTION_L2_128B, CU_TENSOR_MAP_FLOAT_OOB_FILL_NONE); }
        xmap_ptr = (const void*)x; womap_ptr = (const void*)Wo;
    }
    k_chain<<<96, 384, SM_TOTAL, st>>>(xmap, mem0, Wq, Wk, Wv, Wo);
    {
        cudaLaunchConfig_t cfg = {};
        cfg.gridDim = dim3(NAUX); cfg.blockDim = dim3(256); cfg.dynamicSmemBytes = AX_TOTAL; cfg.stream = st;
        cudaLaunchAttribute at[1];
        at[0].id = cudaLaunchAttributeProgrammaticStreamSerialization; at[0].val.programmaticStreamSerializationAllowed = 1;
        cfg.attrs = at; cfg.numAttrs = 1;
        cudaLaunchKernelEx(&cfg, k_aux, womap, x, A_re, A_im, B_re, B_im, C_re, C_im, log_dt, Dskip, gw, out);
    }
}
```

```cpp
#include <cuda_runtime.h>
#include <cuda_bf16.h>
#include <stdint.h>
#include <cuda.h>

typedef __nv_bfloat16 bf16;

#define SEQ 2048
#define DM 640
#define NH 32
#define DH 128
#define NM 8
#define SEG 32
#define NSEG 64
#define NST 128
#define HD 4096

__device__ bf16  g_b[SEQ * DM];
__device__ float g_g[SEQ];

__device__ __forceinline__ float bf2f(bf16 v) { return __bfloat162float(v); }
__device__ __forceinline__ uint32_t pack_bf16(float lo, float hi) {
    uint32_t r; asm("cvt.rn.bf16x2.f32 %0, %1, %2;" : "=r"(r) : "f"(hi), "f"(lo)); return r;
}
__device__ __forceinline__ uint32_t f2tf32(float x) { uint32_t r; asm("cvt.rna.tf32.f32 %0, %1;" : "=r"(r) : "f"(x)); return r; }
__device__ __forceinline__ void mma_tf32(float (&d)[4], uint32_t a0, uint32_t a1, uint32_t a2, uint32_t a3, uint32_t b0, uint32_t b1) {
    asm volatile("mma.sync.aligned.m16n8k8.row.col.f32.tf32.tf32.f32 {%0,%1,%2,%3}, {%4,%5,%6,%7}, {%8,%9}, {%0,%1,%2,%3};\n"
        : "+f"(d[0]), "+f"(d[1]), "+f"(d[2]), "+f"(d[3]) : "r"(a0), "r"(a1), "r"(a2), "r"(a3), "r"(b0), "r"(b1));
}
__device__ __forceinline__ void mma_bf16(float (&d)[4], uint32_t a0, uint32_t a1, uint32_t a2, uint32_t a3, uint32_t b0, uint32_t b1) {
    asm volatile("mma.sync.aligned.m16n8k16.row.col.f32.bf16.bf16.f32 {%0,%1,%2,%3}, {%4,%5,%6,%7}, {%8,%9}, {%0,%1,%2,%3};\n"
        : "+f"(d[0]), "+f"(d[1]), "+f"(d[2]), "+f"(d[3]) : "r"(a0), "r"(a1), "r"(a2), "r"(a3), "r"(b0), "r"(b1));
}
struct cf { float re, im; };
__device__ __forceinline__ cf cmul(cf a, cf b) { cf r; r.re = a.re * b.re - a.im * b.im; r.im = a.re * b.im + a.im * b.re; return r; }
__device__ __forceinline__ cf csq(cf a) { cf r; r.re = a.re * a.re - a.im * a.im; r.im = 2.f * a.re * a.im; return r; }
__device__ __forceinline__ cf cexpL(float zr, float zi, float L) {
    float e = __expf(zr * L);
    float ang = zi * L;
    float k = rintf(ang * 0.15915494309189535f);
    ang = fmaf(-k, 6.2831854820251465f, ang);
    ang = fmaf(-k, -1.7484555314695172e-07f, ang);
    cf r; r.re = e * __cosf(ang); r.im = e * __sinf(ang); return r;
}

#define SSM_CH 8
#define KC_PITCH 648
#define XS_PITCH (2048 + 8)
#define KT_LEN (2048 + 48)
#define PART_PITCH 20
struct SsmSmem {
    float Kc[SSM_CH][KC_PITCH];
    bf16  xs[SSM_CH][XS_PITCH];
    bf16  KT[2][KT_LEN];
    union {
        float part[8][128 * PART_PITCH];
        float st[SSM_CH][NST][8];
    } u;
    bf16  ys[SSM_CH][XS_PITCH];
    uint16_t kidx[2048];
};

__device__ __forceinline__ int kc_index(int l) {
    return l < 256 ? l : (l < 512 ? 256 + ((l - 256) >> 1) : (l < 1024 ? 384 + ((l - 512) >> 2) : 512 + ((l - 1024) >> 3)));
}

__device__ __noinline__ void ssm_group(unsigned char* smem_raw, int grp, const bf16* __restrict__ x, const bf16* __restrict__ A_re, const bf16* __restrict__ A_im,
        const bf16* __restrict__ B_re, const bf16* __restrict__ B_im, const bf16* __restrict__ C_re, const bf16* __restrict__ C_im,
        const bf16* __restrict__ log_dt, const bf16* __restrict__ Dskip) {
    SsmSmem& S = *reinterpret_cast<SsmSmem*>(smem_raw);
    const int tid = threadIdx.x, w = tid >> 5, lane = tid & 31, g = lane >> 2, t = lane & 3;
    const int d0 = grp * SSM_CH;
    __syncthreads();
    #pragma unroll
    for (int it = 0; it < 8; it++) {
        const int l = tid + 256 * it;
        uint4 v = *reinterpret_cast<const uint4*>(x + (size_t)l * DM + d0);
        const bf16* p = reinterpret_cast<const bf16*>(&v);
        const int lr = (l & ~15) | (15 - (l & 15));
        #pragma unroll
        for (int c = 0; c < 8; c++) S.xs[c][lr] = p[c];
        S.kidx[l] = (uint16_t)((int)bf2f(__float2bfloat16_rn((float)l)) == 2048 ? 640 : kc_index((int)bf2f(__float2bfloat16_rn((float)l))));
    }
    if (tid < 48) { const int i = tid < 16 ? tid : 2048 + tid; S.KT[0][i] = __float2bfloat16_rn(0.f); if (i > 0) S.KT[1][i - 1] = __float2bfloat16_rn(0.f); }
    if (tid == 48) S.KT[1][KT_LEN - 1] = __float2bfloat16_rn(0.f);
    {
        const int d = d0 + w;
        const float dt = bf2f(__float2bfloat16_rn(expf(bf2f(log_dt[d]))));
        #pragma unroll
        for (int i = 0; i < 4; i++) {
            const int n = lane + 32 * i;
            float zr = dt * bf2f(A_re[d * NST + n]), zi = dt * bf2f(A_im[d * NST + n]);
            cf dB; dB.re = dt * bf2f(B_re[d * NST + n]); dB.im = dt * bf2f(B_im[d * NST + n]);
            cf C; C.re = bf2f(C_re[d * NST + n]); C.im = bf2f(C_im[d * NST + n]);
            cf wv = cmul(C, dB);
            cf u8 = cexpL(zr, zi, 8.f), u128 = cexpL(zr, zi, 128.f);
            float* st = S.u.st[w][n];
            *reinterpret_cast<float4*>(st) = make_float4(zr, zi, wv.re, wv.im);
            *reinterpret_cast<float4*>(st + 4) = make_float4(u8.re, u8.im, u128.re, u128.im);
        }
        __syncwarp();
        float a0a[4] = {0, 0, 0, 0}, a0b[4] = {0, 0, 0, 0}, a1[4] = {0, 0, 0, 0}, a2a[4] = {0, 0, 0, 0}, a2b[4] = {0, 0, 0, 0};
        float k2048 = 0.f;
        const float Lg = (g < 4) ? (512.f + 4.f * g) : (g < 6 ? 1024.f + 8.f * (g - 4) : 1536.f + 8.f * (g - 6));
        #pragma unroll 4
        for (int kk = 0; kk < 32; kk++) {
            const float* st = S.u.st[w][4 * kk + t];
            float4 s0 = *reinterpret_cast<const float4*>(st), s1 = *reinterpret_cast<const float4*>(st + 4);
            cf wv; wv.re = s0.z; wv.im = s0.w;
            cf u8; u8.re = s1.x; u8.im = s1.y;
            cf u128; u128.re = s1.z; u128.im = s1.w;
            cf e1 = cexpL(s0.x, s0.y, (float)g);
            cf e23 = cexpL(s0.x, s0.y, Lg);
            cf e1b = cmul(e1, u8);
            cf e2 = csq(e1);
            cf p = csq(csq(csq(e2)));
            cf f0 = cmul(wv, p), f1 = cmul(f0, u128), f2 = cmul(f1, u128), f3 = cmul(f2, u128);
            uint32_t A00 = f2tf32(f0.re), A01 = f2tf32(f1.re), A02 = f2tf32(-f0.im), A03 = f2tf32(-f1.im);
            uint32_t A10 = f2tf32(f2.re), A11 = f2tf32(f3.re), A12 = f2tf32(-f2.im), A13 = f2tf32(-f3.im);
            mma_tf32(a0a, A00, A01, A02, A03, f2tf32(e1.re), f2tf32(e1.im));
            mma_tf32(a0b, A00, A01, A02, A03, f2tf32(e1b.re), f2tf32(e1b.im));
            mma_tf32(a1, A10, A11, A12, A13, f2tf32(e2.re), f2tf32(e2.im));
            uint32_t E0 = f2tf32(e23.re), E1 = f2tf32(e23.im);
            mma_tf32(a2a, A00, A01, A02, A03, E0, E1);
            mma_tf32(a2b, A10, A11, A12, A13, E0, E1);
            cf e2048 = csq(e23);
            k2048 += wv.re * e2048.re - wv.im * e2048.im;
        }
        k2048 += __shfl_xor_sync(~0u, k2048, 1);
        k2048 += __shfl_xor_sync(~0u, k2048, 2);
        float* Kc = S.Kc[w];
        Kc[16 * g + 2 * t] = a0a[0]; Kc[16 * g + 2 * t + 1] = a0a[1]; Kc[16 * (g + 8) + 2 * t] = a0a[2]; Kc[16 * (g + 8) + 2 * t + 1] = a0a[3];
        Kc[16 * g + 8 + 2 * t] = a0b[0]; Kc[16 * g + 8 + 2 * t + 1] = a0b[1]; Kc[16 * (g + 8) + 8 + 2 * t] = a0b[2]; Kc[16 * (g + 8) + 8 + 2 * t + 1] = a0b[3];
        Kc[256 + 8 * g + 2 * t] = a1[0]; Kc[256 + 8 * g + 2 * t + 1] = a1[1]; Kc[256 + 8 * (g + 8) + 2 * t] = a1[2]; Kc[256 + 8 * (g + 8) + 2 * t + 1] = a1[3];
        #pragma unroll
        for (int mt = 0; mt < 2; mt++) {
            #pragma unroll
            for (int e = 0; e < 4; e++) {
                int A = mt * 16 + g + (e >> 1) * 8, j = 2 * t + (e & 1);
                int Lj = (j < 4) ? 512 + 4 * j : (j < 6 ? 1024 + 8 * (j - 4) : 1536 + 8 * (j - 6));
                Kc[kc_index(Lj + 16 * A)] = mt ? a2b[e] : a2a[e];
            }
        }
        if (lane == 16) Kc[640] = k2048;
    }
    for (int c = 0; c < SSM_CH; c++) {
        __syncthreads();
        #pragma unroll
        for (int it = 0; it < 8; it++) {
            const int j = tid + 256 * it;
            const bf16 v = __float2bfloat16_rn(S.Kc[c][S.kidx[j]]);
            S.KT[0][16 + j] = v;
            S.KT[1][15 + j] = v;
        }
        uint32_t B[16][2];
        #pragma unroll
        for (int v = 0; v < 16; v++) {
            const bf16* p = &S.xs[c][16 * (8 * v + g) + 2 * t];
            B[v][0] = *reinterpret_cast<const uint32_t*>(p);
            B[v][1] = *reinterpret_cast<const uint32_t*>(p + 8);
        }
        __syncthreads();
        float acc[16][4];
        #pragma unroll
        for (int v = 0; v < 16; v++) { acc[v][0] = acc[v][1] = acc[v][2] = acc[v][3] = 0.f; }
        const bf16* kt = (g & 1) ? &S.KT[0][0] : &S.KT[1][0];
        const int ibase = 16 * w + g + 1 + 2 * t - ((g & 1) ? 0 : 1);
        #pragma unroll
        for (int q = 0; q < 16; q++) {
            const int i0 = ibase + 128 * q;
            uint32_t A0 = *reinterpret_cast<const uint32_t*>(kt + i0);
            uint32_t A1 = *reinterpret_cast<const uint32_t*>(kt + i0 + 8);
            uint32_t A3 = *reinterpret_cast<const uint32_t*>(kt + i0 + 16);
            #pragma unroll
            for (int v = q; v < 16; v++) mma_bf16(acc[v], A0, A1, A1, A3, B[v - q][0], B[v - q][1]);
        }
        float* part = S.u.part[w];
        #pragma unroll
        for (int v = 0; v < 16; v++) {
            int a = 8 * v + 2 * t + w;
            if (v < 15 || a < 128) { part[a * PART_PITCH + g] = acc[v][0]; part[a * PART_PITCH + g + 8] = acc[v][2]; }
            if (v < 15 || a + 1 < 128) { part[(a + 1) * PART_PITCH + g] = acc[v][1]; part[(a + 1) * PART_PITCH + g + 8] = acc[v][3]; }
        }
        __syncthreads();
        const float dsk = bf2f(Dskip[d0 + c]);
        #pragma unroll
        for (int it = 0; it < 2; it++) {
            const int l = (tid + 256 * it) * 4, a = l >> 4, b = l & 15;
            float4 sum = make_float4(0.f, 0.f, 0.f, 0.f);
            #pragma unroll
            for (int r = 0; r < 8; r++)
                if (a >= r) { float4 v = *reinterpret_cast<const float4*>(&S.u.part[r][a * PART_PITCH + b]); sum.x += v.x; sum.y += v.y; sum.z += v.z; sum.w += v.w; }
            const uint2 xr = *reinterpret_cast<const uint2*>(&S.xs[c][(l & ~15) + 12 - b]);
            const float x3 = __uint_as_float(xr.x << 16), x2 = __uint_as_float(xr.x & 0xffff0000u), x1 = __uint_as_float(xr.y << 16), x0 = __uint_as_float(xr.y & 0xffff0000u);
            auto fin = [&](float y, float xv) { return bf2f(__float2bfloat16_rn(y)) + bf2f(__float2bfloat16_rn(xv * dsk)); };
            uint2 o; o.x = pack_bf16(fin(sum.x, x0), fin(sum.y, x1)); o.y = pack_bf16(fin(sum.z, x2), fin(sum.w, x3));
            *reinterpret_cast<uint2*>(&S.ys[c][l]) = o;
        }
    }
    __syncthreads();
    #pragma unroll
    for (int it = 0; it < 8; it++) {
        const int l = tid + 256 * it;
        uint32_t wv[4];
        #pragma unroll
        for (int c = 0; c < 4; c++)
            wv[c] = (uint32_t)*reinterpret_cast<const uint16_t*>(&S.ys[2 * c][l]) | ((uint32_t)*reinterpret_cast<const uint16_t*>(&S.ys[2 * c + 1][l]) << 16);
        *reinterpret_cast<uint4*>(g_b + (size_t)l * DM + d0) = make_uint4(wv[0], wv[1], wv[2], wv[3]);
    }
}

__device__ __forceinline__ uint32_t smem_u32(const void* p) { return (uint32_t)__cvta_generic_to_shared(p); }
__device__ __forceinline__ void mbar_init(uint32_t bar, uint32_t cnt) { asm volatile("mbarrier.init.shared::cta.b64 [%0], %1;" :: "r"(bar), "r"(cnt) : "memory"); }
__device__ __forceinline__ void mbar_expect_tx(uint32_t bar, uint32_t bytes) { asm volatile("mbarrier.arrive.expect_tx.shared::cta.b64 _, [%0], %1;" :: "r"(bar), "r"(bytes) : "memory"); }
__device__ __forceinline__ void mbar_arrive(uint32_t bar) { asm volatile("mbarrier.arrive.shared::cta.b64 _, [%0];" :: "r"(bar) : "memory"); }
__device__ __forceinline__ void mbar_wait(uint32_t bar, uint32_t parity) {
    uint32_t ok; int guard = 0;
    do {
        asm volatile("{\n.reg .pred P1;\nmbarrier.test_wait.parity.shared::cta.b64 P1, [%1], %2;\nselp.u32 %0,1,0,P1;\n}" : "=r"(ok) : "r"(bar), "r"(parity) : "memory");
    } while (!ok && ++guard < (1 << 26));
}
__device__ __forceinline__ uint32_t mapa(uint32_t addr, uint32_t rank) { uint32_t r; asm volatile("mapa.shared::cluster.u32 %0, %1, %2;" : "=r"(r) : "r"(addr), "r"(rank)); return r; }
__device__ __forceinline__ void st_async4(uint32_t addr, float a, float b, float c, float d, uint32_t bar) {
    asm volatile("st.async.weak.shared::cluster.mbarrier::complete_tx::bytes.v4.f32 [%0], {%1,%2,%3,%4}, [%5];" :: "r"(addr), "f"(a), "f"(b), "f"(c), "f"(d), "r"(bar) : "memory");
}
__device__ __forceinline__ void bulk_s2c(uint32_t dst, uint32_t src, uint32_t bytes, uint32_t bar) {
    asm volatile("cp.async.bulk.shared::cluster.shared::cta.mbarrier::complete_tx::bytes [%0], [%1], %2, [%3];" :: "r"(dst), "r"(src), "r"(bytes), "r"(bar) : "memory");
}
__device__ __forceinline__ void bulk_g2s(uint32_t dst, const void* src, uint32_t bytes, uint32_t bar) {
    asm volatile("cp.async.bulk.shared::cluster.global.mbarrier::complete_tx::bytes [%0], [%1], %2, [%3];" :: "r"(dst), "l"(src), "r"(bytes), "r"(bar) : "memory");
}
__device__ __forceinline__ void bulk_s2g(void* dst, uint32_t src, uint32_t bytes) {
    asm volatile("cp.async.bulk.global.shared::cta.bulk_group [%0], [%1], %2;" :: "l"(dst), "r"(src), "r"(bytes) : "memory");
}
__device__ __forceinline__ void bulk_commit() { asm volatile("cp.async.bulk.commit_group;" ::: "memory"); }
__device__ __forceinline__ void bulk_wait_read0() { asm volatile("cp.async.bulk.wait_group.read 0;" ::: "memory"); }
__device__ __forceinline__ void bulk_wait0() { asm volatile("cp.async.bulk.wait_group 0;" ::: "memory"); }
__device__ __forceinline__ void fence_async() { asm volatile("fence.proxy.async.shared::cta;" ::: "memory"); }
__device__ __forceinline__ void nbar_sync(int id, int n) { asm volatile("bar.sync %0, %1;" :: "r"(id), "r"(n) : "memory"); }
__device__ __forceinline__ void nbar_arrive(int id, int n) { asm volatile("bar.arrive %0, %1;" :: "r"(id), "r"(n) : "memory"); }
__device__ __forceinline__ void cp_async16(uint32_t dst, const void* src) { asm volatile("cp.async.cg.shared.global [%0], [%1], 16;" :: "r"(dst), "l"(src) : "memory"); }
__device__ __forceinline__ void cp_async_wait_all() { asm volatile("cp.async.wait_all;" ::: "memory"); }
__device__ __forceinline__ void ldsm4(uint32_t (&r)[4], uint32_t addr) {
    asm volatile("ldmatrix.sync.aligned.m8n8.x4.shared.b16 {%0,%1,%2,%3}, [%4];" : "=r"(r[0]), "=r"(r[1]), "=r"(r[2]), "=r"(r[3]) : "r"(addr) : "memory");
}
__device__ __forceinline__ void ldsm4t(uint32_t (&r)[4], uint32_t addr) {
    asm volatile("ldmatrix.sync.aligned.m8n8.x4.trans.shared.b16 {%0,%1,%2,%3}, [%4];" : "=r"(r[0]), "=r"(r[1]), "=r"(r[2]), "=r"(r[3]) : "r"(addr) : "memory");
}
__device__ __forceinline__ void stsm2t(uint32_t addr, uint32_t r0, uint32_t r1) {
    asm volatile("stmatrix.sync.aligned.m8n8.x2.trans.shared.b16 [%0], {%1,%2};" :: "r"(addr), "r"(r0), "r"(r1) : "memory");
}
__device__ __forceinline__ uint4 ld_relaxed4(const void* p) { uint4 v; asm volatile("ld.relaxed.gpu.global.v4.u32 {%0,%1,%2,%3}, [%4];" : "=r"(v.x), "=r"(v.y), "=r"(v.z), "=r"(v.w) : "l"(p) : "memory"); return v; }
__device__ __forceinline__ void st_relaxed2(void* p, uint32_t a, uint32_t b) { asm volatile("st.relaxed.gpu.global.v2.u32 [%0], {%1,%2};" :: "l"(p), "r"(a), "r"(b) : "memory"); }
__device__ __forceinline__ void st_relaxed1(void* p, uint32_t a) { asm volatile("st.relaxed.gpu.global.u32 [%0], %1;" :: "l"(p), "r"(a) : "memory"); }
__device__ __forceinline__ unsigned ld_acquire(const unsigned* p) { unsigned v; asm volatile("ld.acquire.gpu.global.u32 %0, [%1];" : "=r"(v) : "l"(p) : "memory"); return v; }
__device__ __forceinline__ float ex2_approx(float x) { float r; asm("ex2.approx.ftz.f32 %0, %1;" : "=f"(r) : "f"(x)); return r; }
__device__ __forceinline__ uint64_t make_desc(uint32_t saddr, uint32_t lbo, uint32_t sbo) {
    return (uint64_t)((saddr & 0x3FFFF) >> 4) | ((uint64_t)((lbo & 0x3FFFF) >> 4) << 16) | ((uint64_t)((sbo & 0x3FFFF) >> 4) << 32) | (1ull << 62);
}
__device__ __forceinline__ void wg_fence() { asm volatile("wgmma.fence.sync.aligned;" ::: "memory"); }
__device__ __forceinline__ void wg_commit() { asm volatile("wgmma.commit_group.sync.aligned;" ::: "memory"); }
__device__ __forceinline__ void wg_wait0() { asm volatile("wgmma.wait_group.sync.aligned 0;" ::: "memory"); }
__device__ __forceinline__ void wgmma_n40_tA(float (&d)[20], uint64_t da, uint64_t db, int scale_d) {
    asm volatile("{\n.reg .pred p;\nsetp.ne.b32 p, %22, 0;\n"
        "wgmma.mma_async.sync.aligned.m64n40k16.f32.bf16.bf16 {%0,%1,%2,%3,%4,%5,%6,%7,%8,%9,%10,%11,%12,%13,%14,%15,%16,%17,%18,%19}, %20, %21, p, 1, 1, 1, 0;\n}\n"
        : "+f"(d[0]), "+f"(d[1]), "+f"(d[2]), "+f"(d[3]), "+f"(d[4]), "+f"(d[5]), "+f"(d[6]), "+f"(d[7]), "+f"(d[8]), "+f"(d[9]),
          "+f"(d[10]), "+f"(d[11]), "+f"(d[12]), "+f"(d[13]), "+f"(d[14]), "+f"(d[15]), "+f"(d[16]), "+f"(d[17]), "+f"(d[18]), "+f"(d[19])
        : "l"(da), "l"(db), "r"(scale_d));
}

#define NREP 8
#define NRED 80
#define CAL_THR 410u
#define COMM_REGS "40"
#define NPOOL 576
#define RPS 4
__device__ __align__(4096) uint32_t g_pool[(NPOOL + 1) * 1024];
__device__ unsigned g_cls[NPOOL];
__device__ unsigned g_side[96];
__device__ unsigned g_calcnt;
__device__ unsigned g_epoch;
__device__ unsigned g_flag[NSEG][NH];
__device__ __align__(1024) bf16 g_Qimg[NSEG * NH * 2 * 32 * 64];
__device__ __align__(1024) bf16 g_Kimg[NSEG * NH * 2 * 40 * 64];
__device__ __align__(1024) bf16 g_Vimg[NSEG * NH * 2 * 40 * 64];

#define SM_XB    0
#define SM_VT    81920
#define SM_KT    (SM_VT + 20480)
#define SM_QT    (SM_KT + 10240)
#define SM_QS    (SM_QT + 4096)
#define SM_MEMB  (SM_QS + 1024)
#define SM_RED   (SM_MEMB + 10240)
#define SM_SC    (SM_RED + 16384)
#define SM_CRED  (SM_SC + 5120)
#define SM_PB    (SM_CRED + 1024)
#define SM_TPM   (SM_PB + 1024)
#define SM_TRD   (SM_TPM + 256)
#define SM_TPUB  (SM_TRD + 16)
#define SM_TGAT  (SM_TPUB + 128)
#define SM_CAL   (SM_TGAT + 64)
#define SM_TRACE (SM_CAL + 3072)
#define SM_WO    163840
#define SM_BAR   (SM_WO + 65536)
#define SM_TOTAL (SM_BAR + 256)
#define B_SC   (SM_BAR + 0)
#define B_V    (SM_BAR + 16)
#define B_MEM  (SM_BAR + 32)
#define B_P    (SM_BAR + 48)
#define B_X    (SM_BAR + 56)
#define B_EXP  (SM_BAR + 72)

#define TR(ev) do {} while (0)
__device__ __forceinline__ uint32_t tag_of(int s) { return (uint32_t)(((s >> 1) & 1) + 1); }
__device__ __forceinline__ unsigned probe_latency(uint32_t* p, uint32_t zero) {
    uint32_t v, best = 0xffffffffu;
    asm volatile("atom.relaxed.gpu.global.add.u32 %0, [%1], 0;" : "=r"(v) : "l"(p) : "memory");
    #pragma unroll 1
    for (int r = 0; r < 4; r++) {
        uint32_t c0, c1;
        asm volatile("mov.u32 %0, %%clock;" : "=r"(c0) : "r"(v) : "memory");
        asm volatile("atom.relaxed.gpu.global.add.u32 %0, [%1], 0;" : "=r"(v) : "l"(p + ((v + c0) & zero)) : "memory");
        asm volatile("{\n.reg .u32 t;\nand.b32 t, %1, %2;\nmov.u32 %0, %%clock;\nadd.u32 %0, %0, t;\n}" : "=r"(c1) : "r"(v), "r"(zero) : "memory");
        best = min(best, c1 - c0);
    }
    return best;
}
__device__ __forceinline__ void cluster_sync_all() { asm volatile("barrier.cluster.arrive.release.aligned;\nbarrier.cluster.wait.acquire.aligned;" ::: "memory"); }
__device__ __forceinline__ void tma_load_2d(uint32_t dst, const void* map, int c0, int c1, uint32_t bar) {
    asm volatile("cp.async.bulk.tensor.2d.shared::cluster.global.mbarrier::complete_tx::bytes [%0], [%1, {%3, %4}], [%2];"
        :: "r"(dst), "l"(map), "r"(bar), "r"(c0), "r"(c1) : "memory");
}
__device__ __forceinline__ void stsm4t(uint32_t addr, uint32_t r0, uint32_t r1, uint32_t r2, uint32_t r3) {
    asm volatile("stmatrix.sync.aligned.m8n8.x4.trans.shared.b16 [%0], {%1,%2,%3,%4};" :: "r"(addr), "r"(r0), "r"(r1), "r"(r2), "r"(r3) : "memory");
}
__device__ __forceinline__ void wgmma_n32_rs(float (&d)[16], const uint32_t (&a)[4], uint64_t db, int scale_d) {
    asm volatile("{\n.reg .pred p;\nsetp.ne.b32 p, %21, 0;\n"
        "wgmma.mma_async.sync.aligned.m64n32k16.f32.bf16.bf16 {%0,%1,%2,%3,%4,%5,%6,%7,%8,%9,%10,%11,%12,%13,%14,%15}, {%16,%17,%18,%19}, %20, p, 1, 1, 0;\n}\n"
        : "+f"(d[0]), "+f"(d[1]), "+f"(d[2]), "+f"(d[3]), "+f"(d[4]), "+f"(d[5]), "+f"(d[6]), "+f"(d[7]),
          "+f"(d[8]), "+f"(d[9]), "+f"(d[10]), "+f"(d[11]), "+f"(d[12]), "+f"(d[13]), "+f"(d[14]), "+f"(d[15])
        : "r"(a[0]), "r"(a[1]), "r"(a[2]), "r"(a[3]), "l"(db), "r"(scale_d));
}

__device__ __forceinline__ void st_async4u(uint32_t addr, uint4 v, uint32_t bar) {
    asm volatile("st.async.weak.shared::cluster.mbarrier::complete_tx::bytes.v4.u32 [%0], {%1,%2,%3,%4}, [%5];" :: "r"(addr), "r"(v.x), "r"(v.y), "r"(v.z), "r"(v.w), "r"(bar) : "memory");
}
__device__ __forceinline__ void export_tiles(uint32_t sb, int s, int h, uint32_t rank) {
    const size_t img = (size_t)(s * NH + h) * 2;
    const int sl = s & 1;
    if (rank == 2) {
        bulk_s2g(g_Vimg + img * 2560, sb + SM_VT + sl * 10240, 5120);
        bulk_s2g(g_Vimg + (img + 1) * 2560, sb + SM_VT + sl * 10240 + 5120, 5120);
    } else {
        bulk_s2g(g_Qimg + (img + rank) * 2048, sb + SM_QT, 4096);
        bulk_s2g(g_Kimg + (img + rank) * 2560, sb + SM_KT + sl * 5120, 5120);
    }
    bulk_commit();
    bulk_wait_read0();
    mbar_arrive(sb + B_EXP);
    bulk_wait0();
    asm volatile("fence.proxy.async;" ::: "memory");
    __threadfence();
    atomicAdd(&g_flag[s][h], 1u);
}

__device__ __forceinline__ void score_tile(uint32_t sb, int sl, int nt, int lane, uint32_t rank) {
    float sc[4] = {0, 0, 0, 0}, sd[4] = {0, 0, 0, 0};
    const int r = lane & 7;
    uint32_t qa[2][4], kb[2][4];
    #pragma unroll
    for (int j = 0; j < 2; j++) {
        const int chunk = (lane >> 3) + 4 * j;
        ldsm4(kb[j], sb + SM_KT + sl * 5120 + (8 * nt + r) * 128 + ((chunk ^ r) << 4));
        ldsm4(qa[j], sb + SM_QS + r * 128 + ((chunk ^ r) << 4));
    }
    mma_bf16(sc, qa[0][0], 0u, qa[0][1], 0u, kb[0][0], kb[0][1]);
    mma_bf16(sd, qa[1][0], 0u, qa[1][1], 0u, kb[1][0], kb[1][1]);
    mma_bf16(sc, qa[0][2], 0u, qa[0][3], 0u, kb[0][2], kb[0][3]);
    mma_bf16(sd, qa[1][2], 0u, qa[1][3], 0u, kb[1][2], kb[1][3]);
    sc[0] += sd[0]; sc[1] += sd[1];
    const float o0 = __shfl_down_sync(~0u, sc[0], 1), o1 = __shfl_down_sync(~0u, sc[1], 1);
    if ((lane & 1) == 0) {
        const uint32_t a = SM_SC + sl * 2560 + rank * 1280 + ((lane >> 2) * 40 + 8 * nt + 2 * (lane & 3)) * 4;
        const uint32_t bo = B_SC + 8 * sl;
        #pragma unroll
        for (int d = 0; d < 3; d++) { const uint32_t rb = mapa(sb, d); st_async4(rb + a, sc[0], sc[1], o0, o1, rb + bo); }
    }
}
__device__ __forceinline__ void wgmma_n40_rs(float (&d)[20], const uint32_t (&a)[4], uint64_t db, int scale_d) {
    asm volatile("{\n.reg .pred p;\nsetp.ne.b32 p, %25, 0;\n"
        "wgmma.mma_async.sync.aligned.m64n40k16.f32.bf16.bf16 {%0,%1,%2,%3,%4,%5,%6,%7,%8,%9,%10,%11,%12,%13,%14,%15,%16,%17,%18,%19}, {%20,%21,%22,%23}, %24, p, 1, 1, 0;\n}\n"
        : "+f"(d[0]), "+f"(d[1]), "+f"(d[2]), "+f"(d[3]), "+f"(d[4]), "+f"(d[5]), "+f"(d[6]), "+f"(d[7]), "+f"(d[8]), "+f"(d[9]),
          "+f"(d[10]), "+f"(d[11]), "+f"(d[12]), "+f"(d[13]), "+f"(d[14]), "+f"(d[15]), "+f"(d[16]), "+f"(d[17]), "+f"(d[18]), "+f"(d[19])
        : "r"(a[0]), "r"(a[1]), "r"(a[2]), "r"(a[3]), "l"(db), "r"(scale_d));
}
__device__ __forceinline__ void pu_store(const float (&u)[20], const uint32_t (&pb)[5], float2 inv, unsigned char* smem, int sl, int lt, int warp, int lane, uint32_t tg) {
    float o[4] = {0, 0, 0, 0}, o2[4] = {0, 0, 0, 0};
    mma_bf16(o, pack_bf16(u[0], u[1]), pack_bf16(u[2], u[3]), pack_bf16(u[4], u[5]), pack_bf16(u[6], u[7]), pb[0], pb[1]);
    mma_bf16(o2, pack_bf16(u[8], u[9]), pack_bf16(u[10], u[11]), pack_bf16(u[12], u[13]), pack_bf16(u[14], u[15]), pb[2], pb[3]);
    mma_bf16(o, pack_bf16(u[16], u[17]), pack_bf16(u[18], u[19]), 0u, 0u, pb[4], 0u);
    const uint2 off = *reinterpret_cast<const uint2*>(smem + SM_TPM + (((sl * 4 + lt) * 4 + warp) * 2) * 4);
    unsigned char* pool = reinterpret_cast<unsigned char*>(g_pool) + lane * 8;
    st_relaxed2(pool + off.x, (__float_as_uint((o[0] + o2[0]) * inv.x) & ~3u) | tg, (__float_as_uint((o[1] + o2[1]) * inv.y) & ~3u) | tg);
    st_relaxed2(pool + off.y, (__float_as_uint((o[2] + o2[2]) * inv.x) & ~3u) | tg, (__float_as_uint((o[3] + o2[3]) * inv.y) & ~3u) | tg);
}
template <int NT>
__device__ __forceinline__ void u_pass(unsigned char* smem, uint32_t sb, int s, uint32_t rank, int wg, int warp, int lane) {
    const int sl = s & 1;
    constexpr int NRS = 6;
    uint32_t wa[NRS][4];
    {
        const int mi = lane >> 3, chunk = 2 * warp + (mi & 1);
        #pragma unroll
        for (int ks = 0; ks < NRS; ks++) {
            const int row = 16 * ks + (mi >> 1) * 8 + (lane & 7);
            ldsm4t(wa[ks], sb + SM_WO + (2 * wg) * 16384 + row * 128 + ((chunk ^ (row & 7)) << 4));
        }
    }
    if (rank < 2) { mbar_wait(sb + B_V + 8 * sl, (s >> 1) & 1); fence_async(); }
    if (wg == 0 && warp == 0) TR(4);
    float U0[20];
    wg_fence();
    #pragma unroll
    for (int ks = 0; ks < NRS; ks++)
        wgmma_n40_rs(U0, wa[ks], make_desc(sb + SM_VT + sl * 10240 + (ks >> 2) * 5120 + (ks & 3) * 32, 16, 1024), ks > 0);
    #pragma unroll
    for (int ks = NRS; ks < 8; ks++)
        wgmma_n40_tA(U0, make_desc(sb + SM_WO + (2 * wg) * 16384 + ks * 2048, 1024, 1024),
                     make_desc(sb + SM_VT + sl * 10240 + (ks >> 2) * 5120 + (ks & 3) * 32, 16, 1024), 1);
    wg_commit();
    const uint32_t tg = tag_of(s);
    uint32_t pb[5];
    float2 inv;
    auto get_p = [&]() {
        nbar_sync(9, 288);
        const uint32_t* pbs = reinterpret_cast<const uint32_t*>(smem + SM_PB);
        #pragma unroll
        for (int q = 0; q < 5; q++) pb[q] = pbs[q * 32 + lane];
        float sm[4] = {0, 0, 0, 0}, sm2[4] = {0, 0, 0, 0};
        const uint32_t one = 0x3f803f80u;
        mma_bf16(sm, one, one, one, one, pb[0], pb[1]);
        mma_bf16(sm2, one, one, one, one, pb[2], pb[3]);
        mma_bf16(sm, one, one, 0u, 0u, pb[4], 0u);
        inv.x = __frcp_rn(sm[0] + sm2[0]); inv.y = __frcp_rn(sm[1] + sm2[1]);
    };
    if (NT == 2) {
        wg_wait0();
        float U1[20];
        wg_fence();
        #pragma unroll
        for (int ks = 0; ks < 8; ks++)
            wgmma_n40_tA(U1, make_desc(sb + SM_WO + (2 * wg + 1) * 16384 + ks * 2048, 1024, 1024),
                         make_desc(sb + SM_VT + sl * 10240 + (ks >> 2) * 5120 + (ks & 3) * 32, 16, 1024), ks > 0);
        wg_commit();
        get_p();
        if (wg == 0 && warp == 0) TR(8);
        pu_store(U0, pb, inv, smem, sl, 2 * wg, warp, lane, tg);
        wg_wait0();
        if (wg == 0 && warp == 0) TR(6);
        pu_store(U1, pb, inv, smem, sl, 2 * wg + 1, warp, lane, tg);
    } else {
        wg_wait0();
        get_p();
        pu_store(U0, pb, inv, smem, sl, 2 * wg, warp, lane, tg);
    }
}

__global__ void __cluster_dims__(3, 1, 1) __launch_bounds__(384, 1)
k_chain(const __grid_constant__ CUtensorMap xmap, const bf16* __restrict__ mem0, const bf16* __restrict__ Wq, const bf16* __restrict__ Wk,
        const bf16* __restrict__ Wv, const bf16* __restrict__ Wo) {
    extern __shared__ __align__(1024) unsigned char smem[];
    const uint32_t sb = smem_u32(smem);
    const int tid = threadIdx.x, lane = tid & 31;
    const int wg = __shfl_sync(~0u, tid >> 7, 0), warp = __shfl_sync(~0u, (tid >> 5) & 3, 0);
    uint32_t rank; asm volatile("mov.u32 %0, %%cluster_ctarank;" : "=r"(rank));
    const int cta = blockIdx.x, h = cta / 3;
    asm volatile("griddepcontrol.launch_dependents;");
    if (tid == 0) {
        for (int i = 0; i < 2; i++) { mbar_init(sb + B_SC + 8 * i, 1); mbar_init(sb + B_V + 8 * i, 1); mbar_init(sb + B_MEM + 8 * i, 64); mbar_init(sb + B_X + 8 * i, 1); }
        mbar_init(sb + B_P, 32); mbar_init(sb + B_EXP, 1);
        asm volatile("fence.mbarrier_init.release.cluster;" ::: "memory");
    }
    {
        const int ntile = (rank == 2) ? 4 : 3;
        const int tile0 = (rank == 2) ? 0 : (rank == 0 ? 4 : 7);
        const bf16* src0 = (rank == 2) ? Wv + h * DH : Wq + h * DH + rank * 64;
        const bf16* src1 = (rank == 2) ? Wv + h * DH + 64 : Wk + h * DH + rank * 64;
        for (int i = tid; i < 2 * 640 * 8; i += 384) {
            int mt = i / 5120, r = (i % 5120) >> 3, c = i & 7;
            const bf16* s = (mt ? src1 : src0) + (size_t)r * HD + c * 8;
            cp_async16(sb + mt * 81920 + r * 128 + ((c ^ (r & 7)) << 4), s);
        }
        for (int i = tid; i < ntile * 128 * 8; i += 384) {
            int lt = i >> 10, r = (i >> 3) & 127, c = i & 7;
            const bf16* s = Wo + ((size_t)h * DH + r) * DM + (tile0 + lt) * 64 + c * 8;
            cp_async16(sb + SM_WO + lt * 16384 + r * 128 + ((c ^ (r & 7)) << 4), s);
        }
        {
            const int w12 = tid >> 5;
            const uint32_t zero = blockIdx.y;
            uint4* z = reinterpret_cast<uint4*>(g_pool + (size_t)cta * 6 * 1024);
            for (int i = tid; i < 6 * 256; i += 384) z[i] = make_uint4(0, 0, 0, 0);
            __syncthreads();
            if (lane == 0 && w12 < 7) {
                uint32_t* pp = (w12 < 6) ? g_pool + (size_t)(cta * 6 + w12) * 1024 + 512 : g_pool + (size_t)NPOOL * 1024 + (cta & 31) * 32 + (cta >> 5) * 8;
                reinterpret_cast<unsigned*>(smem + SM_BAR + 128)[w12] = probe_latency(pp, zero);
            }
            __syncthreads();
            if (tid < 6) {
                const unsigned* lat = reinterpret_cast<const unsigned*>(smem + SM_BAR + 128);
                const unsigned myside = lat[6] > CAL_THR ? 1u : 0u;
                g_cls[cta * 6 + tid] = myside ^ (lat[tid] > CAL_THR ? 1u : 0u);
                if (tid == 0) g_side[cta] = myside;
            }
            __threadfence();
            __syncthreads();
            if (tid == 0) atomicAdd(&g_calcnt, 1u);
        }
        cp_async_wait_all();
        fence_async();
    }
    __syncthreads();

    if (wg == 2) {
        asm volatile("setmaxnreg.dec.sync.aligned.u32 " COMM_REGS ";");
        const int ct = tid & 127;
        nbar_sync(5, 384);
        for (int c = ct; c < 640; c += 128) {
            int ks = c >> 4, hf = (c >> 3) & 1, r = c & 7;
            *reinterpret_cast<uint4*>(smem + SM_MEMB + c * 16) = *reinterpret_cast<const uint4*>(mem0 + r * DM + ks * 16 + hf * 8);
        }
        {
            if (ct == 0) {
                const unsigned target = (*reinterpret_cast<volatile unsigned*>(&g_epoch) + 1u) * 96u;
                int guard = 0;
                while ((int)(ld_acquire(&g_calcnt) - target) < 0 && ++guard < (1 << 22)) {}
            }
            nbar_sync(4, 128);
            uint16_t* list = reinterpret_cast<uint16_t*>(smem + SM_CAL);
            uint8_t* rr = smem + SM_CAL + 2304;
            uint8_t* sd = smem + SM_CAL + 2304 + 96;
            int* cnt = reinterpret_cast<int*>(smem + SM_CAL + 2304 + 192);
            if (warp == 0) {
                int n0 = 0, n1 = 0;
                for (int b0 = 0; b0 < NPOOL; b0 += 32) {
                    const unsigned sdb = *reinterpret_cast<volatile unsigned*>(&g_cls[b0 + lane]) & 1u;
                    const unsigned m1 = __ballot_sync(~0u, sdb), lt = (1u << lane) - 1u;
                    if (sdb) list[NPOOL + n1 + __popc(m1 & lt)] = (uint16_t)(b0 + lane); else list[n0 + __popc(~m1 & lt)] = (uint16_t)(b0 + lane);
                    n1 += __popc(m1); n0 += 32 - __popc(m1);
                }
                if (lane == 0) { cnt[0] = n0; cnt[1] = n1; }
            } else if (warp == 1) {
                int n0 = 0, n1 = 0;
                for (int r0 = 0; r0 < 96; r0 += 32) {
                    const unsigned sdr = *reinterpret_cast<volatile unsigned*>(&g_side[r0 + lane]) & 1u;
                    sd[r0 + lane] = (uint8_t)sdr;
                    const bool isred = (r0 + lane) < NRED;
                    const unsigned m1 = __ballot_sync(~0u, sdr && isred), m0 = __ballot_sync(~0u, !sdr && isred), lt = (1u << lane) - 1u;
                    if (isred) rr[r0 + lane] = (uint8_t)(sdr ? n1 + __popc(m1 & lt) : n0 + __popc(m0 & lt));
                    n1 += __popc(m1); n0 += __popc(m0);
                }
                if (lane == 0) { cnt[2] = n0; cnt[3] = n1; }
            }
            nbar_sync(4, 128);
            auto phys = [&](int side, int idx) -> uint32_t {
                const int c = cnt[side];
                return (idx < c) ? list[side * NPOOL + idx] : list[(side ^ 1) * NPOOL + cnt[side ^ 1] - 1 - (idx - c)];
            };
            for (int e = ct; e < 112; e += 128) {
                if (e < 64) {
                    const int slot = e >> 5, lt = (e >> 3) & 3, w = (e >> 1) & 3, hf = e & 1;
                    const int tile0 = (rank == 2) ? 0 : (rank == 0 ? 4 : 7);
                    const int tile = min(tile0 + lt, 9);
                    const int r = 2 * (4 * tile + w) + hf;
                    reinterpret_cast<uint32_t*>(smem + SM_TPM)[e] = phys(sd[r], 4 * rr[r] + slot * 2 + (h >> 4)) * 4096u + (h & 15) * 256u;
                } else if (e < 68) {
                    const int i = e - 64;
                    reinterpret_cast<uint32_t*>(smem + SM_TRD)[i] = (cta < NRED) ? phys(sd[cta], 4 * rr[cta] + i) * 4096u : 0u;
                } else if (e < 100) {
                    const int i = e - 68, slot = i >> 3, rep = i & 7, side = rep / RPS;
                    reinterpret_cast<uint32_t*>(smem + SM_TPUB)[i] = phys(side, 4 * cnt[2 + side] + (slot * RPS + (rep % RPS)) * 3 + (cta >> 5)) * 4096u + (cta & 31) * 128u;
                } else {
                    const int i = e - 100, slot = i / 3, b = i % 3, side = sd[cta];
                    reinterpret_cast<uint32_t*>(smem + SM_TGAT)[slot * 4 + b] = phys(side, 4 * cnt[2 + side] + (slot * RPS + (h % RPS)) * 3 + b) * 4096u;
                }
            }
        }
        if (ct == 0) {
            for (int sg = 0; sg < 2; sg++) {
                mbar_expect_tx(sb + B_X + 8 * sg, 40960);
                for (int c = 0; c < 10; c++) tma_load_2d(sb + SM_XB + sg * 40960 + c * 4096, &xmap, c * 64, sg * 32, sb + B_X + 8 * sg);
            }
            mbar_expect_tx(sb + B_SC, 2560);
            if (rank < 2) mbar_expect_tx(sb + B_V, 8192 + 2048);
        }
        nbar_sync(5, 384);
        cluster_sync_all();
        unsigned char* const pool = reinterpret_cast<unsigned char*>(g_pool);
        for (int s = 0; s < NSEG - 1; s++) {
            if (warp < 2) nbar_sync(6, 320);
            if (warp == 0) {
                if (rank < 2) score_tile(sb, s & 1, 0, lane, rank);
                const int g = lane >> 2, t = lane & 3;
                mbar_wait(sb + B_SC + 8 * (s & 1), (s >> 1) & 1);
                TR(5);
                const uint32_t sa = sb + SM_SC + (s & 1) * 2560 + (g * 40 + 2 * t) * 4;
                float v[5][2], u[5][2];
                #pragma unroll
                for (int q = 0; q < 5; q++) {
                    asm volatile("ld.shared.v2.f32 {%0,%1}, [%2];" : "=f"(v[q][0]), "=f"(v[q][1]) : "r"(sa + 32 * q) : "memory");
                    asm volatile("ld.shared.v2.f32 {%0,%1}, [%2];" : "=f"(u[q][0]), "=f"(u[q][1]) : "r"(sa + 1280 + 32 * q) : "memory");
                }
                float mx = -3.0e38f;
                #pragma unroll
                for (int q = 0; q < 5; q++) {
                    v[q][0] += u[q][0]; v[q][1] += u[q][1];
                    mx = fmaxf(mx, fmaxf(v[q][0], v[q][1]));
                }
                mx = fmaxf(mx, __shfl_xor_sync(~0u, mx, 1));
                mx = fmaxf(mx, __shfl_xor_sync(~0u, mx, 2));
                const float sc2 = 0.08838834764831845f * 1.4426950408889634f;
                const float mxs = mx * sc2;
                uint32_t* pbs = reinterpret_cast<uint32_t*>(smem + SM_PB);
                #pragma unroll
                for (int q = 0; q < 5; q++) {
                    const float e0 = ex2_approx(fmaf(v[q][0], sc2, -mxs)), e1 = ex2_approx(fmaf(v[q][1], sc2, -mxs));
                    pbs[q * 32 + lane] = pack_bf16(e0, e1);
                }
                __syncwarp();
                TR(0);
                nbar_arrive(9, 288);
            } else if (warp == 1 && lane == 0) {
                if (s + 1 < NSEG - 1) {
                    mbar_expect_tx(sb + B_SC + 8 * ((s + 1) & 1), 2560);
                    if (rank < 2) mbar_expect_tx(sb + B_V + 8 * ((s + 1) & 1), 8192 + 2048);
                }
                if (s + 2 < NSEG) {
                    mbar_expect_tx(sb + B_X + 8 * (s & 1), 40960);
                    for (int c = 0; c < 10; c++) tma_load_2d(sb + SM_XB + (s & 1) * 40960 + c * 4096, &xmap, c * 64, (s + 2) * 32, sb + B_X + 8 * (s & 1));
                }
                export_tiles(sb, s, h, rank);
            }
            __syncwarp();
            nbar_sync(3, 384);
            const uint32_t tg = tag_of(s);
            if (cta < NRED) {
                const unsigned char* base = pool + reinterpret_cast<const uint32_t*>(smem + SM_TRD)[(s & 1) * 2 + (warp >> 1)] + (warp & 1) * 2048 + lane * 16;
                uint4 v[4]; int guard = 0;
                #pragma unroll
                for (int j = 0; j < 4; j++) v[j] = make_uint4(0, 0, 0, 0);
                uint32_t pend = 0xF;
                do {
                    #pragma unroll
                    for (int j = 0; j < 4; j++) if (pend & (1u << j)) v[j] = ld_relaxed4(base + j * 512);
                    #pragma unroll
                    for (int j = 0; j < 4; j++)
                        if (((v[j].x & 3) == tg) && ((v[j].y & 3) == tg) && ((v[j].z & 3) == tg) && ((v[j].w & 3) == tg)) pend &= ~(1u << j);
                } while (__any_sync(~0u, pend != 0) && ++guard < (1 << 20));
                if (warp == 0) TR(9);
                float a0 = 0, a1 = 0, a2 = 0, a3 = 0;
                #pragma unroll
                for (int j = 0; j < 4; j++) { a0 += __uint_as_float(v[j].x); a1 += __uint_as_float(v[j].y); a2 += __uint_as_float(v[j].z); a3 += __uint_as_float(v[j].w); }
                a0 += __shfl_xor_sync(~0u, a0, 16); a1 += __shfl_xor_sync(~0u, a1, 16); a2 += __shfl_xor_sync(~0u, a2, 16); a3 += __shfl_xor_sync(~0u, a3, 16);
                float* cr = reinterpret_cast<float*>(smem + SM_CRED);
                if (lane < 16) *reinterpret_cast<float4*>(cr + warp * 64 + lane * 4) = make_float4(a0, a1, a2, a3);
                nbar_sync(4, 128);
                {
                    int rho = lane >> 2, pp = lane & 3;
                    int i0 = ((2 * pp) * 4 + (rho >> 1)) * 2 + (rho & 1), i1 = i0 + 8;
                    uint32_t wv = pack_bf16((cr[i0] + cr[64 + i0]) + (cr[128 + i0] + cr[192 + i0]), (cr[i1] + cr[64 + i1]) + (cr[128 + i1] + cr[192 + i1]));
                    if (wv == 0) wv = 0x8000u;
                    if (warp == 0) TR(10);
                    const uint32_t* tp = reinterpret_cast<const uint32_t*>(smem + SM_TPUB) + warp;
                    st_relaxed1(pool + tp[((s + 1) & 3) * 8] + lane * 4, wv);
                    st_relaxed1(pool + tp[((s + 1) & 3) * 8 + 4] + lane * 4, wv);
                    st_relaxed1(pool + tp[(s & 3) * 8] + lane * 4, 0u);
                    st_relaxed1(pool + tp[(s & 3) * 8 + 4] + lane * 4, 0u);
                }
            }
            {
                const int c0 = warp * 160 + lane;
                const uint32_t* tg3 = reinterpret_cast<const uint32_t*>(smem + SM_TGAT) + ((s + 1) & 3) * 4;
                const uint32_t g0 = tg3[0], g1 = tg3[1], g2 = tg3[2];
                uint4 v[5]; int guard = 0;
                #pragma unroll
                for (int j = 0; j < 5; j++) v[j] = make_uint4(0, 0, 0, 0);
                uint32_t pend = 0x1F;
                do {
                    #pragma unroll
                    for (int j = 0; j < 5; j++) {
                        const int c = c0 + 32 * j;
                        if (pend & (1u << j)) v[j] = ld_relaxed4(pool + ((c >> 8) == 0 ? g0 : ((c >> 8) == 1 ? g1 : g2)) + (c & 255) * 16);
                    }
                    #pragma unroll
                    for (int j = 0; j < 5; j++) if (v[j].x && v[j].y && v[j].z && v[j].w) pend &= ~(1u << j);
                } while (__any_sync(~0u, pend != 0) && ++guard < (1 << 20));
                #pragma unroll
                for (int j = 0; j < 5; j++) *reinterpret_cast<uint4*>(smem + SM_MEMB + (c0 + 32 * j) * 16) = v[j];
                if (warp == 0) TR(11);
                if (warp == 3) TR(12);
                nbar_arrive(7 + (warp >> 1), 192);
            }
        }
        if (warp < 2) nbar_sync(6, 320);
        if (warp == 1 && lane == 0) export_tiles(sb, NSEG - 1, h, rank);
        __syncwarp();
        nbar_sync(3, 384);
        __syncwarp();
        cluster_sync_all();
    } else {
        asm volatile("setmaxnreg.inc.sync.aligned.u32 232;");
        const int wtid = tid & 127;
        const int cw = wg * 4 + warp;
        uint32_t areg[2][20][4];
        #pragma unroll
        for (int mt = 0; mt < 2; mt++)
            #pragma unroll
            for (int kk = 0; kk < 20; kk++) {
                int mi = lane >> 3;
                int row = 16 * (20 * wg + kk) + (mi >> 1) * 8 + (lane & 7);
                int chunk = 2 * warp + (mi & 1);
                ldsm4t(areg[mt][kk], sb + mt * 81920 + row * 128 + ((chunk ^ (row & 7)) << 4));
            }
        nbar_sync(5, 384);
        nbar_sync(5, 384);
        cluster_sync_all();

        for (int s = -1; s < NSEG; s++) {
            const int sl = s & 1;
            if (s >= 0) {
            if (s > 0) nbar_sync(7 + wg, 192);
            float fin[4];
            {
                float acc[2][2][4];
                #pragma unroll
                for (int i = 0; i < 2; i++)
                    #pragma unroll
                    for (int j = 0; j < 2; j++) { acc[i][j][0] = acc[i][j][1] = acc[i][j][2] = acc[i][j][3] = 0.f; }
                uint32_t b[3][4];
                const uint32_t mb = sb + SM_MEMB + (20 * wg) * 256 + lane * 16;
                ldsm4(b[0], mb); ldsm4(b[1], mb + 512);
                #pragma unroll
                for (int kp = 0; kp < 10; kp++) {
                    if (kp + 2 < 10) ldsm4(b[(kp + 2) % 3], mb + (kp + 2) * 512);
                    const uint32_t (&bb)[4] = b[kp % 3];
                    mma_bf16(acc[0][0], areg[0][2 * kp][0], areg[0][2 * kp][1], areg[0][2 * kp][2], areg[0][2 * kp][3], bb[0], bb[1]);
                    mma_bf16(acc[1][0], areg[1][2 * kp][0], areg[1][2 * kp][1], areg[1][2 * kp][2], areg[1][2 * kp][3], bb[0], bb[1]);
                    mma_bf16(acc[0][1], areg[0][2 * kp + 1][0], areg[0][2 * kp + 1][1], areg[0][2 * kp + 1][2], areg[0][2 * kp + 1][3], bb[2], bb[3]);
                    mma_bf16(acc[1][1], areg[1][2 * kp + 1][0], areg[1][2 * kp + 1][1], areg[1][2 * kp + 1][2], areg[1][2 * kp + 1][3], bb[2], bb[3]);
                }
                float4* red = reinterpret_cast<float4*>(smem + SM_RED);
                float m0[4], m1[4];
                #pragma unroll
                for (int i = 0; i < 4; i++) { m0[i] = acc[0][0][i] + acc[0][1][i]; m1[i] = acc[1][0][i] + acc[1][1][i]; }
                red[(wg ^ 1) * 128 + wtid] = wg == 0 ? make_float4(m1[0], m1[1], m1[2], m1[3]) : make_float4(m0[0], m0[1], m0[2], m0[3]);
                nbar_sync(1, 256);
                float4 r = red[wg * 128 + wtid];
                fin[0] = (wg == 0 ? m0[0] : m1[0]) + r.x; fin[1] = (wg == 0 ? m0[1] : m1[1]) + r.y;
                fin[2] = (wg == 0 ? m0[2] : m1[2]) + r.z; fin[3] = (wg == 0 ? m0[3] : m1[3]) + r.w;
            }
            if (cw == 0) TR(1);
            {
                uint32_t p0 = pack_bf16(fin[0], fin[1]), p1 = pack_bf16(fin[2], fin[3]);
                const uint32_t doff = (rank == 2) ? SM_VT + sl * 10240 + wg * 5120 : (wg == 0 ? SM_QS : SM_KT + sl * 5120);
                const int r = lane & 7, chunk = 2 * warp + ((lane >> 3) & 1);
                const uint32_t coff = doff + r * 128 + ((chunk ^ r) << 4);
                stsm2t(sb + coff, p0, p1);
                if (rank == 2 && s < NSEG - 1) {
                    __syncwarp();
                    const uint4 v = *reinterpret_cast<const uint4*>(smem + coff);
                    const uint32_t rb = mapa(sb, lane >> 4);
                    st_async4u(rb + coff, v, rb + B_V + 8 * sl);
                }
            }
            fence_async();
            nbar_sync(1, 256);
            nbar_arrive(6, 320);
            if (cw == 0) TR(2);
            if (rank < 2 && wg == 1 && s < NSEG - 1) score_tile(sb, sl, 1 + warp, lane, rank);
            if (s == NSEG - 1) break;
            if (cw == 0) TR(3);
            if (wg == 0 || rank == 2) u_pass<2>(smem, sb, s, rank, wg, warp, lane);
            else                      u_pass<1>(smem, sb, s, rank, wg, warp, lane);
            if (cw == 0) TR(7);
            nbar_arrive(3, 384);
            }
            {
                const int sn = s + 1, sln = sn & 1;
                mbar_wait(sb + B_X + 8 * sln, (sn >> 1) & 1);
                float acc[2][16];
                wg_fence();
                #pragma unroll
                for (int mt = 0; mt < 2; mt++)
                    #pragma unroll
                    for (int kk = 0; kk < 20; kk++) {
                        uint64_t db = make_desc(sb + SM_XB + sln * 40960 + (5 * wg + (kk >> 2)) * 4096 + (kk & 3) * 32, 16, 1024);
                        wgmma_n32_rs(acc[mt], areg[mt][kk], db, kk > 0);
                    }
                wg_commit();
                if (cw == 0 && s >= 0) TR(14);
                wg_wait0();
                if (cw == 0 && s >= 0) TR(15);
                float4* red = reinterpret_cast<float4*>(smem + SM_RED);
                #pragma unroll
                for (int j = 0; j < 4; j++) {
                    red[((wg ^ 1) * 4 + j) * 128 + wtid] = make_float4(wg == 0 ? acc[1][4 * j] : acc[0][4 * j], wg == 0 ? acc[1][4 * j + 1] : acc[0][4 * j + 1],
                                                                       wg == 0 ? acc[1][4 * j + 2] : acc[0][4 * j + 2], wg == 0 ? acc[1][4 * j + 3] : acc[0][4 * j + 3]);
                }
                if (s >= 0) mbar_wait(sb + B_EXP, s & 1);
                nbar_sync(1, 256);
                uint32_t pk[8];
                #pragma unroll
                for (int j = 0; j < 4; j++) {
                    float4 r = red[(wg * 4 + j) * 128 + wtid];
                    pk[2 * j] = pack_bf16((wg == 0 ? acc[0][4 * j] : acc[1][4 * j]) + r.x, (wg == 0 ? acc[0][4 * j + 1] : acc[1][4 * j + 1]) + r.y);
                    pk[2 * j + 1] = pack_bf16((wg == 0 ? acc[0][4 * j + 2] : acc[1][4 * j + 2]) + r.z, (wg == 0 ? acc[0][4 * j + 3] : acc[1][4 * j + 3]) + r.w);
                }
                const uint32_t dst = (rank == 2) ? sb + SM_VT + sln * 10240 + wg * 5120 + 1024 : (wg == 0 ? sb + SM_QT : sb + SM_KT + sln * 5120 + 1024);
                #pragma unroll
                for (int jj = 0; jj < 2; jj++) {
                    int mi = lane >> 3, tok = 8 * (2 * jj + (mi >> 1)) + (lane & 7), chunk = 2 * warp + (mi & 1);
                    stsm4t(dst + tok * 128 + ((chunk ^ (tok & 7)) << 4), pk[4 * jj], pk[4 * jj + 1], pk[4 * jj + 2], pk[4 * jj + 3]);
                }
                fence_async();
                nbar_sync(1, 256);
                if (rank == 2 && lane == 0 && cw < 4 && sn < NSEG - 1) {
                    const uint32_t off = SM_VT + sln * 10240 + (cw & 1) * 5120 + 1024;
                    const uint32_t rb = mapa(sb, cw >> 1);
                    bulk_s2c(rb + off, sb + off, 4096, rb + B_V + 8 * sln);
                }
                if (cw == 0 && s >= 0) TR(13);
            }
        }
        nbar_arrive(3, 384);
        __syncwarp();
        cluster_sync_all();
    }
}

#define NAUX 36
__device__ __align__(1024) bf16 g_Oimg[16 * 64 * 128 * 64];
__device__ float    g_acc[SEQ * DM];
__device__ unsigned g_ocnt[16];
__device__ unsigned g_gcnt[16][5];
__device__ unsigned g_ssmcnt, g_auxdone, g_taskctr;
#define NATT 8
#define NTASK (80 + 320)
#define ATR(i) do {} while (0)

__device__ __forceinline__ void wait_counter(const unsigned* p, unsigned target) {
    int guard = 0;
    while ((int)(ld_acquire(p) - target) < 0 && ++guard < (1 << 22)) __nanosleep(64);
}
__device__ __forceinline__ void fence_async_all() { asm volatile("fence.proxy.async;" ::: "memory"); }
__device__ __forceinline__ void wgmma_n128_tB(float (&d)[64], uint64_t da, uint64_t db, int scale_d) {
    asm volatile("{\n.reg .pred p;\nsetp.ne.b32 p, %66, 0;\n"
        "wgmma.mma_async.sync.aligned.m64n128k16.f32.bf16.bf16 "
        "{%0,%1,%2,%3,%4,%5,%6,%7,%8,%9,%10,%11,%12,%13,%14,%15,%16,%17,%18,%19,%20,%21,%22,%23,%24,%25,%26,%27,%28,%29,%30,%31,"
        "%32,%33,%34,%35,%36,%37,%38,%39,%40,%41,%42,%43,%44,%45,%46,%47,%48,%49,%50,%51,%52,%53,%54,%55,%56,%57,%58,%59,%60,%61,%62,%63}, %64, %65, p, 1, 1, 0, 1;\n}\n"
        : "+f"(d[0]), "+f"(d[1]), "+f"(d[2]), "+f"(d[3]), "+f"(d[4]), "+f"(d[5]), "+f"(d[6]), "+f"(d[7]),
          "+f"(d[8]), "+f"(d[9]), "+f"(d[10]), "+f"(d[11]), "+f"(d[12]), "+f"(d[13]), "+f"(d[14]), "+f"(d[15]),
          "+f"(d[16]), "+f"(d[17]), "+f"(d[18]), "+f"(d[19]), "+f"(d[20]), "+f"(d[21]), "+f"(d[22]), "+f"(d[23]),
          "+f"(d[24]), "+f"(d[25]), "+f"(d[26]), "+f"(d[27]), "+f"(d[28]), "+f"(d[29]), "+f"(d[30]), "+f"(d[31]),
          "+f"(d[32]), "+f"(d[33]), "+f"(d[34]), "+f"(d[35]), "+f"(d[36]), "+f"(d[37]), "+f"(d[38]), "+f"(d[39]),
          "+f"(d[40]), "+f"(d[41]), "+f"(d[42]), "+f"(d[43]), "+f"(d[44]), "+f"(d[45]), "+f"(d[46]), "+f"(d[47]),
          "+f"(d[48]), "+f"(d[49]), "+f"(d[50]), "+f"(d[51]), "+f"(d[52]), "+f"(d[53]), "+f"(d[54]), "+f"(d[55]),
          "+f"(d[56]), "+f"(d[57]), "+f"(d[58]), "+f"(d[59]), "+f"(d[60]), "+f"(d[61]), "+f"(d[62]), "+f"(d[63])
        : "l"(da), "l"(db), "r"(scale_d));
}
__device__ __forceinline__ void stsm4(uint32_t addr, uint32_t r0, uint32_t r1, uint32_t r2, uint32_t r3) {
    asm volatile("stmatrix.sync.aligned.m8n8.x4.shared.b16 [%0], {%1,%2,%3,%4};" :: "r"(addr), "r"(r0), "r"(r1), "r"(r2), "r"(r3) : "memory");
}

#define AX_BAR   0
#define AX_DATA  1024
#define AX_UNIT  28672
#define AX_STAGE 32768
#define AX_TOTAL (AX_DATA + 8 * AX_UNIT)

__device__ __forceinline__ void attn_compute(unsigned char* smem, uint32_t sb, uint32_t buf, int warp, int lane);
__device__ __noinline__ void attn_loop(unsigned char* smem, int hg, unsigned epoch) {
    const uint32_t sb = smem_u32(smem);
    const int tid = threadIdx.x, warp = tid >> 5, lane = tid & 31;
    for (int s = 0; s < NSEG; s++) {
        const uint32_t buf = AX_DATA + (s & 1) * (4 * AX_UNIT), bar = sb + AX_BAR + 8 * (s & 1);
        if (warp == 0) {
            if (lane < 4) wait_counter(&g_flag[s][4 * hg + lane], (epoch + 1) * 3u);
            __syncwarp();
            if (lane == 0) mbar_expect_tx(bar, 4 * AX_UNIT);
            __syncwarp();
            if (lane < 24) {
                fence_async_all();
                const int u = lane / 6, r = lane % 6, hf = r & 1, kind = r >> 1;
                const uint32_t ub = sb + buf + u * AX_UNIT;
                const size_t img = ((size_t)(s * NH + 4 * hg + u) * 2) + hf;
                if (kind == 0) bulk_g2s(ub + hf * 4096, g_Qimg + img * 2048, 4096, bar);
                else if (kind == 1) bulk_g2s(ub + 8192 + hf * 5120, g_Kimg + img * 2560, 5120, bar);
                else bulk_g2s(ub + 18432 + hf * 5120, g_Vimg + img * 2560, 5120, bar);
            }
        } else if (warp == 1 && lane < 8 && s > 0) {
            bulk_wait0();
            fence_async_all();
            __threadfence();
            atomicAdd(&g_ocnt[(s - 1) >> 2], 1u);
        }
        mbar_wait(bar, (s >> 1) & 1);
        attn_compute(smem, sb, buf, warp, lane);
        fence_async();
        __syncthreads();
        if (warp == 1 && lane < 8) {
            const int uu = lane >> 1, hf = lane & 1, hh = 4 * hg + uu;
            bulk_s2g(g_Oimg + (((size_t)(s >> 2) * 64 + hh * 2 + hf) * 128 + (s & 3) * 32) * 64, sb + buf + uu * AX_UNIT + hf * 4096, 4096);
            bulk_commit();
        }
    }
    if (warp == 1 && lane < 8) {
        bulk_wait0();
        fence_async_all();
        __threadfence();
        atomicAdd(&g_ocnt[15], 1u);
    }
}
__device__ __forceinline__ void attn_compute(unsigned char* smem, uint32_t sb, uint32_t buf, int warp, int lane) {
    const int g = lane >> 2, t = lane & 3;
    const int u = warp >> 1, qh = warp & 1;
    const uint32_t ub = sb + buf + u * AX_UNIT;
    float sc[5][4];
    #pragma unroll
    for (int j = 0; j < 5; j++) { sc[j][0] = sc[j][1] = sc[j][2] = sc[j][3] = 0.f; }
    #pragma unroll
    for (int ks = 0; ks < 8; ks++) {
        const int hf = ks >> 2, c0 = (ks & 3) * 2;
        uint32_t a[4];
        { int mi = lane >> 3, row = 16 * qh + (mi & 1) * 8 + (lane & 7), chunk = c0 + (mi >> 1);
          ldsm4(a, ub + hf * 4096 + row * 128 + ((chunk ^ (row & 7)) << 4)); }
        #pragma unroll
        for (int jp = 0; jp < 3; jp++) {
            uint32_t b[4];
            int mi = lane >> 3, nt = 2 * jp + (mi >> 1); if (nt > 4) nt = 4;
            int row = 8 * nt + (lane & 7), chunk = c0 + (mi & 1);
            ldsm4(b, ub + 8192 + hf * 5120 + row * 128 + ((chunk ^ (row & 7)) << 4));
            mma_bf16(sc[2 * jp], a[0], a[1], a[2], a[3], b[0], b[1]);
            if (jp < 2) mma_bf16(sc[2 * jp + 1], a[0], a[1], a[2], a[3], b[2], b[3]);
        }
    }
    uint32_t pa[3][4];
    {
        const float sc2 = 0.08838834764831845f * 1.4426950408889634f;
        float mx0 = -3.0e38f, mx1 = -3.0e38f;
        const int q0 = 16 * qh + g, q1 = q0 + 8;
        #pragma unroll
        for (int j = 0; j < 5; j++)
            #pragma unroll
            for (int e = 0; e < 2; e++) {
                int key = 8 * j + 2 * t + e - 8;
                sc[j][e] = (key <= q0) ? sc[j][e] * sc2 : -3.0e38f;
                sc[j][2 + e] = (key <= q1) ? sc[j][2 + e] * sc2 : -3.0e38f;
                mx0 = fmaxf(mx0, sc[j][e]); mx1 = fmaxf(mx1, sc[j][2 + e]);
            }
        mx0 = fmaxf(mx0, __shfl_xor_sync(~0u, mx0, 1)); mx0 = fmaxf(mx0, __shfl_xor_sync(~0u, mx0, 2));
        mx1 = fmaxf(mx1, __shfl_xor_sync(~0u, mx1, 1)); mx1 = fmaxf(mx1, __shfl_xor_sync(~0u, mx1, 2));
        float s0 = 0.f, s1 = 0.f;
        #pragma unroll
        for (int j = 0; j < 5; j++)
            #pragma unroll
            for (int e = 0; e < 2; e++) {
                sc[j][e] = ex2_approx(sc[j][e] - mx0); sc[j][2 + e] = ex2_approx(sc[j][2 + e] - mx1);
                s0 += sc[j][e]; s1 += sc[j][2 + e];
            }
        s0 += __shfl_xor_sync(~0u, s0, 1); s0 += __shfl_xor_sync(~0u, s0, 2);
        s1 += __shfl_xor_sync(~0u, s1, 1); s1 += __shfl_xor_sync(~0u, s1, 2);
        const float i0 = __frcp_rn(s0), i1 = __frcp_rn(s1);
        #pragma unroll
        for (int k = 0; k < 3; k++) {
            pa[k][0] = pack_bf16(sc[2 * k][0] * i0, sc[2 * k][1] * i0);
            pa[k][1] = pack_bf16(sc[2 * k][2] * i1, sc[2 * k][3] * i1);
            if (k < 2) { pa[k][2] = pack_bf16(sc[2 * k + 1][0] * i0, sc[2 * k + 1][1] * i0); pa[k][3] = pack_bf16(sc[2 * k + 1][2] * i1, sc[2 * k + 1][3] * i1); }
            else { pa[k][2] = 0u; pa[k][3] = 0u; }
        }
    }
    __syncwarp();
    nbar_sync(1 + u, 64);
    #pragma unroll
    for (int np = 0; np < 8; np++) {
        const int hf = np >> 2, c0 = (np & 3) * 2;
        float o0[4] = {0, 0, 0, 0}, o1[4] = {0, 0, 0, 0};
        #pragma unroll
        for (int k = 0; k < 3; k++) {
            uint32_t b[4];
            int mi = lane >> 3;
            int row = 16 * k + (mi & 1) * 8 + (lane & 7); if (row > 39) row = 39 - 7 + (lane & 7);
            int chunk = c0 + (mi >> 1);
            ldsm4t(b, ub + 18432 + hf * 5120 + row * 128 + ((chunk ^ (row & 7)) << 4));
            mma_bf16(o0, pa[k][0], pa[k][1], pa[k][2], pa[k][3], b[0], k < 2 ? b[1] : 0u);
            mma_bf16(o1, pa[k][0], pa[k][1], pa[k][2], pa[k][3], b[2], k < 2 ? b[3] : 0u);
        }
        int mi = lane >> 3, row = 16 * qh + (mi & 1) * 8 + (lane & 7), chunk = c0 + (mi >> 1);
        stsm4(ub + hf * 4096 + row * 128 + ((chunk ^ (row & 7)) << 4), pack_bf16(o0[0], o0[1]), pack_bf16(o0[2], o0[3]), pack_bf16(o1[0], o1[1]), pack_bf16(o1[2], o1[3]));
    }
}

__device__ __forceinline__ void gemm_task(unsigned char* smem, const CUtensorMap* womap, int m, int c, int kq, uint32_t& ph_g, unsigned epoch,
                                       bf16* __restrict__ out) {
    const uint32_t sb = smem_u32(smem);
    const int tid = threadIdx.x, lane = tid & 31;
    const int wg = __shfl_sync(~0u, tid >> 7, 0), warp = __shfl_sync(~0u, (tid >> 5) & 3, 0);
    __syncthreads();
    if (tid == 0) { wait_counter(&g_ocnt[m], (epoch + 1) * 256u); fence_async_all(); }
    __syncthreads();
    auto load = [&](int kc) {
        const int st = kc & 3;
        const uint32_t a = sb + AX_DATA + st * AX_STAGE, bar = sb + AX_BAR + 8 + 8 * st;
        mbar_expect_tx(bar, AX_STAGE);
        bulk_g2s(a, g_Oimg + ((size_t)m * 64 + kq * 16 + kc) * 8192, 16384, bar);
        tma_load_2d(a + 16384, womap, c * 128, kq * 1024 + kc * 64, bar);
        tma_load_2d(a + 16384 + 8192, womap, c * 128 + 64, kq * 1024 + kc * 64, bar);
    };
    if (tid == 0) { load(0); load(1); load(2); }
    float acc[64];
    #pragma unroll
    for (int i = 0; i < 64; i++) acc[i] = 0.f;
    for (int kc = 0; kc < 16; kc++) {
        const int st = kc & 3;
        mbar_wait(sb + AX_BAR + 8 + 8 * st, (ph_g >> st) & 1);
        ph_g ^= 1u << st;
        const uint32_t a = sb + AX_DATA + st * AX_STAGE;
        wg_fence();
        #pragma unroll
        for (int ks = 0; ks < 4; ks++)
            wgmma_n128_tB(acc, make_desc(a + wg * 8192 + ks * 32, 16, 1024), make_desc(a + 16384 + ks * 2048, 8192, 1024), 1);
        wg_commit();
        asm volatile("wgmma.wait_group.sync.aligned 1;" ::: "memory");
        __syncthreads();
        if (tid == 0 && kc + 3 < 16) load(kc + 3);
    }
    wg_wait0();
    {
        const int g = lane >> 2, t = lane & 3;
        float* base = g_acc + (size_t)(m * 128 + wg * 64 + warp * 16 + g) * DM + c * 128 + 2 * t;
        #pragma unroll
        for (int j = 0; j < 16; j++) {
            asm volatile("red.global.add.v2.f32 [%0], {%1,%2};" :: "l"(base + j * 8), "f"(acc[4 * j]), "f"(acc[4 * j + 1]) : "memory");
            asm volatile("red.global.add.v2.f32 [%0], {%1,%2};" :: "l"(base + 8 * DM + j * 8), "f"(acc[4 * j + 2]), "f"(acc[4 * j + 3]) : "memory");
        }
    }
    __threadfence();
    __syncthreads();
    __shared__ int s_last;
    if (tid == 0) { unsigned old = atomicAdd(&g_gcnt[m][c], 1u); s_last = ((old + 1) == (epoch + 1) * 4u); if (s_last) wait_counter(&g_ssmcnt, (epoch + 1) * 80u); __threadfence(); }
    __syncthreads();
    if (s_last) {
        for (int i = tid; i < 128 * 32; i += 256) {
            const int r = m * 128 + (i >> 5), cc = c * 128 + (i & 31) * 4;
            float4* pa = reinterpret_cast<float4*>(g_acc + (size_t)r * DM + cc);
            float4 a; asm volatile("ld.relaxed.gpu.global.v4.f32 {%0,%1,%2,%3}, [%4];" : "=f"(a.x), "=f"(a.y), "=f"(a.z), "=f"(a.w) : "l"(pa) : "memory");
            *pa = make_float4(0.f, 0.f, 0.f, 0.f);
            float gt; asm volatile("ld.relaxed.gpu.global.f32 %0, [%1];" : "=f"(gt) : "l"(g_g + r) : "memory");
            uint2 bb; asm volatile("ld.relaxed.gpu.global.v2.u32 {%0,%1}, [%2];" : "=r"(bb.x), "=r"(bb.y) : "l"(g_b + (size_t)r * DM + cc) : "memory");
            const float b0 = __uint_as_float(bb.x << 16), b1 = __uint_as_float(bb.x & 0xffff0000u), b2 = __uint_as_float(bb.y << 16), b3 = __uint_as_float(bb.y & 0xffff0000u);
            uint2 o; o.x = pack_bf16(gt * a.x + (1.f - gt) * b0, gt * a.y + (1.f - gt) * b1); o.y = pack_bf16(gt * a.z + (1.f - gt) * b2, gt * a.w + (1.f - gt) * b3);
            *reinterpret_cast<uint2*>(out + (size_t)r * DM + cc) = o;
        }
    }
}

__global__ void __launch_bounds__(256, 1)
k_aux(const __grid_constant__ CUtensorMap womap, const bf16* __restrict__ x, const bf16* __restrict__ A_re, const bf16* __restrict__ A_im,
      const bf16* __restrict__ B_re, const bf16* __restrict__ B_im, const bf16* __restrict__ C_re, const bf16* __restrict__ C_im,
      const bf16* __restrict__ log_dt, const bf16* __restrict__ Dskip, const bf16* __restrict__ gw, bf16* __restrict__ out) {
    extern __shared__ __align__(1024) unsigned char smem[];
    const uint32_t sb = smem_u32(smem);
    const int tid = threadIdx.x, warp = tid >> 5, lane = tid & 31;
    __shared__ unsigned s_epoch;
    if (tid == 0) {
        for (int i = 0; i < 5; i++) mbar_init(sb + AX_BAR + 8 * i, 1);
        asm volatile("fence.mbarrier_init.release.cluster;" ::: "memory");
        s_epoch = *reinterpret_cast<volatile unsigned*>(&g_epoch);
    }
    __syncthreads();
    const unsigned epoch = s_epoch;
    ATR(0);
    uint32_t ph_g = 0;
    __shared__ int s_task;
    int ntask = 0;
    if (blockIdx.x < NATT) attn_loop(smem, blockIdx.x, epoch);
    else for (;;) {
        __syncthreads();
        if (tid == 0) s_task = (int)(atomicAdd(&g_taskctr, 1u) - epoch * (unsigned)(NTASK + NAUX - NATT));
        __syncthreads();
        const int task = s_task;
        if (task >= NTASK) break;
        if (task < 80) {
            for (int r = task * 26 + warp; r < min(SEQ, task * 26 + 26); r += 8) {
                float sum = 0.f;
                for (int i = lane * 2; i < DM; i += 64) {
                    __nv_bfloat162 xv = *reinterpret_cast<const __nv_bfloat162*>(x + (size_t)r * DM + i), wv = *reinterpret_cast<const __nv_bfloat162*>(gw + i);
                    sum += bf2f(xv.x) * bf2f(wv.x) + bf2f(xv.y) * bf2f(wv.y);
                }
                #pragma unroll
                for (int o = 16; o; o >>= 1) sum += __shfl_xor_sync(~0u, sum, o);
                if (lane == 0) g_g[r] = 1.f / (1.f + expf(-sum));
            }
            ssm_group(smem + AX_DATA, task, x, A_re, A_im, B_re, B_im, C_re, C_im, log_dt, Dskip);
            __threadfence();
            __syncthreads();
            if (tid == 0) atomicAdd(&g_ssmcnt, 1u);
        } else {
            const int j = task - 80, m = j / 20, r = j % 20;
            gemm_task(smem, &womap, m, r % 5, r / 5, ph_g, epoch, out);
        }
        if (ntask < 60) ATR(2 + ntask);
        ntask++;
    }
    __syncthreads();
    if (tid == 0) {
        __threadfence();
        unsigned old = atomicAdd(&g_auxdone, 1u);
        if (old == NAUX - 1) { g_auxdone = 0; __threadfence(); atomicAdd(&g_epoch, 1u); }
    }
    asm volatile("griddepcontrol.wait;" ::: "memory");
}

extern "C" void kernel_launch(void* const* d_in, const int* in_sizes, int n_in, void* d_out, int out_size) {
    const bf16* x = (const bf16*)d_in[0];
    const bf16* mem0 = (const bf16*)d_in[1];
    const bf16* Wq = (const bf16*)d_in[2];
    const bf16* Wk = (const bf16*)d_in[3];
    const bf16* Wv = (const bf16*)d_in[4];
    const bf16* Wo = (const bf16*)d_in[5];
    const bf16 *A_re = (const bf16*)d_in[8], *A_im = (const bf16*)d_in[9], *B_re = (const bf16*)d_in[10], *B_im = (const bf16*)d_in[11];
    const bf16 *C_re = (const bf16*)d_in[12], *C_im = (const bf16*)d_in[13], *log_dt = (const bf16*)d_in[14], *Dskip = (const bf16*)d_in[15];
    const bf16* gw = (const bf16*)d_in[16];
    bf16* out = (bf16*)d_out;
    cudaStream_t st = cudaStreamPerThread;
    static bool init = false;
    static CUtensorMap xmap, womap;
    static const void* xmap_ptr = nullptr; static const void* womap_ptr = nullptr;
    if (!init) {
        cudaFuncSetAttribute(k_chain, cudaFuncAttributeMaxDynamicSharedMemorySize, SM_TOTAL);
        cudaFuncSetAttribute(k_aux, cudaFuncAttributeMaxDynamicSharedMemorySize, AX_TOTAL);
        init = true;
    }
    if (xmap_ptr != (const void*)x || womap_ptr != (const void*)Wo) {
        void* fn = nullptr; cudaDriverEntryPointQueryResult qres;
        cudaGetDriverEntryPoint("cuTensorMapEncodeTiled", &fn, cudaEnableDefault, &qres);
        typedef CUresult (*EncFn)(CUtensorMap*, CUtensorMapDataType, cuuint32_t, void*, const cuuint64_t*, const cuuint64_t*, const cuuint32_t*, const cuuint32_t*,
                                  CUtensorMapInterleave, CUtensorMapSwizzle, CUtensorMapL2promotion, CUtensorMapFloatOOBfill);
        cuuint32_t es[2] = {1, 1};
        { cuuint64_t dims[2] = {DM, SEQ}; cuuint64_t strides[1] = {DM * 2}; cuuint32_t box[2] = {64, 32};
          ((EncFn)fn)(&xmap, CU_TENSOR_MAP_DATA_TYPE_BFLOAT16, 2, (void*)x, dims, strides, box, es, CU_TENSOR_MAP_INTERLEAVE_NONE, CU_TENSOR_MAP_SWIZZLE_128B,
                      CU_TENSOR_MAP_L2_PROMOTION_L2_128B, CU_TENSOR_MAP_FLOAT_OOB_FILL_NONE); }
        { cuuint64_t dims[2] = {DM, HD}; cuuint64_t strides[1] = {DM * 2}; cuuint32_t box[2] = {64, 64};
          ((EncFn)fn)(&womap, CU_TENSOR_MAP_DATA_TYPE_BFLOAT16, 2, (void*)Wo, dims, strides, box, es, CU_TENSOR_MAP_INTERLEAVE_NONE, CU_TENSOR_MAP_SWIZZLE_128B,
                      CU_TENSOR_MAP_L2_PROMOTION_L2_128B, CU_TENSOR_MAP_FLOAT_OOB_FILL_NONE); }
        xmap_ptr = (const void*)x; womap_ptr = (const void*)Wo;
    }
    k_chain<<<96, 384, SM_TOTAL, st>>>(xmap, mem0, Wq, Wk, Wv, Wo);
    {
        cudaLaunchConfig_t cfg = {};
        cfg.gridDim = dim3(NAUX); cfg.blockDim = dim3(256); cfg.dynamicSmemBytes = AX_TOTAL; cfg.stream = st;
        cudaLaunchAttribute at[1];
        at[0].id = cudaLaunchAttributeProgrammaticStreamSerialization; at[0].val.programmaticStreamSerializationAllowed = 1;
        cfg.attrs = at; cfg.numAttrs = 1;
        cudaLaunchKernelEx(&cfg, k_aux, womap, x, A_re, A_im, B_re, B_im, C_re, C_im, log_dt, Dskip, gw, out);
    }
}
```

```cpp
#include <cuda_runtime.h>
#include <cuda_bf16.h>
#include <stdint.h>
#include <cuda.h>

typedef __nv_bfloat16 bf16;

#define SEQ 2048
#define DM 640
#define NH 32
#define DH 128
#define NM 8
#define SEG 32
#define NSEG 64
#define NST 128
#define HD 4096

__device__ bf16  g_b[SEQ * DM];
__device__ float g_g[SEQ];

__device__ __forceinline__ float bf2f(bf16 v) { return __bfloat162float(v); }
__device__ __forceinline__ uint32_t pack_bf16(float lo, float hi) {
    uint32_t r; asm("cvt.rn.bf16x2.f32 %0, %1, %2;" : "=r"(r) : "f"(hi), "f"(lo)); return r;
}
__device__ __forceinline__ uint32_t f2tf32(float x) { uint32_t r; asm("cvt.rna.tf32.f32 %0, %1;" : "=r"(r) : "f"(x)); return r; }
__device__ __forceinline__ void mma_tf32(float (&d)[4], uint32_t a0, uint32_t a1, uint32_t a2, uint32_t a3, uint32_t b0, uint32_t b1) {
    asm volatile("mma.sync.aligned.m16n8k8.row.col.f32.tf32.tf32.f32 {%0,%1,%2,%3}, {%4,%5,%6,%7}, {%8,%9}, {%0,%1,%2,%3};\n"
        : "+f"(d[0]), "+f"(d[1]), "+f"(d[2]), "+f"(d[3]) : "r"(a0), "r"(a1), "r"(a2), "r"(a3), "r"(b0), "r"(b1));
}
__device__ __forceinline__ void mma_bf16(float (&d)[4], uint32_t a0, uint32_t a1, uint32_t a2, uint32_t a3, uint32_t b0, uint32_t b1) {
    asm volatile("mma.sync.aligned.m16n8k16.row.col.f32.bf16.bf16.f32 {%0,%1,%2,%3}, {%4,%5,%6,%7}, {%8,%9}, {%0,%1,%2,%3};\n"
        : "+f"(d[0]), "+f"(d[1]), "+f"(d[2]), "+f"(d[3]) : "r"(a0), "r"(a1), "r"(a2), "r"(a3), "r"(b0), "r"(b1));
}
struct cf { float re, im; };
__device__ __forceinline__ cf cmul(cf a, cf b) { cf r; r.re = a.re * b.re - a.im * b.im; r.im = a.re * b.im + a.im * b.re; return r; }
__device__ __forceinline__ cf csq(cf a) { cf r; r.re = a.re * a.re - a.im * a.im; r.im = 2.f * a.re * a.im; return r; }
__device__ __forceinline__ cf cexpL(float zr, float zi, float L) {
    float e = __expf(zr * L);
    float ang = zi * L;
    float k = rintf(ang * 0.15915494309189535f);
    ang = fmaf(-k, 6.2831854820251465f, ang);
    ang = fmaf(-k, -1.7484555314695172e-07f, ang);
    cf r; r.re = e * __cosf(ang); r.im = e * __sinf(ang); return r;
}

#define SSM_CH 8
#define KC_PITCH 648
#define XS_PITCH (2048 + 8)
#define KT_LEN (2048 + 48)
#define PART_PITCH 20
struct SsmSmem {
    float Kc[SSM_CH][KC_PITCH];
    bf16  xs[SSM_CH][XS_PITCH];
    bf16  KT[2][KT_LEN];
    union {
        float part[8][128 * PART_PITCH];
        float st[SSM_CH][NST][8];
    } u;
    bf16  ys[SSM_CH][XS_PITCH];
    uint16_t kidx[2048];
};

__device__ __forceinline__ int kc_index(int l) {
    return l < 256 ? l : (l < 512 ? 256 + ((l - 256) >> 1) : (l < 1024 ? 384 + ((l - 512) >> 2) : 512 + ((l - 1024) >> 3)));
}

__device__ __forceinline__ void ssm_group(unsigned char* smem_raw, int grp, const bf16* __restrict__ x, const bf16* __restrict__ A_re, const bf16* __restrict__ A_im,
        const bf16* __restrict__ B_re, const bf16* __restrict__ B_im, const bf16* __restrict__ C_re, const bf16* __restrict__ C_im,
        const bf16* __restrict__ log_dt, const bf16* __restrict__ Dskip) {
    SsmSmem& S = *reinterpret_cast<SsmSmem*>(smem_raw);
    const int tid = threadIdx.x, w = tid >> 5, lane = tid & 31, g = lane >> 2, t = lane & 3;
    const int d0 = grp * SSM_CH;
    asm volatile("bar.sync 1, 256;" ::: "memory");
    #pragma unroll
    for (int it = 0; it < 8; it++) {
        const int l = tid + 256 * it;
        uint4 v = *reinterpret_cast<const uint4*>(x + (size_t)l * DM + d0);
        const bf16* p = reinterpret_cast<const bf16*>(&v);
        const int lr = (l & ~15) | (15 - (l & 15));
        #pragma unroll
        for (int c = 0; c < 8; c++) S.xs[c][lr] = p[c];
        S.kidx[l] = (uint16_t)((int)bf2f(__float2bfloat16_rn((float)l)) == 2048 ? 640 : kc_index((int)bf2f(__float2bfloat16_rn((float)l))));
    }
    if (tid < 48) { const int i = tid < 16 ? tid : 2048 + tid; S.KT[0][i] = __float2bfloat16_rn(0.f); if (i > 0) S.KT[1][i - 1] = __float2bfloat16_rn(0.f); }
    if (tid == 48) S.KT[1][KT_LEN - 1] = __float2bfloat16_rn(0.f);
    {
        const int d = d0 + w;
        const float dt = bf2f(__float2bfloat16_rn(expf(bf2f(log_dt[d]))));
        #pragma unroll
        for (int i = 0; i < 4; i++) {
            const int n = lane + 32 * i;
            float zr = dt * bf2f(A_re[d * NST + n]), zi = dt * bf2f(A_im[d * NST + n]);
            cf dB; dB.re = dt * bf2f(B_re[d * NST + n]); dB.im = dt * bf2f(B_im[d * NST + n]);
            cf C; C.re = bf2f(C_re[d * NST + n]); C.im = bf2f(C_im[d * NST + n]);
            cf wv = cmul(C, dB);
            cf u8 = cexpL(zr, zi, 8.f), u128 = cexpL(zr, zi, 128.f);
            float* st = S.u.st[w][n];
            *reinterpret_cast<float4*>(st) = make_float4(zr, zi, wv.re, wv.im);
            *reinterpret_cast<float4*>(st + 4) = make_float4(u8.re, u8.im, u128.re, u128.im);
        }
        __syncwarp();
        float a0a[4] = {0, 0, 0, 0}, a0b[4] = {0, 0, 0, 0}, a1[4] = {0, 0, 0, 0}, a2a[4] = {0, 0, 0, 0}, a2b[4] = {0, 0, 0, 0};
        float k2048 = 0.f;
        const float Lg = (g < 4) ? (512.f + 4.f * g) : (g < 6 ? 1024.f + 8.f * (g - 4) : 1536.f + 8.f * (g - 6));
        #pragma unroll 4
        for (int kk = 0; kk < 32; kk++) {
            const float* st = S.u.st[w][4 * kk + t];
            float4 s0 = *reinterpret_cast<const float4*>(st), s1 = *reinterpret_cast<const float4*>(st + 4);
            cf wv; wv.re = s0.z; wv.im = s0.w;
            cf u8; u8.re = s1.x; u8.im = s1.y;
            cf u128; u128.re = s1.z; u128.im = s1.w;
            cf e1 = cexpL(s0.x, s0.y, (float)g);
            cf e23 = cexpL(s0.x, s0.y, Lg);
            cf e1b = cmul(e1, u8);
            cf e2 = csq(e1);
            cf p = csq(csq(csq(e2)));
            cf f0 = cmul(wv, p), f1 = cmul(f0, u128), f2 = cmul(f1, u128), f3 = cmul(f2, u128);
            uint32_t A00 = f2tf32(f0.re), A01 = f2tf32(f1.re), A02 = f2tf32(-f0.im), A03 = f2tf32(-f1.im);
            uint32_t A10 = f2tf32(f2.re), A11 = f2tf32(f3.re), A12 = f2tf32(-f2.im), A13 = f2tf32(-f3.im);
            mma_tf32(a0a, A00, A01, A02, A03, f2tf32(e1.re), f2tf32(e1.im));
            mma_tf32(a0b, A00, A01, A02, A03, f2tf32(e1b.re), f2tf32(e1b.im));
            mma_tf32(a1, A10, A11, A12, A13, f2tf32(e2.re), f2tf32(e2.im));
            uint32_t E0 = f2tf32(e23.re), E1 = f2tf32(e23.im);
            mma_tf32(a2a, A00, A01, A02, A03, E0, E1);
            mma_tf32(a2b, A10, A11, A12, A13, E0, E1);
            cf e2048 = csq(e23);
            k2048 += wv.re * e2048.re - wv.im * e2048.im;
        }
        k2048 += __shfl_xor_sync(~0u, k2048, 1);
        k2048 += __shfl_xor_sync(~0u, k2048, 2);
        float* Kc = S.Kc[w];
        Kc[16 * g + 2 * t] = a0a[0]; Kc[16 * g + 2 * t + 1] = a0a[1]; Kc[16 * (g + 8) + 2 * t] = a0a[2]; Kc[16 * (g + 8) + 2 * t + 1] = a0a[3];
        Kc[16 * g + 8 + 2 * t] = a0b[0]; Kc[16 * g + 8 + 2 * t + 1] = a0b[1]; Kc[16 * (g + 8) + 8 + 2 * t] = a0b[2]; Kc[16 * (g + 8) + 8 + 2 * t + 1] = a0b[3];
        Kc[256 + 8 * g + 2 * t] = a1[0]; Kc[256 + 8 * g + 2 * t + 1] = a1[1]; Kc[256 + 8 * (g + 8) + 2 * t] = a1[2]; Kc[256 + 8 * (g + 8) + 2 * t + 1] = a1[3];
        #pragma unroll
        for (int mt = 0; mt < 2; mt++) {
            #pragma unroll
            for (int e = 0; e < 4; e++) {
                int A = mt * 16 + g + (e >> 1) * 8, j = 2 * t + (e & 1);
                int Lj = (j < 4) ? 512 + 4 * j : (j < 6 ? 1024 + 8 * (j - 4) : 1536 + 8 * (j - 6));
                Kc[kc_index(Lj + 16 * A)] = mt ? a2b[e] : a2a[e];
            }
        }
        if (lane == 16) Kc[640] = k2048;
    }
    for (int c = 0; c < SSM_CH; c++) {
        asm volatile("bar.sync 1, 256;" ::: "memory");
        #pragma unroll
        for (int it = 0; it < 8; it++) {
            const int j = tid + 256 * it;
            const bf16 v = __float2bfloat16_rn(S.Kc[c][S.kidx[j]]);
            S.KT[0][16 + j] = v;
            S.KT[1][15 + j] = v;
        }
        uint32_t B[16][2];
        #pragma unroll
        for (int v = 0; v < 16; v++) {
            const bf16* p = &S.xs[c][16 * (8 * v + g) + 2 * t];
            B[v][0] = *reinterpret_cast<const uint32_t*>(p);
            B[v][1] = *reinterpret_cast<const uint32_t*>(p + 8);
        }
        asm volatile("bar.sync 1, 256;" ::: "memory");
        float acc[16][4];
        #pragma unroll
        for (int v = 0; v < 16; v++) { acc[v][0] = acc[v][1] = acc[v][2] = acc[v][3] = 0.f; }
        const bf16* kt = (g & 1) ? &S.KT[0][0] : &S.KT[1][0];
        const int ibase = 16 * w + g + 1 + 2 * t - ((g & 1) ? 0 : 1);
        #pragma unroll
        for (int q = 0; q < 16; q++) {
            const int i0 = ibase + 128 * q;
            uint32_t A0 = *reinterpret_cast<const uint32_t*>(kt + i0);
            uint32_t A1 = *reinterpret_cast<const uint32_t*>(kt + i0 + 8);
            uint32_t A3 = *reinterpret_cast<const uint32_t*>(kt + i0 + 16);
            #pragma unroll
            for (int v = q; v < 16; v++) mma_bf16(acc[v], A0, A1, A1, A3, B[v - q][0], B[v - q][1]);
        }
        float* part = S.u.part[w];
        #pragma unroll
        for (int v = 0; v < 16; v++) {
            int a = 8 * v + 2 * t + w;
            if (v < 15 || a < 128) { part[a * PART_PITCH + g] = acc[v][0]; part[a * PART_PITCH + g + 8] = acc[v][2]; }
            if (v < 15 || a + 1 < 128) { part[(a + 1) * PART_PITCH + g] = acc[v][1]; part[(a + 1) * PART_PITCH + g + 8] = acc[v][3]; }
        }
        asm volatile("bar.sync 1, 256;" ::: "memory");
        const float dsk = bf2f(Dskip[d0 + c]);
        #pragma unroll
        for (int it = 0; it < 2; it++) {
            const int l = (tid + 256 * it) * 4, a = l >> 4, b = l & 15;
            float4 sum = make_float4(0.f, 0.f, 0.f, 0.f);
            #pragma unroll
            for (int r = 0; r < 8; r++)
                if (a >= r) { float4 v = *reinterpret_cast<const float4*>(&S.u.part[r][a * PART_PITCH + b]); sum.x += v.x; sum.y += v.y; sum.z += v.z; sum.w += v.w; }
            const uint2 xr = *reinterpret_cast<const uint2*>(&S.xs[c][(l & ~15) + 12 - b]);
            const float x3 = __uint_as_float(xr.x << 16), x2 = __uint_as_float(xr.x & 0xffff0000u), x1 = __uint_as_float(xr.y << 16), x0 = __uint_as_float(xr.y & 0xffff0000u);
            auto fin = [&](float y, float xv) { return bf2f(__float2bfloat16_rn(y)) + bf2f(__float2bfloat16_rn(xv * dsk)); };
            uint2 o; o.x = pack_bf16(fin(sum.x, x0), fin(sum.y, x1)); o.y = pack_bf16(fin(sum.z, x2), fin(sum.w, x3));
            *reinterpret_cast<uint2*>(&S.ys[c][l]) = o;
        }
    }
    asm volatile("bar.sync 1, 256;" ::: "memory");
    #pragma unroll
    for (int it = 0; it < 8; it++) {
        const int l = tid + 256 * it;
        uint32_t wv[4];
        #pragma unroll
        for (int c = 0; c < 4; c++)
            wv[c] = (uint32_t)*reinterpret_cast<const uint16_t*>(&S.ys[2 * c][l]) | ((uint32_t)*reinterpret_cast<const uint16_t*>(&S.ys[2 * c + 1][l]) << 16);
        *reinterpret_cast<uint4*>(g_b + (size_t)l * DM + d0) = make_uint4(wv[0], wv[1], wv[2], wv[3]);
    }
}

__device__ __forceinline__ uint32_t smem_u32(const void* p) { return (uint32_t)__cvta_generic_to_shared(p); }
__device__ __forceinline__ void mbar_init(uint32_t bar, uint32_t cnt) { asm volatile("mbarrier.init.shared::cta.b64 [%0], %1;" :: "r"(bar), "r"(cnt) : "memory"); }
__device__ __forceinline__ void mbar_expect_tx(uint32_t bar, uint32_t bytes) { asm volatile("mbarrier.arrive.expect_tx.shared::cta.b64 _, [%0], %1;" :: "r"(bar), "r"(bytes) : "memory"); }
__device__ __forceinline__ void mbar_arrive(uint32_t bar) { asm volatile("mbarrier.arrive.shared::cta.b64 _, [%0];" :: "r"(bar) : "memory"); }
__device__ __forceinline__ void mbar_wait(uint32_t bar, uint32_t parity) {
    uint32_t ok; int guard = 0;
    do {
        asm volatile("{\n.reg .pred P1;\nmbarrier.test_wait.parity.shared::cta.b64 P1, [%1], %2;\nselp.u32 %0,1,0,P1;\n}" : "=r"(ok) : "r"(bar), "r"(parity) : "memory");
    } while (!ok && ++guard < (1 << 26));
}
__device__ __forceinline__ void mbar_wait_sleep(uint32_t bar, uint32_t parity) {
    uint32_t ok; int guard = 0;
    do {
        asm volatile("{\n.reg .pred P1;\nmbarrier.try_wait.parity.shared::cta.b64 P1, [%1], %2;\nselp.u32 %0,1,0,P1;\n}" : "=r"(ok) : "r"(bar), "r"(parity) : "memory");
    } while (!ok && ++guard < (1 << 22));
}
__device__ __forceinline__ uint32_t mapa(uint32_t addr, uint32_t rank) { uint32_t r; asm volatile("mapa.shared::cluster.u32 %0, %1, %2;" : "=r"(r) : "r"(addr), "r"(rank)); return r; }
__device__ __forceinline__ void st_async4(uint32_t addr, float a, float b, float c, float d, uint32_t bar) {
    asm volatile("st.async.weak.shared::cluster.mbarrier::complete_tx::bytes.v4.f32 [%0], {%1,%2,%3,%4}, [%5];" :: "r"(addr), "f"(a), "f"(b), "f"(c), "f"(d), "r"(bar) : "memory");
}
__device__ __forceinline__ void bulk_s2c(uint32_t dst, uint32_t src, uint32_t bytes, uint32_t bar) {
    asm volatile("cp.async.bulk.shared::cluster.shared::cta.mbarrier::complete_tx::bytes [%0], [%1], %2, [%3];" :: "r"(dst), "r"(src), "r"(bytes), "r"(bar) : "memory");
}
__device__ __forceinline__ void bulk_g2s(uint32_t dst, const void* src, uint32_t bytes, uint32_t bar) {
    asm volatile("cp.async.bulk.shared::cluster.global.mbarrier::complete_tx::bytes [%0], [%1], %2, [%3];" :: "r"(dst), "l"(src), "r"(bytes), "r"(bar) : "memory");
}
__device__ __forceinline__ void bulk_s2g(void* dst, uint32_t src, uint32_t bytes) {
    asm volatile("cp.async.bulk.global.shared::cta.bulk_group [%0], [%1], %2;" :: "l"(dst), "r"(src), "r"(bytes) : "memory");
}
__device__ __forceinline__ void bulk_commit() { asm volatile("cp.async.bulk.commit_group;" ::: "memory"); }
__device__ __forceinline__ void bulk_wait_read0() { asm volatile("cp.async.bulk.wait_group.read 0;" ::: "memory"); }
__device__ __forceinline__ void bulk_wait0() { asm volatile("cp.async.bulk.wait_group 0;" ::: "memory"); }
__device__ __forceinline__ void fence_async() { asm volatile("fence.proxy.async.shared::cta;" ::: "memory"); }
__device__ __forceinline__ void nbar_sync(int id, int n) { asm volatile("bar.sync %0, %1;" :: "r"(id), "r"(n) : "memory"); }
__device__ __forceinline__ void nbar_arrive(int id, int n) { asm volatile("bar.arrive %0, %1;" :: "r"(id), "r"(n) : "memory"); }
__device__ __forceinline__ void cp_async16(uint32_t dst, const void* src) { asm volatile("cp.async.cg.shared.global [%0], [%1], 16;" :: "r"(dst), "l"(src) : "memory"); }
__device__ __forceinline__ void cp_async_wait_all() { asm volatile("cp.async.wait_all;" ::: "memory"); }
__device__ __forceinline__ void ldsm4(uint32_t (&r)[4], uint32_t addr) {
    asm volatile("ldmatrix.sync.aligned.m8n8.x4.shared.b16 {%0,%1,%2,%3}, [%4];" : "=r"(r[0]), "=r"(r[1]), "=r"(r[2]), "=r"(r[3]) : "r"(addr) : "memory");
}
__device__ __forceinline__ void ldsm4t(uint32_t (&r)[4], uint32_t addr) {
    asm volatile("ldmatrix.sync.aligned.m8n8.x4.trans.shared.b16 {%0,%1,%2,%3}, [%4];" : "=r"(r[0]), "=r"(r[1]), "=r"(r[2]), "=r"(r[3]) : "r"(addr) : "memory");
}
__device__ __forceinline__ void stsm2t(uint32_t addr, uint32_t r0, uint32_t r1) {
    asm volatile("stmatrix.sync.aligned.m8n8.x2.trans.shared.b16 [%0], {%1,%2};" :: "r"(addr), "r"(r0), "r"(r1) : "memory");
}
__device__ __forceinline__ uint4 ld_relaxed4(const void* p) { uint4 v; asm volatile("ld.relaxed.gpu.global.v4.u32 {%0,%1,%2,%3}, [%4];" : "=r"(v.x), "=r"(v.y), "=r"(v.z), "=r"(v.w) : "l"(p) : "memory"); return v; }
__device__ __forceinline__ void st_relaxed2(void* p, uint32_t a, uint32_t b) { asm volatile("st.relaxed.gpu.global.v2.u32 [%0], {%1,%2};" :: "l"(p), "r"(a), "r"(b) : "memory"); }
__device__ __forceinline__ void st_relaxed1(void* p, uint32_t a) { asm volatile("st.relaxed.gpu.global.u32 [%0], %1;" :: "l"(p), "r"(a) : "memory"); }
__device__ __forceinline__ unsigned ld_acquire(const unsigned* p) { unsigned v; asm volatile("ld.acquire.gpu.global.u32 %0, [%1];" : "=r"(v) : "l"(p) : "memory"); return v; }
__device__ __forceinline__ float ex2_approx(float x) { float r; asm("ex2.approx.ftz.f32 %0, %1;" : "=f"(r) : "f"(x)); return r; }
__device__ __forceinline__ uint64_t make_desc(uint32_t saddr, uint32_t lbo, uint32_t sbo) {
    return (uint64_t)((saddr & 0x3FFFF) >> 4) | ((uint64_t)((lbo & 0x3FFFF) >> 4) << 16) | ((uint64_t)((sbo & 0x3FFFF) >> 4) << 32) | (1ull << 62);
}
__device__ __forceinline__ void wg_fence() { asm volatile("wgmma.fence.sync.aligned;" ::: "memory"); }
__device__ __forceinline__ void wg_commit() { asm volatile("wgmma.commit_group.sync.aligned;" ::: "memory"); }
__device__ __forceinline__ void wg_wait0() { asm volatile("wgmma.wait_group.sync.aligned 0;" ::: "memory"); }
__device__ __forceinline__ void wgmma_n40_tA(float (&d)[20], uint64_t da, uint64_t db, int scale_d) {
    asm volatile("{\n.reg .pred p;\nsetp.ne.b32 p, %22, 0;\n"
        "wgmma.mma_async.sync.aligned.m64n40k16.f32.bf16.bf16 {%0,%1,%2,%3,%4,%5,%6,%7,%8,%9,%10,%11,%12,%13,%14,%15,%16,%17,%18,%19}, %20, %21, p, 1, 1, 1, 0;\n}\n"
        : "+f"(d[0]), "+f"(d[1]), "+f"(d[2]), "+f"(d[3]), "+f"(d[4]), "+f"(d[5]), "+f"(d[6]), "+f"(d[7]), "+f"(d[8]), "+f"(d[9]),
          "+f"(d[10]), "+f"(d[11]), "+f"(d[12]), "+f"(d[13]), "+f"(d[14]), "+f"(d[15]), "+f"(d[16]), "+f"(d[17]), "+f"(d[18]), "+f"(d[19])
        : "l"(da), "l"(db), "r"(scale_d));
}

#define NREP 8
#define NRED 80
#define CAL_THR 410u
#define COMM_REGS "40"
#define NPOOL 576
#define RPS 4
__device__ __align__(4096) uint32_t g_pool[(NPOOL + 1) * 1024];
__device__ unsigned g_cls[NPOOL];
__device__ unsigned g_side[96];
__device__ unsigned g_calcnt;
__device__ unsigned g_epoch;
__device__ unsigned g_flag[NSEG][NH];
__device__ __align__(1024) bf16 g_Qimg[NSEG * NH * 2 * 32 * 64];
__device__ __align__(1024) bf16 g_Kimg[NSEG * NH * 2 * 40 * 64];
__device__ __align__(1024) bf16 g_Vimg[NSEG * NH * 2 * 40 * 64];

#define SM_XB    0
#define SM_VT    81920
#define SM_KT    (SM_VT + 20480)
#define SM_QT    (SM_KT + 10240)
#define SM_QS    (SM_QT + 4096)
#define SM_MEMB  (SM_QS + 1024)
#define SM_RED   (SM_MEMB + 10240)
#define SM_SC    (SM_RED + 16384)
#define SM_CRED  (SM_SC + 5120)
#define SM_PB    (SM_CRED + 1024)
#define SM_TRACE (SM_PB + 1024)
#define SM_WO    163840
#define SM_BAR   (SM_WO + 65536)
#define SM_TPM   (SM_BAR + 256)
#define SM_TRD   (SM_TPM + 256)
#define SM_TPUB  (SM_TRD + 16)
#define SM_TGAT  (SM_TPUB + 128)
#define SM_CAL   (SM_TGAT + 64)
#define SM_TOTAL (SM_CAL + 128)
#define B_SC   (SM_BAR + 0)
#define B_V    (SM_BAR + 16)
#define B_MEM  (SM_BAR + 32)
#define B_P    (SM_BAR + 48)
#define B_X    (SM_BAR + 56)
#define B_EXP  (SM_BAR + 72)

#define TR(ev) do {} while (0)
__device__ __forceinline__ uint32_t tag_of(int s) { return (uint32_t)(((s >> 1) & 1) + 1); }
__device__ __forceinline__ unsigned probe_latency(uint32_t* p, uint32_t zero) {
    uint32_t v, best = 0xffffffffu;
    asm volatile("atom.relaxed.gpu.global.add.u32 %0, [%1], 0;" : "=r"(v) : "l"(p) : "memory");
    #pragma unroll 1
    for (int r = 0; r < 4; r++) {
        uint32_t c0, c1;
        asm volatile("mov.u32 %0, %%clock;" : "=r"(c0) : "r"(v) : "memory");
        asm volatile("atom.relaxed.gpu.global.add.u32 %0, [%1], 0;" : "=r"(v) : "l"(p + ((v + c0) & zero)) : "memory");
        asm volatile("{\n.reg .u32 t;\nand.b32 t, %1, %2;\nmov.u32 %0, %%clock;\nadd.u32 %0, %0, t;\n}" : "=r"(c1) : "r"(v), "r"(zero) : "memory");
        best = min(best, c1 - c0);
    }
    return best;
}
__device__ __forceinline__ void cluster_sync_all() { asm volatile("barrier.cluster.arrive.release.aligned;\nbarrier.cluster.wait.acquire.aligned;" ::: "memory"); }
__device__ __forceinline__ void tma_load_2d(uint32_t dst, const void* map, int c0, int c1, uint32_t bar) {
    asm volatile("cp.async.bulk.tensor.2d.shared::cluster.global.mbarrier::complete_tx::bytes [%0], [%1, {%3, %4}], [%2];"
        :: "r"(dst), "l"(map), "r"(bar), "r"(c0), "r"(c1) : "memory");
}
__device__ __forceinline__ void stsm4t(uint32_t addr, uint32_t r0, uint32_t r1, uint32_t r2, uint32_t r3) {
    asm volatile("stmatrix.sync.aligned.m8n8.x4.trans.shared.b16 [%0], {%1,%2,%3,%4};" :: "r"(addr), "r"(r0), "r"(r1), "r"(r2), "r"(r3) : "memory");
}
__device__ __forceinline__ void wgmma_n32_rs(float (&d)[16], const uint32_t (&a)[4], uint64_t db, int scale_d) {
    asm volatile("{\n.reg .pred p;\nsetp.ne.b32 p, %21, 0;\n"
        "wgmma.mma_async.sync.aligned.m64n32k16.f32.bf16.bf16 {%0,%1,%2,%3,%4,%5,%6,%7,%8,%9,%10,%11,%12,%13,%14,%15}, {%16,%17,%18,%19}, %20, p, 1, 1, 0;\n}\n"
        : "+f"(d[0]), "+f"(d[1]), "+f"(d[2]), "+f"(d[3]), "+f"(d[4]), "+f"(d[5]), "+f"(d[6]), "+f"(d[7]),
          "+f"(d[8]), "+f"(d[9]), "+f"(d[10]), "+f"(d[11]), "+f"(d[12]), "+f"(d[13]), "+f"(d[14]), "+f"(d[15])
        : "r"(a[0]), "r"(a[1]), "r"(a[2]), "r"(a[3]), "l"(db), "r"(scale_d));
}

__device__ __forceinline__ void st_async4u(uint32_t addr, uint4 v, uint32_t bar) {
    asm volatile("st.async.weak.shared::cluster.mbarrier::complete_tx::bytes.v4.u32 [%0], {%1,%2,%3,%4}, [%5];" :: "r"(addr), "r"(v.x), "r"(v.y), "r"(v.z), "r"(v.w), "r"(bar) : "memory");
}
__device__ __forceinline__ void export_tiles(uint32_t sb, int s, int h, uint32_t rank) {
    const size_t img = (size_t)(s * NH + h) * 2;
    const int sl = s & 1;
    if (rank == 2) {
        bulk_s2g(g_Vimg + img * 2560, sb + SM_VT + sl * 10240, 5120);
        bulk_s2g(g_Vimg + (img + 1) * 2560, sb + SM_VT + sl * 10240 + 5120, 5120);
    } else {
        bulk_s2g(g_Qimg + (img + rank) * 2048, sb + SM_QT, 4096);
        bulk_s2g(g_Kimg + (img + rank) * 2560, sb + SM_KT + sl * 5120, 5120);
    }
    bulk_commit();
    bulk_wait_read0();
    mbar_arrive(sb + B_EXP);
    bulk_wait0();
    asm volatile("fence.proxy.async;" ::: "memory");
    __threadfence();
    atomicAdd(&g_flag[s][h], 1u);
}

__device__ __forceinline__ void score_tile(uint32_t sb, int sl, int nt, int lane, uint32_t rank) {
    float sc[4] = {0, 0, 0, 0}, sd[4] = {0, 0, 0, 0};
    const int r = lane & 7;
    uint32_t qa[2][4], kb[2][4];
    #pragma unroll
    for (int j = 0; j < 2; j++) {
        const int chunk = (lane >> 3) + 4 * j;
        ldsm4(kb[j], sb + SM_KT + sl * 5120 + (8 * nt + r) * 128 + ((chunk ^ r) << 4));
        ldsm4(qa[j], sb + SM_QS + r * 128 + ((chunk ^ r) << 4));
    }
    mma_bf16(sc, qa[0][0], 0u, qa[0][1], 0u, kb[0][0], kb[0][1]);
    mma_bf16(sd, qa[1][0], 0u, qa[1][1], 0u, kb[1][0], kb[1][1]);
    mma_bf16(sc, qa[0][2], 0u, qa[0][3], 0u, kb[0][2], kb[0][3]);
    mma_bf16(sd, qa[1][2], 0u, qa[1][3], 0u, kb[1][2], kb[1][3]);
    sc[0] += sd[0]; sc[1] += sd[1];
    const float o0 = __shfl_down_sync(~0u, sc[0], 1), o1 = __shfl_down_sync(~0u, sc[1], 1);
    if ((lane & 1) == 0) {
        const uint32_t a = SM_SC + sl * 2560 + rank * 1280 + ((lane >> 2) * 40 + 8 * nt + 2 * (lane & 3)) * 4;
        const uint32_t bo = B_SC + 8 * sl;
        #pragma unroll
        for (int d = 0; d < 3; d++) { const uint32_t rb = mapa(sb, d); st_async4(rb + a, sc[0], sc[1], o0, o1, rb + bo); }
    }
}
__device__ __forceinline__ void wgmma_n40_rs(float (&d)[20], const uint32_t (&a)[4], uint64_t db, int scale_d) {
    asm volatile("{\n.reg .pred p;\nsetp.ne.b32 p, %25, 0;\n"
        "wgmma.mma_async.sync.aligned.m64n40k16.f32.bf16.bf16 {%0,%1,%2,%3,%4,%5,%6,%7,%8,%9,%10,%11,%12,%13,%14,%15,%16,%17,%18,%19}, {%20,%21,%22,%23}, %24, p, 1, 1, 0;\n}\n"
        : "+f"(d[0]), "+f"(d[1]), "+f"(d[2]), "+f"(d[3]), "+f"(d[4]), "+f"(d[5]), "+f"(d[6]), "+f"(d[7]), "+f"(d[8]), "+f"(d[9]),
          "+f"(d[10]), "+f"(d[11]), "+f"(d[12]), "+f"(d[13]), "+f"(d[14]), "+f"(d[15]), "+f"(d[16]), "+f"(d[17]), "+f"(d[18]), "+f"(d[19])
        : "r"(a[0]), "r"(a[1]), "r"(a[2]), "r"(a[3]), "l"(db), "r"(scale_d));
}
__device__ __forceinline__ void pu_store(const float (&u)[20], const uint32_t (&pb)[5], float2 inv, unsigned char* smem, int sl, int lt, int warp, int lane, uint32_t tg) {
    float o[4] = {0, 0, 0, 0}, o2[4] = {0, 0, 0, 0};
    mma_bf16(o, pack_bf16(u[0], u[1]), pack_bf16(u[2], u[3]), pack_bf16(u[4], u[5]), pack_bf16(u[6], u[7]), pb[0], pb[1]);
    mma_bf16(o2, pack_bf16(u[8], u[9]), pack_bf16(u[10], u[11]), pack_bf16(u[12], u[13]), pack_bf16(u[14], u[15]), pb[2], pb[3]);
    mma_bf16(o, pack_bf16(u[16], u[17]), pack_bf16(u[18], u[19]), 0u, 0u, pb[4], 0u);
    const uint2 off = *reinterpret_cast<const uint2*>(smem + SM_TPM + (((sl * 4 + lt) * 4 + warp) * 2) * 4);
    unsigned char* pool = reinterpret_cast<unsigned char*>(g_pool) + lane * 8;
    st_relaxed2(pool + off.x, (__float_as_uint((o[0] + o2[0]) * inv.x) & ~3u) | tg, (__float_as_uint((o[1] + o2[1]) * inv.y) & ~3u) | tg);
    st_relaxed2(pool + off.y, (__float_as_uint((o[2] + o2[2]) * inv.x) & ~3u) | tg, (__float_as_uint((o[3] + o2[3]) * inv.y) & ~3u) | tg);
}
template <int NT>
__device__ __forceinline__ void u_pass(unsigned char* smem, uint32_t sb, int s, uint32_t rank, int wg, int warp, int lane) {
    const int sl = s & 1;
    constexpr int NRS = 6;
    uint32_t wa[NRS][4];
    {
        const int mi = lane >> 3, chunk = 2 * warp + (mi & 1);
        #pragma unroll
        for (int ks = 0; ks < NRS; ks++) {
            const int row = 16 * ks + (mi >> 1) * 8 + (lane & 7);
            ldsm4t(wa[ks], sb + SM_WO + (2 * wg) * 16384 + row * 128 + ((chunk ^ (row & 7)) << 4));
        }
    }
    if (rank < 2) { mbar_wait(sb + B_V + 8 * sl, (s >> 1) & 1); fence_async(); }
    if (wg == 0 && warp == 0) TR(4);
    float U0[20];
    wg_fence();
    #pragma unroll
    for (int ks = 0; ks < NRS; ks++)
        wgmma_n40_rs(U0, wa[ks], make_desc(sb + SM_VT + sl * 10240 + (ks >> 2) * 5120 + (ks & 3) * 32, 16, 1024), ks > 0);
    #pragma unroll
    for (int ks = NRS; ks < 8; ks++)
        wgmma_n40_tA(U0, make_desc(sb + SM_WO + (2 * wg) * 16384 + ks * 2048, 1024, 1024),
                     make_desc(sb + SM_VT + sl * 10240 + (ks >> 2) * 5120 + (ks & 3) * 32, 16, 1024), 1);
    wg_commit();
    const uint32_t tg = tag_of(s);
    uint32_t pb[5];
    float2 inv;
    auto get_p = [&]() {
        nbar_sync(9, 288);
        const uint32_t* pbs = reinterpret_cast<const uint32_t*>(smem + SM_PB);
        #pragma unroll
        for (int q = 0; q < 5; q++) pb[q] = pbs[q * 32 + lane];
        float sm[4] = {0, 0, 0, 0}, sm2[4] = {0, 0, 0, 0};
        const uint32_t one = 0x3f803f80u;
        mma_bf16(sm, one, one, one, one, pb[0], pb[1]);
        mma_bf16(sm2, one, one, one, one, pb[2], pb[3]);
        mma_bf16(sm, one, one, 0u, 0u, pb[4], 0u);
        inv.x = __frcp_rn(sm[0] + sm2[0]); inv.y = __frcp_rn(sm[1] + sm2[1]);
    };
    if (NT == 2) {
        wg_wait0();
        float U1[20];
        wg_fence();
        #pragma unroll
        for (int ks = 0; ks < 8; ks++)
            wgmma_n40_tA(U1, make_desc(sb + SM_WO + (2 * wg + 1) * 16384 + ks * 2048, 1024, 1024),
                         make_desc(sb + SM_VT + sl * 10240 + (ks >> 2) * 5120 + (ks & 3) * 32, 16, 1024), ks > 0);
        wg_commit();
        get_p();
        if (wg == 0 && warp == 0) TR(8);
        pu_store(U0, pb, inv, smem, sl, 2 * wg, warp, lane, tg);
        wg_wait0();
        if (wg == 0 && warp == 0) TR(6);
        pu_store(U1, pb, inv, smem, sl, 2 * wg + 1, warp, lane, tg);
    } else {
        wg_wait0();
        get_p();
        pu_store(U0, pb, inv, smem, sl, 2 * wg, warp, lane, tg);
    }
}

__global__ void __cluster_dims__(3, 1, 1) __launch_bounds__(384, 1)
k_chain(const __grid_constant__ CUtensorMap xmap, const bf16* __restrict__ xptr, const bf16* __restrict__ mem0, const bf16* __restrict__ Wq, const bf16* __restrict__ Wk,
        const bf16* __restrict__ Wv, const bf16* __restrict__ Wo) {
    extern __shared__ __align__(1024) unsigned char smem[];
    const uint32_t sb = smem_u32(smem);
    const int tid = threadIdx.x, lane = tid & 31;
    const int wg = __shfl_sync(~0u, tid >> 7, 0), warp = __shfl_sync(~0u, (tid >> 5) & 3, 0);
    uint32_t rank; asm volatile("mov.u32 %0, %%cluster_ctarank;" : "=r"(rank));
    const int cta = blockIdx.x, h = cta / 3;
    asm volatile("griddepcontrol.launch_dependents;");
    if (tid == 0) {
        for (int i = 0; i < 2; i++) { mbar_init(sb + B_SC + 8 * i, 1); mbar_init(sb + B_V + 8 * i, 1); mbar_init(sb + B_MEM + 8 * i, 64); mbar_init(sb + B_X + 8 * i, 1); }
        mbar_init(sb + B_P, 32); mbar_init(sb + B_EXP, 1);
        asm volatile("fence.mbarrier_init.release.cluster;" ::: "memory");
    }
    if (tid < 80) asm volatile("prefetch.global.L2 [%0];" :: "l"(mem0 + tid * 64));
    if (h < 2) { for (int i = tid; i < 320; i += 384) asm volatile("prefetch.global.L2 [%0];" :: "l"(xptr + (size_t)h * 32 * DM + i * 64)); }
    {
        const int w12 = tid >> 5;
        if (lane == 0 && w12 < 7) {
            uint32_t* pp = (w12 < 6) ? g_pool + (size_t)(cta * 6 + w12) * 1024 + 512 : g_pool + (size_t)NPOOL * 1024 + (cta & 31) * 32 + (cta >> 5) * 8;
            const unsigned lat = probe_latency(pp, blockIdx.y);
            if (w12 < 6) g_cls[cta * 6 + w12] = lat > CAL_THR ? 1u : 0u; else g_side[cta] = lat > CAL_THR ? 1u : 0u;
        }
        __syncwarp();
        uint4* z = reinterpret_cast<uint4*>(g_pool + (size_t)cta * 6 * 1024);
        #pragma unroll
        for (int q = 0; q < 4; q++) z[tid + 384 * q] = make_uint4(0, 0, 0, 0);
        __threadfence();
        __syncwarp();
        if (lane == 0) atomicAdd(&g_calcnt, 1u);
    }
    {
        const int ntile = (rank == 2) ? 4 : 3;
        const int tile0 = (rank == 2) ? 0 : (rank == 0 ? 4 : 7);
        const bf16* src0 = (rank == 2) ? Wv + h * DH : Wq + h * DH + rank * 64;
        const bf16* src1 = (rank == 2) ? Wv + h * DH + 64 : Wk + h * DH + rank * 64;
        for (int i = tid; i < 2 * 640 * 8; i += 384) {
            int mt = i / 5120, r = (i % 5120) >> 3, c = i & 7;
            const bf16* s = (mt ? src1 : src0) + (size_t)r * HD + c * 8;
            cp_async16(sb + mt * 81920 + r * 128 + ((c ^ (r & 7)) << 4), s);
        }
        for (int i = tid; i < ntile * 128 * 8; i += 384) {
            int lt = i >> 10, r = (i >> 3) & 127, c = i & 7;
            const bf16* s = Wo + ((size_t)h * DH + r) * DM + (tile0 + lt) * 64 + c * 8;
            cp_async16(sb + SM_WO + lt * 16384 + r * 128 + ((c ^ (r & 7)) << 4), s);
        }
        if (wg == 2) {
            const int ct = tid & 127;
            if (ct == 0) {
                const unsigned target = (*reinterpret_cast<volatile unsigned*>(&g_epoch) + 1u) * (96u * 12u);
                int guard = 0;
                while ((int)(ld_acquire(&g_calcnt) - target) < 0 && ++guard < (1 << 22)) {}
            }
            nbar_sync(4, 128);
            uint32_t* bm = reinterpret_cast<uint32_t*>(smem + SM_CAL);
            {
                unsigned v[5];
                #pragma unroll
                for (int q = 0; q < 5; q++) { const int b = ct + 128 * q; v[q] = (b < NPOOL) ? (__ldcg(&g_cls[b]) ^ __ldcg(&g_side[b / 6])) : 0u; }
                const unsigned sv = (ct < 96) ? __ldcg(&g_side[ct]) : 0u;
                #pragma unroll
                for (int q = 0; q < 5; q++) { const unsigned m = __ballot_sync(~0u, v[q] & 1u); if (lane == 0 && q * 4 + warp < 18) bm[q * 4 + warp] = m; }
                const unsigned m = __ballot_sync(~0u, sv & 1u);
                if (lane == 0 && warp < 3) bm[18 + warp] = m;
            }
            nbar_sync(4, 128);
            int nblk1 = 0;
            for (int i = 0; i < 18; i++) nblk1 += __popc(bm[i]);
            const unsigned red_last = (1u << (NRED - 64)) - 1u;
            const int nred1 = __popc(bm[18]) + __popc(bm[19]) + __popc(bm[20] & red_last);
            auto side_of = [&](int c) -> int { return (bm[18 + (c >> 5)] >> (c & 31)) & 1; };
            auto rank_of = [&](int c) -> int {
                int ones = 0;
                for (int i = 0; i < (c >> 5); i++) ones += __popc(bm[18 + i]);
                ones += __popc(bm[18 + (c >> 5)] & ((1u << (c & 31)) - 1u));
                return side_of(c) ? ones : c - ones;
            };
            auto nth = [&](int side, int idx) -> uint32_t {
                for (int i = 0; i < 18; i++) {
                    const unsigned m = side ? bm[i] : ~bm[i];
                    const int n = __popc(m);
                    if (idx < n) return (uint32_t)(i * 32 + __fns(m, 0, idx + 1));
                    idx -= n;
                }
                return 0u;
            };
            auto phys = [&](int side, int idx) -> uint32_t {
                const int c = side ? nblk1 : NPOOL - nblk1;
                return (idx < c) ? nth(side, idx) : nth(side ^ 1, (NPOOL - c) - 1 - (idx - c));
            };
            const int e = ct;
            if (e < 64) {
                const int slot = e >> 5, lt = (e >> 3) & 3, w = (e >> 1) & 3, hf = e & 1;
                const int tile = min(tile0 + lt, 9);
                const int r = 2 * (4 * tile + w) + hf;
                reinterpret_cast<uint32_t*>(smem + SM_TPM)[e] = phys(side_of(r), 4 * rank_of(r) + slot * 2 + (h >> 4)) * 4096u + (h & 15) * 256u;
            } else if (e < 68) {
                const int i = e - 64;
                reinterpret_cast<uint32_t*>(smem + SM_TRD)[i] = (cta < NRED) ? phys(side_of(cta), 4 * rank_of(cta) + i) * 4096u : 0u;
            } else if (e < 100) {
                const int i = e - 68, slot = i >> 3, rep = i & 7, side = rep / RPS;
                reinterpret_cast<uint32_t*>(smem + SM_TPUB)[i] = phys(side, 4 * (side ? nred1 : NRED - nred1) + (slot * RPS + (rep % RPS)) * 3 + (cta >> 5)) * 4096u + (cta & 31) * 128u;
            } else if (e < 112) {
                const int i = e - 100, slot = i / 3, b = i % 3, side = side_of(cta);
                reinterpret_cast<uint32_t*>(smem + SM_TGAT)[slot * 4 + b] = phys(side, 4 * (side ? nred1 : NRED - nred1) + (slot * RPS + (h % RPS)) * 3 + b) * 4096u;
            }
        }
        cp_async_wait_all();
        fence_async();
    }
    __syncthreads();

    if (wg == 2) {
        asm volatile("setmaxnreg.dec.sync.aligned.u32 " COMM_REGS ";");
        const int ct = tid & 127;
        nbar_sync(5, 384);
        for (int c = ct; c < 640; c += 128) {
            int ks = c >> 4, hf = (c >> 3) & 1, r = c & 7;
            *reinterpret_cast<uint4*>(smem + SM_MEMB + c * 16) = *reinterpret_cast<const uint4*>(mem0 + r * DM + ks * 16 + hf * 8);
        }
        if (ct == 0) {
            for (int sg = 0; sg < 2; sg++) {
                mbar_expect_tx(sb + B_X + 8 * sg, 40960);
                for (int c = 0; c < 10; c++) tma_load_2d(sb + SM_XB + sg * 40960 + c * 4096, &xmap, c * 64, sg * 32, sb + B_X + 8 * sg);
            }
            mbar_expect_tx(sb + B_SC, 2560);
            if (rank < 2) mbar_expect_tx(sb + B_V, 8192 + 2048);
        }
        nbar_sync(5, 384);
        cluster_sync_all();
        unsigned char* const pool = reinterpret_cast<unsigned char*>(g_pool);
        for (int s = 0; s < NSEG - 1; s++) {
            if (warp < 2) nbar_sync(6, 320);
            if (warp == 0) {
                if (rank < 2) score_tile(sb, s & 1, 0, lane, rank);
                const int g = lane >> 2, t = lane & 3;
                mbar_wait(sb + B_SC + 8 * (s & 1), (s >> 1) & 1);
                TR(5);
                const uint32_t sa = sb + SM_SC + (s & 1) * 2560 + (g * 40 + 2 * t) * 4;
                float v[5][2], u[5][2];
                #pragma unroll
                for (int q = 0; q < 5; q++) {
                    asm volatile("ld.shared.v2.f32 {%0,%1}, [%2];" : "=f"(v[q][0]), "=f"(v[q][1]) : "r"(sa + 32 * q) : "memory");
                    asm volatile("ld.shared.v2.f32 {%0,%1}, [%2];" : "=f"(u[q][0]), "=f"(u[q][1]) : "r"(sa + 1280 + 32 * q) : "memory");
                }
                float mx = -3.0e38f;
                #pragma unroll
                for (int q = 0; q < 5; q++) {
                    v[q][0] += u[q][0]; v[q][1] += u[q][1];
                    mx = fmaxf(mx, fmaxf(v[q][0], v[q][1]));
                }
                mx = fmaxf(mx, __shfl_xor_sync(~0u, mx, 1));
                mx = fmaxf(mx, __shfl_xor_sync(~0u, mx, 2));
                const float sc2 = 0.08838834764831845f * 1.4426950408889634f;
                const float mxs = mx * sc2;
                uint32_t* pbs = reinterpret_cast<uint32_t*>(smem + SM_PB);
                #pragma unroll
                for (int q = 0; q < 5; q++) {
                    const float e0 = ex2_approx(fmaf(v[q][0], sc2, -mxs)), e1 = ex2_approx(fmaf(v[q][1], sc2, -mxs));
                    pbs[q * 32 + lane] = pack_bf16(e0, e1);
                }
                __syncwarp();
                TR(0);
                nbar_arrive(9, 288);
            } else if (warp == 1 && lane == 0) {
                if (s + 1 < NSEG - 1) {
                    mbar_expect_tx(sb + B_SC + 8 * ((s + 1) & 1), 2560);
                    if (rank < 2) mbar_expect_tx(sb + B_V + 8 * ((s + 1) & 1), 8192 + 2048);
                }
                if (s + 2 < NSEG) {
                    mbar_expect_tx(sb + B_X + 8 * (s & 1), 40960);
                    for (int c = 0; c < 10; c++) tma_load_2d(sb + SM_XB + (s & 1) * 40960 + c * 4096, &xmap, c * 64, (s + 2) * 32, sb + B_X + 8 * (s & 1));
                }
                export_tiles(sb, s, h, rank);
            }
            __syncwarp();
            nbar_sync(3, 384);
            const uint32_t tg = tag_of(s);
            if (cta < NRED) {
                const unsigned char* base = pool + reinterpret_cast<const uint32_t*>(smem + SM_TRD)[(s & 1) * 2 + (warp >> 1)] + (warp & 1) * 2048 + lane * 16;
                uint4 v[4]; int guard = 0;
                #pragma unroll
                for (int j = 0; j < 4; j++) v[j] = make_uint4(0, 0, 0, 0);
                uint32_t pend = 0xF;
                do {
                    #pragma unroll
                    for (int j = 0; j < 4; j++) if (pend & (1u << j)) v[j] = ld_relaxed4(base + j * 512);
                    #pragma unroll
                    for (int j = 0; j < 4; j++)
                        if (((v[j].x & 3) == tg) && ((v[j].y & 3) == tg) && ((v[j].z & 3) == tg) && ((v[j].w & 3) == tg)) pend &= ~(1u << j);
                } while (__any_sync(~0u, pend != 0) && ++guard < (1 << 20));
                if (warp == 0) TR(9);
                float a0 = 0, a1 = 0, a2 = 0, a3 = 0;
                #pragma unroll
                for (int j = 0; j < 4; j++) { a0 += __uint_as_float(v[j].x); a1 += __uint_as_float(v[j].y); a2 += __uint_as_float(v[j].z); a3 += __uint_as_float(v[j].w); }
                a0 += __shfl_xor_sync(~0u, a0, 16); a1 += __shfl_xor_sync(~0u, a1, 16); a2 += __shfl_xor_sync(~0u, a2, 16); a3 += __shfl_xor_sync(~0u, a3, 16);
                float* cr = reinterpret_cast<float*>(smem + SM_CRED);
                if (lane < 16) *reinterpret_cast<float4*>(cr + warp * 64 + lane * 4) = make_float4(a0, a1, a2, a3);
                nbar_sync(4, 128);
                {
                    int rho = lane >> 2, pp = lane & 3;
                    int i0 = ((2 * pp) * 4 + (rho >> 1)) * 2 + (rho & 1), i1 = i0 + 8;
                    uint32_t wv = pack_bf16((cr[i0] + cr[64 + i0]) + (cr[128 + i0] + cr[192 + i0]), (cr[i1] + cr[64 + i1]) + (cr[128 + i1] + cr[192 + i1]));
                    if (wv == 0) wv = 0x8000u;
                    if (warp == 0) TR(10);
                    const uint32_t* tp = reinterpret_cast<const uint32_t*>(smem + SM_TPUB) + warp;
                    st_relaxed1(pool + tp[((s + 1) & 3) * 8] + lane * 4, wv);
                    st_relaxed1(pool + tp[((s + 1) & 3) * 8 + 4] + lane * 4, wv);
                    st_relaxed1(pool + tp[(s & 3) * 8] + lane * 4, 0u);
                    st_relaxed1(pool + tp[(s & 3) * 8 + 4] + lane * 4, 0u);
                }
            }
            {
                const int c0 = warp * 160 + lane;
                const uint32_t* tg3 = reinterpret_cast<const uint32_t*>(smem + SM_TGAT) + ((s + 1) & 3) * 4;
                const uint32_t g0 = tg3[0], g1 = tg3[1], g2 = tg3[2];
                uint4 v[5]; int guard = 0;
                #pragma unroll
                for (int j = 0; j < 5; j++) v[j] = make_uint4(0, 0, 0, 0);
                uint32_t pend = 0x1F;
                do {
                    #pragma unroll
                    for (int j = 0; j < 5; j++) {
                        const int c = c0 + 32 * j;
                        if (pend & (1u << j)) v[j] = ld_relaxed4(pool + ((c >> 8) == 0 ? g0 : ((c >> 8) == 1 ? g1 : g2)) + (c & 255) * 16);
                    }
                    #pragma unroll
                    for (int j = 0; j < 5; j++) if (v[j].x && v[j].y && v[j].z && v[j].w) pend &= ~(1u << j);
                } while (__any_sync(~0u, pend != 0) && ++guard < (1 << 20));
                #pragma unroll
                for (int j = 0; j < 5; j++) *reinterpret_cast<uint4*>(smem + SM_MEMB + (c0 + 32 * j) * 16) = v[j];
                if (warp == 0) TR(11);
                if (warp == 3) TR(12);
                nbar_arrive(7 + (warp >> 1), 192);
            }
        }
        if (warp < 2) nbar_sync(6, 320);
        if (warp == 1 && lane == 0) export_tiles(sb, NSEG - 1, h, rank);
        __syncwarp();
        nbar_sync(3, 384);
        __syncwarp();
        cluster_sync_all();
    } else {
        asm volatile("setmaxnreg.inc.sync.aligned.u32 232;");
        const int wtid = tid & 127;
        const int cw = wg * 4 + warp;
        uint32_t areg[2][20][4];
        #pragma unroll
        for (int mt = 0; mt < 2; mt++)
            #pragma unroll
            for (int kk = 0; kk < 20; kk++) {
                int mi = lane >> 3;
                int row = 16 * (20 * wg + kk) + (mi >> 1) * 8 + (lane & 7);
                int chunk = 2 * warp + (mi & 1);
                ldsm4t(areg[mt][kk], sb + mt * 81920 + row * 128 + ((chunk ^ (row & 7)) << 4));
            }
        nbar_sync(5, 384);
        nbar_sync(5, 384);
        cluster_sync_all();

        for (int s = -1; s < NSEG; s++) {
            const int sl = s & 1;
            if (s >= 0) {
            if (s > 0) nbar_sync(7 + wg, 192);
            float fin[4];
            {
                float acc[2][2][4];
                #pragma unroll
                for (int i = 0; i < 2; i++)
                    #pragma unroll
                    for (int j = 0; j < 2; j++) { acc[i][j][0] = acc[i][j][1] = acc[i][j][2] = acc[i][j][3] = 0.f; }
                uint32_t b[3][4];
                const uint32_t mb = sb + SM_MEMB + (20 * wg) * 256 + lane * 16;
                ldsm4(b[0], mb); ldsm4(b[1], mb + 512);
                #pragma unroll
                for (int kp = 0; kp < 10; kp++) {
                    if (kp + 2 < 10) ldsm4(b[(kp + 2) % 3], mb + (kp + 2) * 512);
                    const uint32_t (&bb)[4] = b[kp % 3];
                    mma_bf16(acc[0][0], areg[0][2 * kp][0], areg[0][2 * kp][1], areg[0][2 * kp][2], areg[0][2 * kp][3], bb[0], bb[1]);
                    mma_bf16(acc[1][0], areg[1][2 * kp][0], areg[1][2 * kp][1], areg[1][2 * kp][2], areg[1][2 * kp][3], bb[0], bb[1]);
                    mma_bf16(acc[0][1], areg[0][2 * kp + 1][0], areg[0][2 * kp + 1][1], areg[0][2 * kp + 1][2], areg[0][2 * kp + 1][3], bb[2], bb[3]);
                    mma_bf16(acc[1][1], areg[1][2 * kp + 1][0], areg[1][2 * kp + 1][1], areg[1][2 * kp + 1][2], areg[1][2 * kp + 1][3], bb[2], bb[3]);
                }
                float4* red = reinterpret_cast<float4*>(smem + SM_RED);
                float m0[4], m1[4];
                #pragma unroll
                for (int i = 0; i < 4; i++) { m0[i] = acc[0][0][i] + acc[0][1][i]; m1[i] = acc[1][0][i] + acc[1][1][i]; }
                red[(wg ^ 1) * 128 + wtid] = wg == 0 ? make_float4(m1[0], m1[1], m1[2], m1[3]) : make_float4(m0[0], m0[1], m0[2], m0[3]);
                nbar_sync(1, 256);
                float4 r = red[wg * 128 + wtid];
                fin[0] = (wg == 0 ? m0[0] : m1[0]) + r.x; fin[1] = (wg == 0 ? m0[1] : m1[1]) + r.y;
                fin[2] = (wg == 0 ? m0[2] : m1[2]) + r.z; fin[3] = (wg == 0 ? m0[3] : m1[3]) + r.w;
            }
            if (cw == 0) TR(1);
            {
                uint32_t p0 = pack_bf16(fin[0], fin[1]), p1 = pack_bf16(fin[2], fin[3]);
                const uint32_t doff = (rank == 2) ? SM_VT + sl * 10240 + wg * 5120 : (wg == 0 ? SM_QS : SM_KT + sl * 5120);
                const int r = lane & 7, chunk = 2 * warp + ((lane >> 3) & 1);
                const uint32_t coff = doff + r * 128 + ((chunk ^ r) << 4);
                stsm2t(sb + coff, p0, p1);
                if (rank == 2 && s < NSEG - 1) {
                    __syncwarp();
                    const uint4 v = *reinterpret_cast<const uint4*>(smem + coff);
                    const uint32_t rb = mapa(sb, lane >> 4);
                    st_async4u(rb + coff, v, rb + B_V + 8 * sl);
                }
            }
            fence_async();
            nbar_sync(1, 256);
            nbar_arrive(6, 320);
            if (cw == 0) TR(2);
            if (rank < 2 && wg == 1 && s < NSEG - 1) score_tile(sb, sl, 1 + warp, lane, rank);
            if (s == NSEG - 1) break;
            if (cw == 0) TR(3);
            if (wg == 0 || rank == 2) u_pass<2>(smem, sb, s, rank, wg, warp, lane);
            else                      u_pass<1>(smem, sb, s, rank, wg, warp, lane);
            if (cw == 0) TR(7);
            nbar_arrive(3, 384);
            }
            {
                const int sn = s + 1, sln = sn & 1;
                mbar_wait(sb + B_X + 8 * sln, (sn >> 1) & 1);
                float acc[2][16];
                wg_fence();
                #pragma unroll
                for (int mt = 0; mt < 2; mt++)
                    #pragma unroll
                    for (int kk = 0; kk < 20; kk++) {
                        uint64_t db = make_desc(sb + SM_XB + sln * 40960 + (5 * wg + (kk >> 2)) * 4096 + (kk & 3) * 32, 16, 1024);
                        wgmma_n32_rs(acc[mt], areg[mt][kk], db, kk > 0);
                    }
                wg_commit();
                if (cw == 0 && s >= 0) TR(14);
                wg_wait0();
                if (cw == 0 && s >= 0) TR(15);
                float4* red = reinterpret_cast<float4*>(smem + SM_RED);
                #pragma unroll
                for (int j = 0; j < 4; j++) {
                    red[((wg ^ 1) * 4 + j) * 128 + wtid] = make_float4(wg == 0 ? acc[1][4 * j] : acc[0][4 * j], wg == 0 ? acc[1][4 * j + 1] : acc[0][4 * j + 1],
                                                                       wg == 0 ? acc[1][4 * j + 2] : acc[0][4 * j + 2], wg == 0 ? acc[1][4 * j + 3] : acc[0][4 * j + 3]);
                }
                if (s >= 0) mbar_wait(sb + B_EXP, s & 1);
                nbar_sync(1, 256);
                uint32_t pk[8];
                #pragma unroll
                for (int j = 0; j < 4; j++) {
                    float4 r = red[(wg * 4 + j) * 128 + wtid];
                    pk[2 * j] = pack_bf16((wg == 0 ? acc[0][4 * j] : acc[1][4 * j]) + r.x, (wg == 0 ? acc[0][4 * j + 1] : acc[1][4 * j + 1]) + r.y);
                    pk[2 * j + 1] = pack_bf16((wg == 0 ? acc[0][4 * j + 2] : acc[1][4 * j + 2]) + r.z, (wg == 0 ? acc[0][4 * j + 3] : acc[1][4 * j + 3]) + r.w);
                }
                const uint32_t dst = (rank == 2) ? sb + SM_VT + sln * 10240 + wg * 5120 + 1024 : (wg == 0 ? sb + SM_QT : sb + SM_KT + sln * 5120 + 1024);
                #pragma unroll
                for (int jj = 0; jj < 2; jj++) {
                    int mi = lane >> 3, tok = 8 * (2 * jj + (mi >> 1)) + (lane & 7), chunk = 2 * warp + (mi & 1);
                    stsm4t(dst + tok * 128 + ((chunk ^ (tok & 7)) << 4), pk[4 * jj], pk[4 * jj + 1], pk[4 * jj + 2], pk[4 * jj + 3]);
                }
                fence_async();
                nbar_sync(1, 256);
                if (rank == 2 && lane == 0 && cw < 4 && sn < NSEG - 1) {
                    const uint32_t off = SM_VT + sln * 10240 + (cw & 1) * 5120 + 1024;
                    const uint32_t rb = mapa(sb, cw >> 1);
                    bulk_s2c(rb + off, sb + off, 4096, rb + B_V + 8 * sln);
                }
                if (cw == 0 && s >= 0) TR(13);
            }
        }
        nbar_arrive(3, 384);
        __syncwarp();
        cluster_sync_all();
    }
}

#define NAUX 36
__device__ __align__(1024) bf16 g_Oimg[16 * 64 * 128 * 64];
__device__ float    g_part[4 * SEQ * DM];
__device__ float    g_part31[2 * 13 * 64 * DM];
__device__ unsigned g_ocnt[32];
__device__ unsigned g_gcnt[32][2];
__device__ unsigned g_ssmcnt, g_auxdone, g_taskctr, g_gemmctr;
#define NATT 8
#define ATR(i) do {} while (0)
#define ATRID(i, id) do {} while (0)

__device__ __forceinline__ void wait_counter(const unsigned* p, unsigned target) {
    int guard = 0;
    while ((int)(ld_acquire(p) - target) < 0 && ++guard < (1 << 22)) __nanosleep(64);
}
__device__ __forceinline__ void fence_async_all() { asm volatile("fence.proxy.async;" ::: "memory"); }
template <int OFF>
__device__ __forceinline__ void wgmma_n192_tB(float (&d)[160], uint64_t da, uint64_t db) {
    asm volatile("wgmma.mma_async.sync.aligned.m64n192k16.f32.bf16.bf16 {%0,%1,%2,%3,%4,%5,%6,%7,%8,%9,%10,%11,%12,%13,%14,%15,%16,%17,%18,%19,%20,%21,%22,%23,%24,%25,%26,%27,%28,%29,%30,%31,%32,%33,%34,%35,%36,%37,%38,%39,%40,%41,%42,%43,%44,%45,%46,%47,%48,%49,%50,%51,%52,%53,%54,%55,%56,%57,%58,%59,%60,%61,%62,%63,%64,%65,%66,%67,%68,%69,%70,%71,%72,%73,%74,%75,%76,%77,%78,%79,%80,%81,%82,%83,%84,%85,%86,%87,%88,%89,%90,%91,%92,%93,%94,%95}, %96, %97, 1, 1, 1, 0, 1;\n"
        : "+f"(d[OFF + 0]), "+f"(d[OFF + 1]), "+f"(d[OFF + 2]), "+f"(d[OFF + 3]), "+f"(d[OFF + 4]), "+f"(d[OFF + 5]), "+f"(d[OFF + 6]), "+f"(d[OFF + 7]), "+f"(d[OFF + 8]), "+f"(d[OFF + 9]), "+f"(d[OFF + 10]), "+f"(d[OFF + 11]), "+f"(d[OFF + 12]), "+f"(d[OFF + 13]), "+f"(d[OFF + 14]), "+f"(d[OFF + 15]), "+f"(d[OFF + 16]), "+f"(d[OFF + 17]), "+f"(d[OFF + 18]), "+f"(d[OFF + 19]), "+f"(d[OFF + 20]), "+f"(d[OFF + 21]), "+f"(d[OFF + 22]), "+f"(d[OFF + 23]), "+f"(d[OFF + 24]), "+f"(d[OFF + 25]), "+f"(d[OFF + 26]), "+f"(d[OFF + 27]), "+f"(d[OFF + 28]), "+f"(d[OFF + 29]), "+f"(d[OFF + 30]), "+f"(d[OFF + 31]), "+f"(d[OFF + 32]), "+f"(d[OFF + 33]), "+f"(d[OFF + 34]), "+f"(d[OFF + 35]), "+f"(d[OFF + 36]), "+f"(d[OFF + 37]), "+f"(d[OFF + 38]), "+f"(d[OFF + 39]), "+f"(d[OFF + 40]), "+f"(d[OFF + 41]), "+f"(d[OFF + 42]), "+f"(d[OFF + 43]), "+f"(d[OFF + 44]), "+f"(d[OFF + 45]), "+f"(d[OFF + 46]), "+f"(d[OFF + 47]), "+f"(d[OFF + 48]), "+f"(d[OFF + 49]), "+f"(d[OFF + 50]), "+f"(d[OFF + 51]), "+f"(d[OFF + 52]), "+f"(d[OFF + 53]), "+f"(d[OFF + 54]), "+f"(d[OFF + 55]), "+f"(d[OFF + 56]), "+f"(d[OFF + 57]), "+f"(d[OFF + 58]), "+f"(d[OFF + 59]), "+f"(d[OFF + 60]), "+f"(d[OFF + 61]), "+f"(d[OFF + 62]), "+f"(d[OFF + 63]), "+f"(d[OFF + 64]), "+f"(d[OFF + 65]), "+f"(d[OFF + 66]), "+f"(d[OFF + 67]), "+f"(d[OFF + 68]), "+f"(d[OFF + 69]), "+f"(d[OFF + 70]), "+f"(d[OFF + 71]), "+f"(d[OFF + 72]), "+f"(d[OFF + 73]), "+f"(d[OFF + 74]), "+f"(d[OFF + 75]), "+f"(d[OFF + 76]), "+f"(d[OFF + 77]), "+f"(d[OFF + 78]), "+f"(d[OFF + 79]), "+f"(d[OFF + 80]), "+f"(d[OFF + 81]), "+f"(d[OFF + 82]), "+f"(d[OFF + 83]), "+f"(d[OFF + 84]), "+f"(d[OFF + 85]), "+f"(d[OFF + 86]), "+f"(d[OFF + 87]), "+f"(d[OFF + 88]), "+f"(d[OFF + 89]), "+f"(d[OFF + 90]), "+f"(d[OFF + 91]), "+f"(d[OFF + 92]), "+f"(d[OFF + 93]), "+f"(d[OFF + 94]), "+f"(d[OFF + 95])
        : "l"(da), "l"(db));
}
template <int OFF>
__device__ __forceinline__ void wgmma_n128_tB(float (&d)[160], uint64_t da, uint64_t db) {
    asm volatile("wgmma.mma_async.sync.aligned.m64n128k16.f32.bf16.bf16 {%0,%1,%2,%3,%4,%5,%6,%7,%8,%9,%10,%11,%12,%13,%14,%15,%16,%17,%18,%19,%20,%21,%22,%23,%24,%25,%26,%27,%28,%29,%30,%31,%32,%33,%34,%35,%36,%37,%38,%39,%40,%41,%42,%43,%44,%45,%46,%47,%48,%49,%50,%51,%52,%53,%54,%55,%56,%57,%58,%59,%60,%61,%62,%63}, %64, %65, 1, 1, 1, 0, 1;\n"
        : "+f"(d[OFF + 0]), "+f"(d[OFF + 1]), "+f"(d[OFF + 2]), "+f"(d[OFF + 3]), "+f"(d[OFF + 4]), "+f"(d[OFF + 5]), "+f"(d[OFF + 6]), "+f"(d[OFF + 7]), "+f"(d[OFF + 8]), "+f"(d[OFF + 9]), "+f"(d[OFF + 10]), "+f"(d[OFF + 11]), "+f"(d[OFF + 12]), "+f"(d[OFF + 13]), "+f"(d[OFF + 14]), "+f"(d[OFF + 15]), "+f"(d[OFF + 16]), "+f"(d[OFF + 17]), "+f"(d[OFF + 18]), "+f"(d[OFF + 19]), "+f"(d[OFF + 20]), "+f"(d[OFF + 21]), "+f"(d[OFF + 22]), "+f"(d[OFF + 23]), "+f"(d[OFF + 24]), "+f"(d[OFF + 25]), "+f"(d[OFF + 26]), "+f"(d[OFF + 27]), "+f"(d[OFF + 28]), "+f"(d[OFF + 29]), "+f"(d[OFF + 30]), "+f"(d[OFF + 31]), "+f"(d[OFF + 32]), "+f"(d[OFF + 33]), "+f"(d[OFF + 34]), "+f"(d[OFF + 35]), "+f"(d[OFF + 36]), "+f"(d[OFF + 37]), "+f"(d[OFF + 38]), "+f"(d[OFF + 39]), "+f"(d[OFF + 40]), "+f"(d[OFF + 41]), "+f"(d[OFF + 42]), "+f"(d[OFF + 43]), "+f"(d[OFF + 44]), "+f"(d[OFF + 45]), "+f"(d[OFF + 46]), "+f"(d[OFF + 47]), "+f"(d[OFF + 48]), "+f"(d[OFF + 49]), "+f"(d[OFF + 50]), "+f"(d[OFF + 51]), "+f"(d[OFF + 52]), "+f"(d[OFF + 53]), "+f"(d[OFF + 54]), "+f"(d[OFF + 55]), "+f"(d[OFF + 56]), "+f"(d[OFF + 57]), "+f"(d[OFF + 58]), "+f"(d[OFF + 59]), "+f"(d[OFF + 60]), "+f"(d[OFF + 61]), "+f"(d[OFF + 62]), "+f"(d[OFF + 63])
        : "l"(da), "l"(db));
}
__device__ __forceinline__ void stsm4(uint32_t addr, uint32_t r0, uint32_t r1, uint32_t r2, uint32_t r3) {
    asm volatile("stmatrix.sync.aligned.m8n8.x4.shared.b16 [%0], {%1,%2,%3,%4};" :: "r"(addr), "r"(r0), "r"(r1), "r"(r2), "r"(r3) : "memory");
}

#define AX_BAR   0
#define NST_G 4
#define AX_EMPTY (AX_BAR + 16 + 8 * NST_G)
#define AX_DATA  1024
#define AX_UNIT  28672
#define AX_STAGE 57344
#define AX_TOTAL (AX_DATA + 8 * AX_UNIT)

__device__ __forceinline__ void attn_compute(unsigned char* smem, uint32_t sb, uint32_t buf, int warp, int lane);
__device__ __forceinline__ void attn_producer(unsigned char* smem, int hg, unsigned epoch) {
    const uint32_t sb = smem_u32(smem);
    const int lane = threadIdx.x & 31;
    {
        for (int s = 0; s < NSEG; s++) {
            const uint32_t buf = AX_DATA + (s & 1) * (4 * AX_UNIT), bar = sb + AX_BAR + 8 * (s & 1);
            if (lane < 4) wait_counter(&g_flag[s][4 * hg + lane], (epoch + 1) * 3u);
            if (lane == 4) mbar_wait_sleep(sb + AX_EMPTY + 8 * (s & 1), ((s >> 1) & 1) ^ 1);
            __syncwarp();
            if (lane == 0) mbar_expect_tx(bar, 4 * AX_UNIT);
            __syncwarp();
            if (lane < 24) {
                fence_async_all();
                const int u = lane / 6, r = lane % 6, hf = r & 1, kind = r >> 1;
                const uint32_t ub = sb + buf + u * AX_UNIT;
                const size_t img = ((size_t)(s * NH + 4 * hg + u) * 2) + hf;
                if (kind == 0) bulk_g2s(ub + hf * 4096, g_Qimg + img * 2048, 4096, bar);
                else if (kind == 1) bulk_g2s(ub + 8192 + hf * 5120, g_Kimg + img * 2560, 5120, bar);
                else bulk_g2s(ub + 18432 + hf * 5120, g_Vimg + img * 2560, 5120, bar);
            }
            __syncwarp();
        }
    }
}
__device__ __forceinline__ void attn_loop(unsigned char* smem, int hg, unsigned epoch) {
    const uint32_t sb = smem_u32(smem);
    const int tid = threadIdx.x, warp = tid >> 5, lane = tid & 31;
    for (int s = 0; s < NSEG; s++) {
        const uint32_t buf = AX_DATA + (s & 1) * (4 * AX_UNIT), bar = sb + AX_BAR + 8 * (s & 1);
        mbar_wait_sleep(bar, (s >> 1) & 1);
        if (s < 30) ATR(2 + 2 * s);
        attn_compute(smem, sb, buf, warp, lane);
        if (s < 30) ATR(3 + 2 * s);
        fence_async();
        __syncwarp();
        if (lane == 0) mbar_arrive(sb + AX_EMPTY + 16 + 8 * (s & 1));
    }
}
__device__ __forceinline__ void attn_storer(unsigned char* smem, int hg) {
    const uint32_t sb = smem_u32(smem);
    const int lane = threadIdx.x & 31;
    for (int s = 0; s < NSEG; s++) {
        const uint32_t buf = AX_DATA + (s & 1) * (4 * AX_UNIT);
        mbar_wait_sleep(sb + AX_EMPTY + 16 + 8 * (s & 1), (s >> 1) & 1);
        if (lane < 8) {
            const int uu = lane >> 1, hf = lane & 1, hh = 4 * hg + uu;
            bulk_s2g(g_Oimg + (((size_t)(s >> 2) * 64 + hh * 2 + hf) * 128 + (s & 3) * 32) * 64, sb + buf + uu * AX_UNIT + hf * 4096, 4096);
            bulk_commit();
            bulk_wait_read0();
            mbar_arrive(sb + AX_EMPTY + 8 * (s & 1));
            bulk_wait0();
            fence_async_all();
            __threadfence();
            atomicAdd(&g_ocnt[s >> 1], 1u);
        }
        __syncwarp();
    }
}
__device__ __forceinline__ void attn_compute(unsigned char* smem, uint32_t sb, uint32_t buf, int warp, int lane) {
    const int g = lane >> 2, t = lane & 3;
    const int u = warp >> 1, qh = warp & 1;
    const uint32_t ub = sb + buf + u * AX_UNIT;
    float sc[5][4];
    #pragma unroll
    for (int j = 0; j < 5; j++) { sc[j][0] = sc[j][1] = sc[j][2] = sc[j][3] = 0.f; }
    #pragma unroll
    for (int ks = 0; ks < 8; ks++) {
        const int hf = ks >> 2, c0 = (ks & 3) * 2;
        uint32_t a[4];
        { int mi = lane >> 3, row = 16 * qh + (mi & 1) * 8 + (lane & 7), chunk = c0 + (mi >> 1);
          ldsm4(a, ub + hf * 4096 + row * 128 + ((chunk ^ (row & 7)) << 4)); }
        #pragma unroll
        for (int jp = 0; jp < 3; jp++) {
            uint32_t b[4];
            int mi = lane >> 3, nt = 2 * jp + (mi >> 1); if (nt > 4) nt = 4;
            int row = 8 * nt + (lane & 7), chunk = c0 + (mi & 1);
            ldsm4(b, ub + 8192 + hf * 5120 + row * 128 + ((chunk ^ (row & 7)) << 4));
            mma_bf16(sc[2 * jp], a[0], a[1], a[2], a[3], b[0], b[1]);
            if (jp < 2) mma_bf16(sc[2 * jp + 1], a[0], a[1], a[2], a[3], b[2], b[3]);
        }
    }
    uint32_t pa[3][4];
    {
        const float sc2 = 0.08838834764831845f * 1.4426950408889634f;
        float mx0 = -3.0e38f, mx1 = -3.0e38f;
        const int q0 = 16 * qh + g, q1 = q0 + 8;
        #pragma unroll
        for (int j = 0; j < 5; j++)
            #pragma unroll
            for (int e = 0; e < 2; e++) {
                int key = 8 * j + 2 * t + e - 8;
                sc[j][e] = (key <= q0) ? sc[j][e] * sc2 : -3.0e38f;
                sc[j][2 + e] = (key <= q1) ? sc[j][2 + e] * sc2 : -3.0e38f;
                mx0 = fmaxf(mx0, sc[j][e]); mx1 = fmaxf(mx1, sc[j][2 + e]);
            }
        mx0 = fmaxf(mx0, __shfl_xor_sync(~0u, mx0, 1)); mx0 = fmaxf(mx0, __shfl_xor_sync(~0u, mx0, 2));
        mx1 = fmaxf(mx1, __shfl_xor_sync(~0u, mx1, 1)); mx1 = fmaxf(mx1, __shfl_xor_sync(~0u, mx1, 2));
        float s0 = 0.f, s1 = 0.f;
        #pragma unroll
        for (int j = 0; j < 5; j++)
            #pragma unroll
            for (int e = 0; e < 2; e++) {
                sc[j][e] = ex2_approx(sc[j][e] - mx0); sc[j][2 + e] = ex2_approx(sc[j][2 + e] - mx1);
                s0 += sc[j][e]; s1 += sc[j][2 + e];
            }
        s0 += __shfl_xor_sync(~0u, s0, 1); s0 += __shfl_xor_sync(~0u, s0, 2);
        s1 += __shfl_xor_sync(~0u, s1, 1); s1 += __shfl_xor_sync(~0u, s1, 2);
        const float i0 = __frcp_rn(s0), i1 = __frcp_rn(s1);
        #pragma unroll
        for (int k = 0; k < 3; k++) {
            pa[k][0] = pack_bf16(sc[2 * k][0] * i0, sc[2 * k][1] * i0);
            pa[k][1] = pack_bf16(sc[2 * k][2] * i1, sc[2 * k][3] * i1);
            if (k < 2) { pa[k][2] = pack_bf16(sc[2 * k + 1][0] * i0, sc[2 * k + 1][1] * i0); pa[k][3] = pack_bf16(sc[2 * k + 1][2] * i1, sc[2 * k + 1][3] * i1); }
            else { pa[k][2] = 0u; pa[k][3] = 0u; }
        }
    }
    __syncwarp();
    nbar_sync(5 + u, 64);
    #pragma unroll
    for (int np = 0; np < 8; np++) {
        const int hf = np >> 2, c0 = (np & 3) * 2;
        float o0[4] = {0, 0, 0, 0}, o1[4] = {0, 0, 0, 0};
        #pragma unroll
        for (int k = 0; k < 3; k++) {
            uint32_t b[4];
            int mi = lane >> 3;
            int row = 16 * k + (mi & 1) * 8 + (lane & 7); if (row > 39) row = 39 - 7 + (lane & 7);
            int chunk = c0 + (mi >> 1);
            ldsm4t(b, ub + 18432 + hf * 5120 + row * 128 + ((chunk ^ (row & 7)) << 4));
            mma_bf16(o0, pa[k][0], pa[k][1], pa[k][2], pa[k][3], b[0], k < 2 ? b[1] : 0u);
            mma_bf16(o1, pa[k][0], pa[k][1], pa[k][2], pa[k][3], b[2], k < 2 ? b[3] : 0u);
        }
        int mi = lane >> 3, row = 16 * qh + (mi & 1) * 8 + (lane & 7), chunk = c0 + (mi >> 1);
        stsm4(ub + hf * 4096 + row * 128 + ((chunk ^ (row & 7)) << 4), pack_bf16(o0[0], o0[1]), pack_bf16(o0[2], o0[3]), pack_bf16(o1[0], o1[1]), pack_bf16(o1[2], o1[3]));
    }
}

template <int V> struct IntC { static constexpr int value = V; };
struct Task { int type, rb, c, k0, nch, plane; };
#define NGEMM 284
__device__ __forceinline__ Task decode_task(int j) {
    Task t; t.type = 0; t.rb = 0; t.c = 0; t.k0 = 0; t.nch = 16; t.plane = 0;
    auto H = [&](int rb, int i) { t.type = 1; t.rb = rb; t.c = i & 1; t.plane = i >> 1; t.k0 = t.plane * 16; };
    auto H13 = [&](int rb, int i) { t.type = 1; t.rb = rb; t.c = i & 1; t.plane = i >> 1; t.k0 = t.plane * 5; t.nch = (t.plane == 12) ? 4 : 5; };
    auto CF = [&](int rb, int i) { t.type = 2; t.rb = rb; t.c = i & 1; t.k0 = rb * 64 + (i >> 1) * 16; t.nch = 16; };
    auto C13 = [&](int rb, int i) { t.type = 2; t.rb = rb; t.c = i & 1; t.k0 = rb * 64 + (i >> 1) * 8; t.nch = 8; };
    if (j >= NGEMM) { t.type = 3; return t; }
    if (j < 8) { t.c = j & 1; t.plane = j >> 1; t.k0 = t.plane * 16; return t; }
    j -= 8;
    if (j < 156) {
        const int q = j / 12, r = j % 12;
        if (r < 8) { t.rb = 2 * (q + 1); t.c = r & 1; t.plane = r >> 1; t.k0 = t.plane * 16; }
        else { t.type = 2; t.rb = 2 * q + ((r - 8) >> 1); t.c = r & 1; t.k0 = t.rb * 64; t.nch = 64; }
        return t;
    }
    j -= 156;
    if (j < 8) { H(28, j); return t; }
    j -= 8;
    if (j < 8) { H(29, j); return t; }
    j -= 8;
    if (j < 4) { t.type = 2; t.rb = 26 + (j >> 1); t.c = j & 1; t.k0 = t.rb * 64; t.nch = 64; return t; }
    j -= 4;
    if (j < 8) { CF(28, j); return t; }
    j -= 8;
    if (j < 26) { H13(30, j); return t; }
    j -= 26;
    if (j < 8) { CF(29, j); return t; }
    j -= 8;
    if (j < 26) { H13(31, j); return t; }
    j -= 26;
    if (j < 16) { C13(30, j); return t; }
    j -= 16;
    C13(31, j);
    return t;
}
__device__ __forceinline__ void gemm_producer(unsigned char* smem, const CUtensorMap* womap, unsigned epoch, volatile int* s_tasks) {
    const uint32_t sb = smem_u32(smem);
    uint32_t st = 0, ph = 1;
    for (int n = 0;; n++) {
        const int j = (int)(atomicAdd(&g_gemmctr, 1u) - epoch * (unsigned)(NGEMM + NAUX - NATT));
        const Task t = decode_task(j);
        if (t.type <= 1) {
            wait_counter(&g_ocnt[t.rb], (epoch + 1) * 128u);
            if (t.type == 0) wait_counter(&g_ocnt[t.rb + 1], (epoch + 1) * 128u);
            fence_async_all();
        } else if (t.type == 2) {
            wait_counter(&g_gcnt[t.rb][t.c], (epoch + 1) * (t.rb >= 30 ? 13u : 4u));
            wait_counter(&g_ssmcnt, (epoch + 1) * 80u);
        }
        const int nch = (t.type <= 1) ? t.nch : 1;
        for (int kc = 0; kc < nch; kc++) {
            mbar_wait_sleep(sb + AX_EMPTY + 8 * st, ph);
            const uint32_t a = sb + AX_DATA + st * AX_STAGE, bar = sb + AX_BAR + 16 + 8 * st;
            if (kc == 0) s_tasks[n & 7] = j;
            if (t.type > 1) mbar_arrive(bar);
            else {
                const bf16* asrc = g_Oimg + ((size_t)(t.rb >> 1) * 64 + t.k0 + kc) * 8192 + (t.rb & 1) * 4096;
                if (t.type == 0) { mbar_expect_tx(bar, AX_STAGE); bulk_g2s(a, asrc, 8192, bar); bulk_g2s(a + 8192, asrc + 4096, 8192, bar); }
                else { mbar_expect_tx(bar, AX_STAGE - 8192); bulk_g2s(a, asrc, 8192, bar); }
                #pragma unroll
                for (int b = 0; b < 5; b++) tma_load_2d(a + 16384 + b * 8192, womap, t.c * 320 + b * 64, (t.k0 + kc) * 64, bar);
            }
            if (++st == NST_G) { st = 0; ph ^= 1; }
        }
        if (t.type == 3) break;
    }
}
__device__ __forceinline__ void gemm_signaller(volatile int* s_done) {
    for (int n = 0;; n++) {
        nbar_sync(2, 288);
        const int j = s_done[n & 7];
        if (j < 0) break;
        if ((threadIdx.x & 31) == 0) {
            const Task t = decode_task(j);
            __threadfence();
            atomicAdd(&g_gcnt[t.rb][t.c], 1u);
            if (t.type == 0) atomicAdd(&g_gcnt[t.rb + 1][t.c], 1u);
        }
        __syncwarp();
    }
}
__device__ __forceinline__ void gemm_consumer(unsigned char* smem, bf16* __restrict__ out, volatile int* s_tasks, volatile int* s_done) {
    const uint32_t sb = smem_u32(smem);
    const int tid = threadIdx.x, lane = tid & 31;
    const int wg = __shfl_sync(~0u, tid >> 7, 0), warp = __shfl_sync(~0u, (tid >> 5) & 3, 0);
    uint32_t st = 0, ph = 0;
    int ndone = 0;
    for (int n = 0;; n++) {
        mbar_wait_sleep(sb + AX_BAR + 16 + 8 * st, ph);
        const Task t = decode_task(__shfl_sync(~0u, s_tasks[n & 7], 0));
        if (t.type > 1) {
            nbar_sync(1, 256);
            if ((tid & 127) == 0) mbar_arrive(sb + AX_EMPTY + 8 * st);
            if (++st == NST_G) { st = 0; ph ^= 1; }
            if (t.type == 3) break;
            const int np = (t.rb >= 30) ? 13 : 4;
            const float* pbase = (t.rb >= 30) ? g_part31 + (size_t)(t.rb - 30) * 13 * 64 * DM - (size_t)t.rb * 64 * DM : g_part;
            const size_t pstride = (t.rb >= 30) ? (size_t)64 * DM : (size_t)SEQ * DM;
            auto combine = [&](int i, auto NP) {
                const int r = t.k0 + i / 80, cc = t.c * 320 + (i % 80) * 4;
                float4 v[NP.value];
                #pragma unroll
                for (int q = 0; q < NP.value; q++) v[q] = __ldcg(reinterpret_cast<const float4*>(pbase + q * pstride + (size_t)r * DM + cc));
                const float gt = __ldcg(g_g + r);
                const uint2 bb = __ldcg(reinterpret_cast<const uint2*>(g_b + (size_t)r * DM + cc));
                float4 a = v[0];
                #pragma unroll
                for (int q = 1; q < NP.value; q++) { a.x += v[q].x; a.y += v[q].y; a.z += v[q].z; a.w += v[q].w; }
                const float b0 = __uint_as_float(bb.x << 16), b1 = __uint_as_float(bb.x & 0xffff0000u), b2 = __uint_as_float(bb.y << 16), b3 = __uint_as_float(bb.y & 0xffff0000u);
                uint2 o; o.x = pack_bf16(gt * a.x + (1.f - gt) * b0, gt * a.y + (1.f - gt) * b1); o.y = pack_bf16(gt * a.z + (1.f - gt) * b2, gt * a.w + (1.f - gt) * b3);
                *reinterpret_cast<uint2*>(out + (size_t)r * DM + cc) = o;
            };
            if (np == 4) {
                const int nit = t.nch * 80 / 256;
                for (int it0 = 0; it0 < nit; it0 += 5) {
                    #pragma unroll
                    for (int it = 0; it < 5; it++) combine(tid + 256 * (it0 + it), IntC<4>());
                }
            } else {
                #pragma unroll
                for (int it = 0; it < 3; it++) { const int i = tid + 256 * it; if (i < 640) combine(i, IntC<13>()); }
            }
            if (n < 56) ATRID(6 + n, s_tasks[n & 7]);
            continue;
        }
        const int g = lane >> 2, tq = lane & 3;
        if (t.type == 0) {
            float acc[160];
            #pragma unroll
            for (int i = 0; i < 160; i++) acc[i] = 0.f;
            uint32_t prev = 0;
            for (int kc = 0; kc < 16; kc++) {
                mbar_wait(sb + AX_BAR + 16 + 8 * st, ph);
                const uint32_t a = sb + AX_DATA + st * AX_STAGE;
                const uint64_t da = make_desc(a + wg * 8192, 16, 1024), db = make_desc(a + 16384, 8192, 1024);
                wg_fence();
                #pragma unroll
                for (int ks = 0; ks < 4; ks++) {
                    wgmma_n192_tB<0>(acc, da + ks * 2, db + ks * 128);
                    wgmma_n128_tB<96>(acc, da + ks * 2, db + ks * 128 + 3 * 512);
                }
                wg_commit();
                asm volatile("wgmma.wait_group.sync.aligned 1;" ::: "memory");
                if (kc > 0 && (tid & 127) == 0) mbar_arrive(sb + AX_EMPTY + 8 * prev);
                prev = st;
                if (++st == NST_G) { st = 0; ph ^= 1; }
            }
            wg_wait0();
            if ((tid & 127) == 0) mbar_arrive(sb + AX_EMPTY + 8 * prev);
            float* base = g_part + ((size_t)t.plane * SEQ + t.rb * 64 + wg * 64 + warp * 16 + g) * DM + t.c * 320 + 2 * tq;
            #pragma unroll
            for (int q = 0; q < 40; q++) {
                *reinterpret_cast<float2*>(base + q * 8) = make_float2(acc[4 * q], acc[4 * q + 1]);
                *reinterpret_cast<float2*>(base + 8 * DM + q * 8) = make_float2(acc[4 * q + 2], acc[4 * q + 3]);
            }
        } else {
            float* base = (t.rb >= 30 ? g_part31 + (size_t)((t.rb - 30) * 13 + t.plane) * 64 * DM : g_part + ((size_t)t.plane * SEQ + t.rb * 64) * DM) + (size_t)(warp * 16 + g) * DM + t.c * 320 + 2 * tq;
            if (wg == 0) {
                float acc[160];
                #pragma unroll
                for (int i = 0; i < 96; i++) acc[i] = 0.f;
                uint32_t prev = 0;
                for (int kc = 0; kc < t.nch; kc++) {
                    mbar_wait(sb + AX_BAR + 16 + 8 * st, ph);
                    const uint32_t a = sb + AX_DATA + st * AX_STAGE;
                    const uint64_t da = make_desc(a, 16, 1024), db = make_desc(a + 16384, 8192, 1024);
                    wg_fence();
                    #pragma unroll
                    for (int ks = 0; ks < 4; ks++) wgmma_n192_tB<0>(acc, da + ks * 2, db + ks * 128);
                    wg_commit();
                    asm volatile("wgmma.wait_group.sync.aligned 1;" ::: "memory");
                    if (kc > 0 && (tid & 127) == 0) mbar_arrive(sb + AX_EMPTY + 8 * prev);
                    prev = st;
                    if (++st == NST_G) { st = 0; ph ^= 1; }
                }
                wg_wait0();
                if ((tid & 127) == 0) mbar_arrive(sb + AX_EMPTY + 8 * prev);
                #pragma unroll
                for (int q = 0; q < 24; q++) {
                    *reinterpret_cast<float2*>(base + q * 8) = make_float2(acc[4 * q], acc[4 * q + 1]);
                    *reinterpret_cast<float2*>(base + 8 * DM + q * 8) = make_float2(acc[4 * q + 2], acc[4 * q + 3]);
                }
            } else {
                float acc[160];
                #pragma unroll
                for (int i = 96; i < 160; i++) acc[i] = 0.f;
                uint32_t prev = 0;
                for (int kc = 0; kc < t.nch; kc++) {
                    mbar_wait(sb + AX_BAR + 16 + 8 * st, ph);
                    const uint32_t a = sb + AX_DATA + st * AX_STAGE;
                    const uint64_t da = make_desc(a, 16, 1024), db = make_desc(a + 16384, 8192, 1024);
                    wg_fence();
                    #pragma unroll
                    for (int ks = 0; ks < 4; ks++) wgmma_n128_tB<96>(acc, da + ks * 2, db + ks * 128 + 3 * 512);
                    wg_commit();
                    asm volatile("wgmma.wait_group.sync.aligned 1;" ::: "memory");
                    if (kc > 0 && (tid & 127) == 0) mbar_arrive(sb + AX_EMPTY + 8 * prev);
                    prev = st;
                    if (++st == NST_G) { st = 0; ph ^= 1; }
                }
                wg_wait0();
                if ((tid & 127) == 0) mbar_arrive(sb + AX_EMPTY + 8 * prev);
                #pragma unroll
                for (int q = 24; q < 40; q++) {
                    *reinterpret_cast<float2*>(base + q * 8) = make_float2(acc[4 * q], acc[4 * q + 1]);
                    *reinterpret_cast<float2*>(base + 8 * DM + q * 8) = make_float2(acc[4 * q + 2], acc[4 * q + 3]);
                }
            }
        }
        if (tid == 0) s_done[ndone & 7] = s_tasks[n & 7];
        ndone++;
        nbar_arrive(2, 288);
        if (n < 56) ATRID(6 + n, s_tasks[n & 7]);
    }
    if (tid == 0) s_done[ndone & 7] = -1;
    nbar_arrive(2, 288);
}

__global__ void __launch_bounds__(384, 1)
k_aux(const __grid_constant__ CUtensorMap womap, const bf16* __restrict__ x, const bf16* __restrict__ A_re, const bf16* __restrict__ A_im,
      const bf16* __restrict__ B_re, const bf16* __restrict__ B_im, const bf16* __restrict__ C_re, const bf16* __restrict__ C_im,
      const bf16* __restrict__ log_dt, const bf16* __restrict__ Dskip, const bf16* __restrict__ gw, bf16* __restrict__ out) {
    extern __shared__ __align__(1024) unsigned char smem[];
    const uint32_t sb = smem_u32(smem);
    const int tid = threadIdx.x, warp = tid >> 5, lane = tid & 31;
    __shared__ unsigned s_epoch;
    __shared__ int s_task, s_tasks[8], s_done[8];
    if (tid == 0) {
        for (int i = 0; i < 2 + NST_G; i++) mbar_init(sb + AX_BAR + 8 * i, 1);
        for (int i = 0; i < NST_G; i++) mbar_init(sb + AX_EMPTY + 8 * i, blockIdx.x < NATT ? 8 : 2);
        asm volatile("fence.mbarrier_init.release.cluster;" ::: "memory");
        s_epoch = *reinterpret_cast<volatile unsigned*>(&g_epoch);
    }
    __syncthreads();
    const unsigned epoch = s_epoch;
    ATR(0);
    const int wg = __shfl_sync(~0u, tid >> 7, 0);
    if (wg == 2) {
        asm volatile("setmaxnreg.dec.sync.aligned.u32 40;");
        if (blockIdx.x < NATT) { if (warp == 8) attn_producer(smem, blockIdx.x, epoch); else if (warp == 9) attn_storer(smem, blockIdx.x); }
        else {
            nbar_sync(3, 384);
            if (warp == 8) { if (lane == 0) gemm_producer(smem, &womap, epoch, s_tasks); }
            else if (warp == 9) gemm_signaller(s_done);
        }
        __syncwarp();
        nbar_sync(4, 384);
    } else {
        asm volatile("setmaxnreg.inc.sync.aligned.u32 232;");
        if (blockIdx.x < NATT) attn_loop(smem, blockIdx.x, epoch);
        else {
            int ntask = 0;
            for (;;) {
                nbar_sync(1, 256);
                if (tid == 0) s_task = (int)(atomicAdd(&g_taskctr, 1u) - epoch * (unsigned)(80 + NAUX - NATT));
                nbar_sync(1, 256);
                const int task = s_task;
                if (task >= 80) break;
                for (int r = task * 26 + warp; r < min(SEQ, task * 26 + 26); r += 8) {
                    float sum = 0.f;
                    for (int i = lane * 2; i < DM; i += 64) {
                        __nv_bfloat162 xv = *reinterpret_cast<const __nv_bfloat162*>(x + (size_t)r * DM + i), wv = *reinterpret_cast<const __nv_bfloat162*>(gw + i);
                        sum += bf2f(xv.x) * bf2f(wv.x) + bf2f(xv.y) * bf2f(wv.y);
                    }
                    #pragma unroll
                    for (int o = 16; o; o >>= 1) sum += __shfl_xor_sync(~0u, sum, o);
                    if (lane == 0) g_g[r] = 1.f / (1.f + expf(-sum));
                }
                ssm_group(smem + AX_DATA, task, x, A_re, A_im, B_re, B_im, C_re, C_im, log_dt, Dskip);
                nbar_sync(1, 256);
                if (tid == 0) { __threadfence(); atomicAdd(&g_ssmcnt, 1u); }
                if (ntask < 4) ATR(2 + ntask);
                ntask++;
            }
            fence_async();
            nbar_sync(3, 384);
            gemm_consumer(smem, out, s_tasks, s_done);
        }
        nbar_sync(4, 384);
        if (tid == 0) {
            __threadfence();
            unsigned old = atomicAdd(&g_auxdone, 1u);
            if (old == NAUX - 1) { g_auxdone = 0; __threadfence(); atomicAdd(&g_epoch, 1u); }
        }
    }
    asm volatile("griddepcontrol.wait;" ::: "memory");
}

extern "C" void kernel_launch(void* const* d_in, const int* in_sizes, int n_in, void* d_out, int out_size) {
    const bf16* x = (const bf16*)d_in[0];
    const bf16* mem0 = (const bf16*)d_in[1];
    const bf16* Wq = (const bf16*)d_in[2];
    const bf16* Wk = (const bf16*)d_in[3];
    const bf16* Wv = (const bf16*)d_in[4];
    const bf16* Wo = (const bf16*)d_in[5];
    const bf16 *A_re = (const bf16*)d_in[8], *A_im = (const bf16*)d_in[9], *B_re = (const bf16*)d_in[10], *B_im = (const bf16*)d_in[11];
    const bf16 *C_re = (const bf16*)d_in[12], *C_im = (const bf16*)d_in[13], *log_dt = (const bf16*)d_in[14], *Dskip = (const bf16*)d_in[15];
    const bf16* gw = (const bf16*)d_in[16];
    bf16* out = (bf16*)d_out;
    cudaStream_t st = cudaStreamPerThread;
    static bool init = false;
    static CUtensorMap xmap, womap;
    static const void* xmap_ptr = nullptr; static const void* womap_ptr = nullptr;
    if (!init) {
        cudaFuncSetAttribute(k_chain, cudaFuncAttributeMaxDynamicSharedMemorySize, SM_TOTAL);
        cudaFuncSetAttribute(k_aux, cudaFuncAttributeMaxDynamicSharedMemorySize, AX_TOTAL);
        init = true;
    }
    if (xmap_ptr != (const void*)x || womap_ptr != (const void*)Wo) {
        void* fn = nullptr; cudaDriverEntryPointQueryResult qres;
        cudaGetDriverEntryPoint("cuTensorMapEncodeTiled", &fn, cudaEnableDefault, &qres);
        typedef CUresult (*EncFn)(CUtensorMap*, CUtensorMapDataType, cuuint32_t, void*, const cuuint64_t*, const cuuint64_t*, const cuuint32_t*, const cuuint32_t*,
                                  CUtensorMapInterleave, CUtensorMapSwizzle, CUtensorMapL2promotion, CUtensorMapFloatOOBfill);
        cuuint32_t es[2] = {1, 1};
        { cuuint64_t dims[2] = {DM, SEQ}; cuuint64_t strides[1] = {DM * 2}; cuuint32_t box[2] = {64, 32};
          ((EncFn)fn)(&xmap, CU_TENSOR_MAP_DATA_TYPE_BFLOAT16, 2, (void*)x, dims, strides, box, es, CU_TENSOR_MAP_INTERLEAVE_NONE, CU_TENSOR_MAP_SWIZZLE_128B,
                      CU_TENSOR_MAP_L2_PROMOTION_L2_128B, CU_TENSOR_MAP_FLOAT_OOB_FILL_NONE); }
        { cuuint64_t dims[2] = {DM, HD}; cuuint64_t strides[1] = {DM * 2}; cuuint32_t box[2] = {64, 64};
          ((EncFn)fn)(&womap, CU_TENSOR_MAP_DATA_TYPE_BFLOAT16, 2, (void*)Wo, dims, strides, box, es, CU_TENSOR_MAP_INTERLEAVE_NONE, CU_TENSOR_MAP_SWIZZLE_128B,
                      CU_TENSOR_MAP_L2_PROMOTION_L2_128B, CU_TENSOR_MAP_FLOAT_OOB_FILL_NONE); }
        xmap_ptr = (const void*)x; womap_ptr = (const void*)Wo;
    }
    k_chain<<<96, 384, SM_TOTAL, st>>>(xmap, x, mem0, Wq, Wk, Wv, Wo);
    {
        cudaLaunchConfig_t cfg = {};
        cfg.gridDim = dim3(NAUX); cfg.blockDim = dim3(384); cfg.dynamicSmemBytes = AX_TOTAL; cfg.stream = st;
        cudaLaunchAttribute at[1];
        at[0].id = cudaLaunchAttributeProgrammaticStreamSerialization; at[0].val.programmaticStreamSerializationAllowed = 1;
        cfg.attrs = at; cfg.numAttrs = 1;
        cudaLaunchKernelEx(&cfg, k_aux, womap, x, A_re, A_im, B_re, B_im, C_re, C_im, log_dt, Dskip, gw, out);
    }
}
```

```cpp
#include <cuda_runtime.h>
#include <cuda_bf16.h>
#include <stdint.h>
#include <cuda.h>

typedef __nv_bfloat16 bf16;

#define SEQ 2048
#define DM 640
#define NH 32
#define DH 128
#define NM 8
#define SEG 32
#define NSEG 64
#define NST 128
#define HD 4096

__device__ bf16  g_b[SEQ * DM];
__device__ float g_g[SEQ];

__device__ __forceinline__ float bf2f(bf16 v) { return __bfloat162float(v); }
__device__ __forceinline__ uint32_t pack_bf16(float lo, float hi) {
    uint32_t r; asm("cvt.rn.bf16x2.f32 %0, %1, %2;" : "=r"(r) : "f"(hi), "f"(lo)); return r;
}
__device__ __forceinline__ uint32_t f2tf32(float x) { uint32_t r; asm("cvt.rna.tf32.f32 %0, %1;" : "=r"(r) : "f"(x)); return r; }
__device__ __forceinline__ void mma_tf32(float (&d)[4], uint32_t a0, uint32_t a1, uint32_t a2, uint32_t a3, uint32_t b0, uint32_t b1) {
    asm volatile("mma.sync.aligned.m16n8k8.row.col.f32.tf32.tf32.f32 {%0,%1,%2,%3}, {%4,%5,%6,%7}, {%8,%9}, {%0,%1,%2,%3};\n"
        : "+f"(d[0]), "+f"(d[1]), "+f"(d[2]), "+f"(d[3]) : "r"(a0), "r"(a1), "r"(a2), "r"(a3), "r"(b0), "r"(b1));
}
__device__ __forceinline__ void mma_bf16(float (&d)[4], uint32_t a0, uint32_t a1, uint32_t a2, uint32_t a3, uint32_t b0, uint32_t b1) {
    asm volatile("mma.sync.aligned.m16n8k16.row.col.f32.bf16.bf16.f32 {%0,%1,%2,%3}, {%4,%5,%6,%7}, {%8,%9}, {%0,%1,%2,%3};\n"
        : "+f"(d[0]), "+f"(d[1]), "+f"(d[2]), "+f"(d[3]) : "r"(a0), "r"(a1), "r"(a2), "r"(a3), "r"(b0), "r"(b1));
}
struct cf { float re, im; };
__device__ __forceinline__ cf cmul(cf a, cf b) { cf r; r.re = a.re * b.re - a.im * b.im; r.im = a.re * b.im + a.im * b.re; return r; }
__device__ __forceinline__ cf csq(cf a) { cf r; r.re = a.re * a.re - a.im * a.im; r.im = 2.f * a.re * a.im; return r; }
__device__ __forceinline__ cf cexpL(float zr, float zi, float L) {
    float e = __expf(zr * L);
    float ang = zi * L;
    float k = rintf(ang * 0.15915494309189535f);
    ang = fmaf(-k, 6.2831854820251465f, ang);
    ang = fmaf(-k, -1.7484555314695172e-07f, ang);
    cf r; r.re = e * __cosf(ang); r.im = e * __sinf(ang); return r;
}

#define SSM_CH 8
#define KC_PITCH 648
#define XS_PITCH (2048 + 8)
#define KT_LEN (2048 + 48)
#define PART_PITCH 20
struct SsmSmem {
    float Kc[SSM_CH][KC_PITCH];
    bf16  xs[SSM_CH][XS_PITCH];
    bf16  KT[2][KT_LEN];
    union {
        float part[8][128 * PART_PITCH];
        float st[SSM_CH][NST][8];
    } u;
    bf16  ys[SSM_CH][XS_PITCH];
    uint16_t kidx[2048];
};

__device__ __forceinline__ int kc_index(int l) {
    return l < 256 ? l : (l < 512 ? 256 + ((l - 256) >> 1) : (l < 1024 ? 384 + ((l - 512) >> 2) : 512 + ((l - 1024) >> 3)));
}

__device__ __forceinline__ void ssm_group(unsigned char* smem_raw, int grp, const bf16* __restrict__ x, const bf16* __restrict__ A_re, const bf16* __restrict__ A_im,
        const bf16* __restrict__ B_re, const bf16* __restrict__ B_im, const bf16* __restrict__ C_re, const bf16* __restrict__ C_im,
        const bf16* __restrict__ log_dt, const bf16* __restrict__ Dskip) {
    SsmSmem& S = *reinterpret_cast<SsmSmem*>(smem_raw);
    const int tid = threadIdx.x, w = tid >> 5, lane = tid & 31, g = lane >> 2, t = lane & 3;
    const int d0 = grp * SSM_CH;
    asm volatile("bar.sync 1, 256;" ::: "memory");
    #pragma unroll
    for (int it = 0; it < 8; it++) {
        const int l = tid + 256 * it;
        uint4 v = *reinterpret_cast<const uint4*>(x + (size_t)l * DM + d0);
        const bf16* p = reinterpret_cast<const bf16*>(&v);
        const int lr = (l & ~15) | (15 - (l & 15));
        #pragma unroll
        for (int c = 0; c < 8; c++) S.xs[c][lr] = p[c];
        S.kidx[l] = (uint16_t)((int)bf2f(__float2bfloat16_rn((float)l)) == 2048 ? 640 : kc_index((int)bf2f(__float2bfloat16_rn((float)l))));
    }
    if (tid < 48) { const int i = tid < 16 ? tid : 2048 + tid; S.KT[0][i] = __float2bfloat16_rn(0.f); if (i > 0) S.KT[1][i - 1] = __float2bfloat16_rn(0.f); }
    if (tid == 48) S.KT[1][KT_LEN - 1] = __float2bfloat16_rn(0.f);
    {
        const int d = d0 + w;
        const float dt = bf2f(__float2bfloat16_rn(expf(bf2f(log_dt[d]))));
        #pragma unroll
        for (int i = 0; i < 4; i++) {
            const int n = lane + 32 * i;
            float zr = dt * bf2f(A_re[d * NST + n]), zi = dt * bf2f(A_im[d * NST + n]);
            cf dB; dB.re = dt * bf2f(B_re[d * NST + n]); dB.im = dt * bf2f(B_im[d * NST + n]);
            cf C; C.re = bf2f(C_re[d * NST + n]); C.im = bf2f(C_im[d * NST + n]);
            cf wv = cmul(C, dB);
            cf u8 = cexpL(zr, zi, 8.f), u128 = cexpL(zr, zi, 128.f);
            float* st = S.u.st[w][n];
            *reinterpret_cast<float4*>(st) = make_float4(zr, zi, wv.re, wv.im);
            *reinterpret_cast<float4*>(st + 4) = make_float4(u8.re, u8.im, u128.re, u128.im);
        }
        __syncwarp();
        float a0a[4] = {0, 0, 0, 0}, a0b[4] = {0, 0, 0, 0}, a1[4] = {0, 0, 0, 0}, a2a[4] = {0, 0, 0, 0}, a2b[4] = {0, 0, 0, 0};
        float k2048 = 0.f;
        const float Lg = (g < 4) ? (512.f + 4.f * g) : (g < 6 ? 1024.f + 8.f * (g - 4) : 1536.f + 8.f * (g - 6));
        #pragma unroll 4
        for (int kk = 0; kk < 32; kk++) {
            const float* st = S.u.st[w][4 * kk + t];
            float4 s0 = *reinterpret_cast<const float4*>(st), s1 = *reinterpret_cast<const float4*>(st + 4);
            cf wv; wv.re = s0.z; wv.im = s0.w;
            cf u8; u8.re = s1.x; u8.im = s1.y;
            cf u128; u128.re = s1.z; u128.im = s1.w;
            cf e1 = cexpL(s0.x, s0.y, (float)g);
            cf e23 = cexpL(s0.x, s0.y, Lg);
            cf e1b = cmul(e1, u8);
            cf e2 = csq(e1);
            cf p = csq(csq(csq(e2)));
            cf f0 = cmul(wv, p), f1 = cmul(f0, u128), f2 = cmul(f1, u128), f3 = cmul(f2, u128);
            uint32_t A00 = f2tf32(f0.re), A01 = f2tf32(f1.re), A02 = f2tf32(-f0.im), A03 = f2tf32(-f1.im);
            uint32_t A10 = f2tf32(f2.re), A11 = f2tf32(f3.re), A12 = f2tf32(-f2.im), A13 = f2tf32(-f3.im);
            mma_tf32(a0a, A00, A01, A02, A03, f2tf32(e1.re), f2tf32(e1.im));
            mma_tf32(a0b, A00, A01, A02, A03, f2tf32(e1b.re), f2tf32(e1b.im));
            mma_tf32(a1, A10, A11, A12, A13, f2tf32(e2.re), f2tf32(e2.im));
            uint32_t E0 = f2tf32(e23.re), E1 = f2tf32(e23.im);
            mma_tf32(a2a, A00, A01, A02, A03, E0, E1);
            mma_tf32(a2b, A10, A11, A12, A13, E0, E1);
            cf e2048 = csq(e23);
            k2048 += wv.re * e2048.re - wv.im * e2048.im;
        }
        k2048 += __shfl_xor_sync(~0u, k2048, 1);
        k2048 += __shfl_xor_sync(~0u, k2048, 2);
        float* Kc = S.Kc[w];
        Kc[16 * g + 2 * t] = a0a[0]; Kc[16 * g + 2 * t + 1] = a0a[1]; Kc[16 * (g + 8) + 2 * t] = a0a[2]; Kc[16 * (g + 8) + 2 * t + 1] = a0a[3];
        Kc[16 * g + 8 + 2 * t] = a0b[0]; Kc[16 * g + 8 + 2 * t + 1] = a0b[1]; Kc[16 * (g + 8) + 8 + 2 * t] = a0b[2]; Kc[16 * (g + 8) + 8 + 2 * t + 1] = a0b[3];
        Kc[256 + 8 * g + 2 * t] = a1[0]; Kc[256 + 8 * g + 2 * t + 1] = a1[1]; Kc[256 + 8 * (g + 8) + 2 * t] = a1[2]; Kc[256 + 8 * (g + 8) + 2 * t + 1] = a1[3];
        #pragma unroll
        for (int mt = 0; mt < 2; mt++) {
            #pragma unroll
            for (int e = 0; e < 4; e++) {
                int A = mt * 16 + g + (e >> 1) * 8, j = 2 * t + (e & 1);
                int Lj = (j < 4) ? 512 + 4 * j : (j < 6 ? 1024 + 8 * (j - 4) : 1536 + 8 * (j - 6));
                Kc[kc_index(Lj + 16 * A)] = mt ? a2b[e] : a2a[e];
            }
        }
        if (lane == 16) Kc[640] = k2048;
    }
    for (int c = 0; c < SSM_CH; c++) {
        asm volatile("bar.sync 1, 256;" ::: "memory");
        #pragma unroll
        for (int it = 0; it < 8; it++) {
            const int j = tid + 256 * it;
            const bf16 v = __float2bfloat16_rn(S.Kc[c][S.kidx[j]]);
            S.KT[0][16 + j] = v;
            S.KT[1][15 + j] = v;
        }
        uint32_t B[16][2];
        #pragma unroll
        for (int v = 0; v < 16; v++) {
            const bf16* p = &S.xs[c][16 * (8 * v + g) + 2 * t];
            B[v][0] = *reinterpret_cast<const uint32_t*>(p);
            B[v][1] = *reinterpret_cast<const uint32_t*>(p + 8);
        }
        asm volatile("bar.sync 1, 256;" ::: "memory");
        float acc[16][4];
        #pragma unroll
        for (int v = 0; v < 16; v++) { acc[v][0] = acc[v][1] = acc[v][2] = acc[v][3] = 0.f; }
        const bf16* kt = (g & 1) ? &S.KT[0][0] : &S.KT[1][0];
        const int ibase = 16 * w + g + 1 + 2 * t - ((g & 1) ? 0 : 1);
        #pragma unroll
        for (int q = 0; q < 16; q++) {
            const int i0 = ibase + 128 * q;
            uint32_t A0 = *reinterpret_cast<const uint32_t*>(kt + i0);
            uint32_t A1 = *reinterpret_cast<const uint32_t*>(kt + i0 + 8);
            uint32_t A3 = *reinterpret_cast<const uint32_t*>(kt + i0 + 16);
            #pragma unroll
            for (int v = q; v < 16; v++) mma_bf16(acc[v], A0, A1, A1, A3, B[v - q][0], B[v - q][1]);
        }
        float* part = S.u.part[w];
        #pragma unroll
        for (int v = 0; v < 16; v++) {
            int a = 8 * v + 2 * t + w;
            if (v < 15 || a < 128) { part[a * PART_PITCH + g] = acc[v][0]; part[a * PART_PITCH + g + 8] = acc[v][2]; }
            if (v < 15 || a + 1 < 128) { part[(a + 1) * PART_PITCH + g] = acc[v][1]; part[(a + 1) * PART_PITCH + g + 8] = acc[v][3]; }
        }
        asm volatile("bar.sync 1, 256;" ::: "memory");
        const float dsk = bf2f(Dskip[d0 + c]);
        #pragma unroll
        for (int it = 0; it < 2; it++) {
            const int l = (tid + 256 * it) * 4, a = l >> 4, b = l & 15;
            float4 sum = make_float4(0.f, 0.f, 0.f, 0.f);
            #pragma unroll
            for (int r = 0; r < 8; r++)
                if (a >= r) { float4 v = *reinterpret_cast<const float4*>(&S.u.part[r][a * PART_PITCH + b]); sum.x += v.x; sum.y += v.y; sum.z += v.z; sum.w += v.w; }
            const uint2 xr = *reinterpret_cast<const uint2*>(&S.xs[c][(l & ~15) + 12 - b]);
            const float x3 = __uint_as_float(xr.x << 16), x2 = __uint_as_float(xr.x & 0xffff0000u), x1 = __uint_as_float(xr.y << 16), x0 = __uint_as_float(xr.y & 0xffff0000u);
            auto fin = [&](float y, float xv) { return bf2f(__float2bfloat16_rn(y)) + bf2f(__float2bfloat16_rn(xv * dsk)); };
            uint2 o; o.x = pack_bf16(fin(sum.x, x0), fin(sum.y, x1)); o.y = pack_bf16(fin(sum.z, x2), fin(sum.w, x3));
            *reinterpret_cast<uint2*>(&S.ys[c][l]) = o;
        }
    }
    asm volatile("bar.sync 1, 256;" ::: "memory");
    #pragma unroll
    for (int it = 0; it < 8; it++) {
        const int l = tid + 256 * it;
        uint32_t wv[4];
        #pragma unroll
        for (int c = 0; c < 4; c++)
            wv[c] = (uint32_t)*reinterpret_cast<const uint16_t*>(&S.ys[2 * c][l]) | ((uint32_t)*reinterpret_cast<const uint16_t*>(&S.ys[2 * c + 1][l]) << 16);
        *reinterpret_cast<uint4*>(g_b + (size_t)l * DM + d0) = make_uint4(wv[0], wv[1], wv[2], wv[3]);
    }
}

__device__ __forceinline__ uint32_t smem_u32(const void* p) { return (uint32_t)__cvta_generic_to_shared(p); }
__device__ __forceinline__ void mbar_init(uint32_t bar, uint32_t cnt) { asm volatile("mbarrier.init.shared::cta.b64 [%0], %1;" :: "r"(bar), "r"(cnt) : "memory"); }
__device__ __forceinline__ void mbar_expect_tx(uint32_t bar, uint32_t bytes) { asm volatile("mbarrier.arrive.expect_tx.shared::cta.b64 _, [%0], %1;" :: "r"(bar), "r"(bytes) : "memory"); }
__device__ __forceinline__ void mbar_arrive(uint32_t bar) { asm volatile("mbarrier.arrive.shared::cta.b64 _, [%0];" :: "r"(bar) : "memory"); }
__device__ __forceinline__ void mbar_wait(uint32_t bar, uint32_t parity) {
    uint32_t ok; int guard = 0;
    do {
        asm volatile("{\n.reg .pred P1;\nmbarrier.test_wait.parity.shared::cta.b64 P1, [%1], %2;\nselp.u32 %0,1,0,P1;\n}" : "=r"(ok) : "r"(bar), "r"(parity) : "memory");
    } while (!ok && ++guard < (1 << 26));
}
__device__ __forceinline__ void mbar_wait_sleep(uint32_t bar, uint32_t parity) {
    uint32_t ok; int guard = 0;
    do {
        asm volatile("{\n.reg .pred P1;\nmbarrier.try_wait.parity.shared::cta.b64 P1, [%1], %2;\nselp.u32 %0,1,0,P1;\n}" : "=r"(ok) : "r"(bar), "r"(parity) : "memory");
    } while (!ok && ++guard < (1 << 22));
}
__device__ __forceinline__ uint32_t mapa(uint32_t addr, uint32_t rank) { uint32_t r; asm volatile("mapa.shared::cluster.u32 %0, %1, %2;" : "=r"(r) : "r"(addr), "r"(rank)); return r; }
__device__ __forceinline__ void st_async4(uint32_t addr, float a, float b, float c, float d, uint32_t bar) {
    asm volatile("st.async.weak.shared::cluster.mbarrier::complete_tx::bytes.v4.f32 [%0], {%1,%2,%3,%4}, [%5];" :: "r"(addr), "f"(a), "f"(b), "f"(c), "f"(d), "r"(bar) : "memory");
}
__device__ __forceinline__ void bulk_s2c(uint32_t dst, uint32_t src, uint32_t bytes, uint32_t bar) {
    asm volatile("cp.async.bulk.shared::cluster.shared::cta.mbarrier::complete_tx::bytes [%0], [%1], %2, [%3];" :: "r"(dst), "r"(src), "r"(bytes), "r"(bar) : "memory");
}
__device__ __forceinline__ void bulk_g2s(uint32_t dst, const void* src, uint32_t bytes, uint32_t bar) {
    asm volatile("cp.async.bulk.shared::cluster.global.mbarrier::complete_tx::bytes [%0], [%1], %2, [%3];" :: "r"(dst), "l"(src), "r"(bytes), "r"(bar) : "memory");
}
__device__ __forceinline__ void bulk_s2g(void* dst, uint32_t src, uint32_t bytes) {
    asm volatile("cp.async.bulk.global.shared::cta.bulk_group [%0], [%1], %2;" :: "l"(dst), "r"(src), "r"(bytes) : "memory");
}
__device__ __forceinline__ void bulk_commit() { asm volatile("cp.async.bulk.commit_group;" ::: "memory"); }
__device__ __forceinline__ void bulk_wait_read0() { asm volatile("cp.async.bulk.wait_group.read 0;" ::: "memory"); }
__device__ __forceinline__ void bulk_wait0() { asm volatile("cp.async.bulk.wait_group 0;" ::: "memory"); }
__device__ __forceinline__ void fence_async() { asm volatile("fence.proxy.async.shared::cta;" ::: "memory"); }
__device__ __forceinline__ void nbar_sync(int id, int n) { asm volatile("bar.sync %0, %1;" :: "r"(id), "r"(n) : "memory"); }
__device__ __forceinline__ void nbar_arrive(int id, int n) { asm volatile("bar.arrive %0, %1;" :: "r"(id), "r"(n) : "memory"); }
__device__ __forceinline__ void cp_async16(uint32_t dst, const void* src) { asm volatile("cp.async.cg.shared.global [%0], [%1], 16;" :: "r"(dst), "l"(src) : "memory"); }
__device__ __forceinline__ void cp_async_wait_all() { asm volatile("cp.async.wait_all;" ::: "memory"); }
__device__ __forceinline__ void ldsm4(uint32_t (&r)[4], uint32_t addr) {
    asm volatile("ldmatrix.sync.aligned.m8n8.x4.shared.b16 {%0,%1,%2,%3}, [%4];" : "=r"(r[0]), "=r"(r[1]), "=r"(r[2]), "=r"(r[3]) : "r"(addr) : "memory");
}
__device__ __forceinline__ void ldsm4t(uint32_t (&r)[4], uint32_t addr) {
    asm volatile("ldmatrix.sync.aligned.m8n8.x4.trans.shared.b16 {%0,%1,%2,%3}, [%4];" : "=r"(r[0]), "=r"(r[1]), "=r"(r[2]), "=r"(r[3]) : "r"(addr) : "memory");
}
__device__ __forceinline__ void stsm2t(uint32_t addr, uint32_t r0, uint32_t r1) {
    asm volatile("stmatrix.sync.aligned.m8n8.x2.trans.shared.b16 [%0], {%1,%2};" :: "r"(addr), "r"(r0), "r"(r1) : "memory");
}
__device__ __forceinline__ uint4 ld_relaxed4(const void* p) { uint4 v; asm volatile("ld.relaxed.gpu.global.v4.u32 {%0,%1,%2,%3}, [%4];" : "=r"(v.x), "=r"(v.y), "=r"(v.z), "=r"(v.w) : "l"(p) : "memory"); return v; }
__device__ __forceinline__ void st_relaxed2(void* p, uint32_t a, uint32_t b) { asm volatile("st.relaxed.gpu.global.v2.u32 [%0], {%1,%2};" :: "l"(p), "r"(a), "r"(b) : "memory"); }
__device__ __forceinline__ void st_relaxed1(void* p, uint32_t a) { asm volatile("st.relaxed.gpu.global.u32 [%0], %1;" :: "l"(p), "r"(a) : "memory"); }
__device__ __forceinline__ unsigned ld_acquire(const unsigned* p) { unsigned v; asm volatile("ld.acquire.gpu.global.u32 %0, [%1];" : "=r"(v) : "l"(p) : "memory"); return v; }
__device__ __forceinline__ float ex2_approx(float x) { float r; asm("ex2.approx.ftz.f32 %0, %1;" : "=f"(r) : "f"(x)); return r; }
__device__ __forceinline__ uint64_t make_desc(uint32_t saddr, uint32_t lbo, uint32_t sbo) {
    return (uint64_t)((saddr & 0x3FFFF) >> 4) | ((uint64_t)((lbo & 0x3FFFF) >> 4) << 16) | ((uint64_t)((sbo & 0x3FFFF) >> 4) << 32) | (1ull << 62);
}
__device__ __forceinline__ void wg_fence() { asm volatile("wgmma.fence.sync.aligned;" ::: "memory"); }
__device__ __forceinline__ void wg_commit() { asm volatile("wgmma.commit_group.sync.aligned;" ::: "memory"); }
__device__ __forceinline__ void wg_wait0() { asm volatile("wgmma.wait_group.sync.aligned 0;" ::: "memory"); }
__device__ __forceinline__ void wgmma_n40_tA(float (&d)[20], uint64_t da, uint64_t db, int scale_d) {
    asm volatile("{\n.reg .pred p;\nsetp.ne.b32 p, %22, 0;\n"
        "wgmma.mma_async.sync.aligned.m64n40k16.f32.bf16.bf16 {%0,%1,%2,%3,%4,%5,%6,%7,%8,%9,%10,%11,%12,%13,%14,%15,%16,%17,%18,%19}, %20, %21, p, 1, 1, 1, 0;\n}\n"
        : "+f"(d[0]), "+f"(d[1]), "+f"(d[2]), "+f"(d[3]), "+f"(d[4]), "+f"(d[5]), "+f"(d[6]), "+f"(d[7]), "+f"(d[8]), "+f"(d[9]),
          "+f"(d[10]), "+f"(d[11]), "+f"(d[12]), "+f"(d[13]), "+f"(d[14]), "+f"(d[15]), "+f"(d[16]), "+f"(d[17]), "+f"(d[18]), "+f"(d[19])
        : "l"(da), "l"(db), "r"(scale_d));
}

#define NREP 8
#define NRED 80
#define CAL_THR 410u
#define COMM_REGS "40"
#define NPOOL 576
#define RPS 1
__device__ __align__(4096) uint32_t g_pool[(NPOOL + 1) * 1024];
__device__ unsigned g_cls[NPOOL];
__device__ unsigned g_side[96];
__device__ unsigned g_calcnt;
__device__ unsigned g_epoch;
__device__ unsigned g_flag[NSEG][NH];
__device__ __align__(1024) bf16 g_Qimg[NSEG * NH * 2 * 32 * 64];
__device__ __align__(1024) bf16 g_Kimg[NSEG * NH * 2 * 40 * 64];
__device__ __align__(1024) bf16 g_Vimg[NSEG * NH * 2 * 40 * 64];

#define SM_XB    0
#define SM_VT    81920
#define SM_KT    (SM_VT + 20480)
#define SM_QT    (SM_KT + 10240)
#define SM_QS    (SM_QT + 4096)
#define SM_MEMB  (SM_QS + 1024)
#define SM_RED   (SM_MEMB + 10240)
#define SM_SC    (SM_RED + 16384)
#define SM_CRED  (SM_SC + 5120)
#define SM_PB    (SM_CRED + 1024)
#define SM_TRACE (SM_PB + 1024)
#define SM_WO    163840
#define SM_BAR   (SM_WO + 65536)
#define SM_TPM   (SM_BAR + 256)
#define SM_TRD   (SM_TPM + 256)
#define SM_TPUB  (SM_TRD + 16)
#define SM_TGAT  (SM_TPUB + 128)
#define SM_CAL   (SM_TGAT + 64)
#define SM_TOTAL (SM_CAL + 128)
#define B_SC   (SM_BAR + 0)
#define B_V    (SM_BAR + 16)
#define B_MEM  (SM_BAR + 32)
#define B_P    (SM_BAR + 48)
#define B_X    (SM_BAR + 56)
#define B_EXP  (SM_BAR + 72)

#define TR(ev) do {} while (0)
__device__ __forceinline__ uint32_t tag_of(int s) { return (uint32_t)(((s >> 1) & 1) + 1); }
__device__ __forceinline__ unsigned probe_latency(uint32_t* p, uint32_t zero) {
    uint32_t v, best = 0xffffffffu;
    asm volatile("atom.relaxed.gpu.global.add.u32 %0, [%1], 0;" : "=r"(v) : "l"(p) : "memory");
    #pragma unroll 1
    for (int r = 0; r < 4; r++) {
        uint32_t c0, c1;
        asm volatile("mov.u32 %0, %%clock;" : "=r"(c0) : "r"(v) : "memory");
        asm volatile("atom.relaxed.gpu.global.add.u32 %0, [%1], 0;" : "=r"(v) : "l"(p + ((v + c0) & zero)) : "memory");
        asm volatile("{\n.reg .u32 t;\nand.b32 t, %1, %2;\nmov.u32 %0, %%clock;\nadd.u32 %0, %0, t;\n}" : "=r"(c1) : "r"(v), "r"(zero) : "memory");
        best = min(best, c1 - c0);
    }
    return best;
}
__device__ __forceinline__ void cluster_sync_all() { asm volatile("barrier.cluster.arrive.release.aligned;\nbarrier.cluster.wait.acquire.aligned;" ::: "memory"); }
__device__ __forceinline__ void tma_load_2d(uint32_t dst, const void* map, int c0, int c1, uint32_t bar) {
    asm volatile("cp.async.bulk.tensor.2d.shared::cluster.global.mbarrier::complete_tx::bytes [%0], [%1, {%3, %4}], [%2];"
        :: "r"(dst), "l"(map), "r"(bar), "r"(c0), "r"(c1) : "memory");
}
__device__ __forceinline__ void tma_load_3d(uint32_t dst, const void* map, int c0, int c1, int c2, uint32_t bar) {
    asm volatile("cp.async.bulk.tensor.3d.shared::cluster.global.mbarrier::complete_tx::bytes [%0], [%1, {%3, %4, %5}], [%2];"
        :: "r"(dst), "l"(map), "r"(bar), "r"(c0), "r"(c1), "r"(c2) : "memory");
}
__device__ __forceinline__ void stsm4t(uint32_t addr, uint32_t r0, uint32_t r1, uint32_t r2, uint32_t r3) {
    asm volatile("stmatrix.sync.aligned.m8n8.x4.trans.shared.b16 [%0], {%1,%2,%3,%4};" :: "r"(addr), "r"(r0), "r"(r1), "r"(r2), "r"(r3) : "memory");
}
__device__ __forceinline__ void wgmma_n32_rs(float (&d)[16], const uint32_t (&a)[4], uint64_t db, int scale_d) {
    asm volatile("{\n.reg .pred p;\nsetp.ne.b32 p, %21, 0;\n"
        "wgmma.mma_async.sync.aligned.m64n32k16.f32.bf16.bf16 {%0,%1,%2,%3,%4,%5,%6,%7,%8,%9,%10,%11,%12,%13,%14,%15}, {%16,%17,%18,%19}, %20, p, 1, 1, 0;\n}\n"
        : "+f"(d[0]), "+f"(d[1]), "+f"(d[2]), "+f"(d[3]), "+f"(d[4]), "+f"(d[5]), "+f"(d[6]), "+f"(d[7]),
          "+f"(d[8]), "+f"(d[9]), "+f"(d[10]), "+f"(d[11]), "+f"(d[12]), "+f"(d[13]), "+f"(d[14]), "+f"(d[15])
        : "r"(a[0]), "r"(a[1]), "r"(a[2]), "r"(a[3]), "l"(db), "r"(scale_d));
}

__device__ __forceinline__ void st_async4u(uint32_t addr, uint4 v, uint32_t bar) {
    asm volatile("st.async.weak.shared::cluster.mbarrier::complete_tx::bytes.v4.u32 [%0], {%1,%2,%3,%4}, [%5];" :: "r"(addr), "r"(v.x), "r"(v.y), "r"(v.z), "r"(v.w), "r"(bar) : "memory");
}
__device__ __forceinline__ void export_issue(uint32_t sb, int s, int h, uint32_t rank) {
    const size_t img = (size_t)(s * NH + h) * 2;
    const int sl = s & 1;
    if (rank == 2) {
        bulk_s2g(g_Vimg + img * 2560, sb + SM_VT + sl * 10240, 5120);
        bulk_s2g(g_Vimg + (img + 1) * 2560, sb + SM_VT + sl * 10240 + 5120, 5120);
    } else {
        bulk_s2g(g_Qimg + (img + rank) * 2048, sb + SM_QT, 4096);
        bulk_s2g(g_Kimg + (img + rank) * 2560, sb + SM_KT + sl * 5120, 5120);
    }
    bulk_commit();
    bulk_wait_read0();
    mbar_arrive(sb + B_EXP);
}
__device__ __forceinline__ void export_signal(int s, int h) {
    bulk_wait0();
    asm volatile("fence.proxy.async;" ::: "memory");
    __threadfence();
    atomicAdd(&g_flag[s][h], 1u);
}

__device__ __forceinline__ void score_tile(uint32_t sb, int sl, int nt, int lane, uint32_t rank) {
    float sc[4] = {0, 0, 0, 0}, sd[4] = {0, 0, 0, 0};
    const int r = lane & 7;
    uint32_t qa[2][4], kb[2][4];
    #pragma unroll
    for (int j = 0; j < 2; j++) {
        const int chunk = (lane >> 3) + 4 * j;
        ldsm4(kb[j], sb + SM_KT + sl * 5120 + (8 * nt + r) * 128 + ((chunk ^ r) << 4));
        ldsm4(qa[j], sb + SM_QS + r * 128 + ((chunk ^ r) << 4));
    }
    mma_bf16(sc, qa[0][0], 0u, qa[0][1], 0u, kb[0][0], kb[0][1]);
    mma_bf16(sd, qa[1][0], 0u, qa[1][1], 0u, kb[1][0], kb[1][1]);
    mma_bf16(sc, qa[0][2], 0u, qa[0][3], 0u, kb[0][2], kb[0][3]);
    mma_bf16(sd, qa[1][2], 0u, qa[1][3], 0u, kb[1][2], kb[1][3]);
    sc[0] += sd[0]; sc[1] += sd[1];
    const float o0 = __shfl_down_sync(~0u, sc[0], 1), o1 = __shfl_down_sync(~0u, sc[1], 1);
    if ((lane & 1) == 0) {
        const uint32_t a = SM_SC + sl * 2560 + rank * 1280 + ((lane >> 2) * 40 + 8 * nt + 2 * (lane & 3)) * 4;
        const uint32_t bo = B_SC + 8 * sl;
        { const uint32_t rb = mapa(sb, 2); st_async4(rb + a, sc[0], sc[1], o0, o1, rb + bo); }
        { const uint32_t rb = mapa(sb, rank ^ 1); st_async4(rb + a, sc[0], sc[1], o0, o1, rb + bo); }
        asm volatile("st.shared.v4.f32 [%0], {%1,%2,%3,%4};" :: "r"(sb + a), "f"(sc[0]), "f"(sc[1]), "f"(o0), "f"(o1) : "memory");
    }
    __syncwarp();
    if (lane == 0) mbar_arrive(sb + B_SC + 8 * sl);
}
__device__ __forceinline__ void wgmma_n40_rs(float (&d)[20], const uint32_t (&a)[4], uint64_t db, int scale_d) {
    asm volatile("{\n.reg .pred p;\nsetp.ne.b32 p, %25, 0;\n"
        "wgmma.mma_async.sync.aligned.m64n40k16.f32.bf16.bf16 {%0,%1,%2,%3,%4,%5,%6,%7,%8,%9,%10,%11,%12,%13,%14,%15,%16,%17,%18,%19}, {%20,%21,%22,%23}, %24, p, 1, 1, 0;\n}\n"
        : "+f"(d[0]), "+f"(d[1]), "+f"(d[2]), "+f"(d[3]), "+f"(d[4]), "+f"(d[5]), "+f"(d[6]), "+f"(d[7]), "+f"(d[8]), "+f"(d[9]),
          "+f"(d[10]), "+f"(d[11]), "+f"(d[12]), "+f"(d[13]), "+f"(d[14]), "+f"(d[15]), "+f"(d[16]), "+f"(d[17]), "+f"(d[18]), "+f"(d[19])
        : "r"(a[0]), "r"(a[1]), "r"(a[2]), "r"(a[3]), "l"(db), "r"(scale_d));
}
__device__ __forceinline__ void pu_store(const float (&u)[20], const uint32_t (&pb)[5], float2 inv, unsigned char* smem, int sl, int lt, int warp, int lane, uint32_t tg) {
    float o[4] = {0, 0, 0, 0}, o2[4] = {0, 0, 0, 0};
    mma_bf16(o, pack_bf16(u[0], u[1]), pack_bf16(u[2], u[3]), pack_bf16(u[4], u[5]), pack_bf16(u[6], u[7]), pb[0], pb[1]);
    mma_bf16(o2, pack_bf16(u[8], u[9]), pack_bf16(u[10], u[11]), pack_bf16(u[12], u[13]), pack_bf16(u[14], u[15]), pb[2], pb[3]);
    mma_bf16(o, pack_bf16(u[16], u[17]), pack_bf16(u[18], u[19]), 0u, 0u, pb[4], 0u);
    const uint2 off = *reinterpret_cast<const uint2*>(smem + SM_TPM + (((sl * 4 + lt) * 4 + warp) * 2) * 4);
    unsigned char* pool = reinterpret_cast<unsigned char*>(g_pool) + lane * 8;
    st_relaxed2(pool + off.x, (__float_as_uint((o[0] + o2[0]) * inv.x) & ~3u) | tg, (__float_as_uint((o[1] + o2[1]) * inv.y) & ~3u) | tg);
    st_relaxed2(pool + off.y, (__float_as_uint((o[2] + o2[2]) * inv.x) & ~3u) | tg, (__float_as_uint((o[3] + o2[3]) * inv.y) & ~3u) | tg);
}
template <int NT>
__device__ __forceinline__ void u_pass(unsigned char* smem, uint32_t sb, int s, uint32_t rank, int wg, int warp, int lane) {
    const int sl = s & 1;
    constexpr int NRS = 6;
    uint32_t wa[NRS][4];
    {
        const int mi = lane >> 3, chunk = 2 * warp + (mi & 1);
        #pragma unroll
        for (int ks = 0; ks < NRS; ks++) {
            const int row = 16 * ks + (mi >> 1) * 8 + (lane & 7);
            ldsm4t(wa[ks], sb + SM_WO + (2 * wg) * 16384 + row * 128 + ((chunk ^ (row & 7)) << 4));
        }
    }
    if (rank < 2) { mbar_wait(sb + B_V + 8 * sl, (s >> 1) & 1); fence_async(); }
    if (wg == 0 && warp == 0) TR(4);
    float U0[20];
    wg_fence();
    #pragma unroll
    for (int ks = 0; ks < NRS; ks++)
        wgmma_n40_rs(U0, wa[ks], make_desc(sb + SM_VT + sl * 10240 + (ks >> 2) * 5120 + (ks & 3) * 32, 16, 1024), ks > 0);
    #pragma unroll
    for (int ks = NRS; ks < 8; ks++)
        wgmma_n40_tA(U0, make_desc(sb + SM_WO + (2 * wg) * 16384 + ks * 2048, 1024, 1024),
                     make_desc(sb + SM_VT + sl * 10240 + (ks >> 2) * 5120 + (ks & 3) * 32, 16, 1024), 1);
    wg_commit();
    const uint32_t tg = tag_of(s);
    uint32_t pb[5];
    float2 inv;
    auto get_p = [&]() {
        nbar_sync(9, 288);
        const uint32_t* pbs = reinterpret_cast<const uint32_t*>(smem + SM_PB);
        #pragma unroll
        for (int q = 0; q < 5; q++) pb[q] = pbs[q * 32 + lane];
        float sm[4] = {0, 0, 0, 0}, sm2[4] = {0, 0, 0, 0};
        const uint32_t one = 0x3f803f80u;
        mma_bf16(sm, one, one, one, one, pb[0], pb[1]);
        mma_bf16(sm2, one, one, one, one, pb[2], pb[3]);
        mma_bf16(sm, one, one, 0u, 0u, pb[4], 0u);
        inv.x = __frcp_rn(sm[0] + sm2[0]); inv.y = __frcp_rn(sm[1] + sm2[1]);
    };
    if (NT == 2) {
        wg_wait0();
        float U1[20];
        wg_fence();
        #pragma unroll
        for (int ks = 0; ks < 8; ks++)
            wgmma_n40_tA(U1, make_desc(sb + SM_WO + (2 * wg + 1) * 16384 + ks * 2048, 1024, 1024),
                         make_desc(sb + SM_VT + sl * 10240 + (ks >> 2) * 5120 + (ks & 3) * 32, 16, 1024), ks > 0);
        wg_commit();
        get_p();
        if (wg == 0 && warp == 0) TR(8);
        pu_store(U0, pb, inv, smem, sl, 2 * wg, warp, lane, tg);
        wg_wait0();
        if (wg == 0 && warp == 0) TR(6);
        pu_store(U1, pb, inv, smem, sl, 2 * wg + 1, warp, lane, tg);
    } else {
        wg_wait0();
        get_p();
        pu_store(U0, pb, inv, smem, sl, 2 * wg, warp, lane, tg);
    }
}

__global__ void __cluster_dims__(3, 1, 1) __launch_bounds__(384, 1)
k_chain(const __grid_constant__ CUtensorMap xmap, const bf16* __restrict__ xptr, const bf16* __restrict__ mem0, const bf16* __restrict__ Wq, const bf16* __restrict__ Wk,
        const bf16* __restrict__ Wv, const bf16* __restrict__ Wo) {
    extern __shared__ __align__(1024) unsigned char smem[];
    const uint32_t sb = smem_u32(smem);
    const int tid = threadIdx.x, lane = tid & 31;
    const int wg = __shfl_sync(~0u, tid >> 7, 0), warp = __shfl_sync(~0u, (tid >> 5) & 3, 0);
    uint32_t rank; asm volatile("mov.u32 %0, %%cluster_ctarank;" : "=r"(rank));
    const int cta = blockIdx.x, h = cta / 3;
    asm volatile("griddepcontrol.launch_dependents;");
    if (tid == 0) {
        for (int i = 0; i < 2; i++) { mbar_init(sb + B_SC + 8 * i, rank < 2 ? 6 : 1); mbar_init(sb + B_V + 8 * i, 1); mbar_init(sb + B_MEM + 8 * i, 64); mbar_init(sb + B_X + 8 * i, 1); }
        mbar_init(sb + B_P, 32); mbar_init(sb + B_EXP, 1);
        asm volatile("fence.mbarrier_init.release.cluster;" ::: "memory");
    }
    if (tid < 80) asm volatile("prefetch.global.L2 [%0];" :: "l"(mem0 + tid * 64));
    if (h < 2) { for (int i = tid; i < 320; i += 384) asm volatile("prefetch.global.L2 [%0];" :: "l"(xptr + (size_t)h * 32 * DM + i * 64)); }
    {
        const int w12 = tid >> 5;
        if (lane == 0 && w12 < 7) {
            uint32_t* pp = (w12 < 6) ? g_pool + (size_t)(cta * 6 + w12) * 1024 + 512 : g_pool + (size_t)NPOOL * 1024 + (cta & 31) * 32 + (cta >> 5) * 8;
            const unsigned lat = probe_latency(pp, blockIdx.y);
            if (w12 < 6) g_cls[cta * 6 + w12] = lat > CAL_THR ? 1u : 0u; else g_side[cta] = lat > CAL_THR ? 1u : 0u;
        }
        __syncwarp();
        uint4* z = reinterpret_cast<uint4*>(g_pool + (size_t)cta * 6 * 1024);
        #pragma unroll
        for (int q = 0; q < 4; q++) z[tid + 384 * q] = make_uint4(0, 0, 0, 0);
        __threadfence();
        __syncwarp();
        if (lane == 0) atomicAdd(&g_calcnt, 1u);
    }
    {
        const int ntile = (rank == 2) ? 4 : 3;
        const int tile0 = (rank == 2) ? 0 : (rank == 0 ? 4 : 7);
        const bf16* src0 = (rank == 2) ? Wv + h * DH : Wq + h * DH + rank * 64;
        const bf16* src1 = (rank == 2) ? Wv + h * DH + 64 : Wk + h * DH + rank * 64;
        for (int i = tid; i < 2 * 640 * 8; i += 384) {
            int mt = i / 5120, r = (i % 5120) >> 3, c = i & 7;
            const bf16* s = (mt ? src1 : src0) + (size_t)r * HD + c * 8;
            cp_async16(sb + mt * 81920 + r * 128 + ((c ^ (r & 7)) << 4), s);
        }
        for (int i = tid; i < ntile * 128 * 8; i += 384) {
            int lt = i >> 10, r = (i >> 3) & 127, c = i & 7;
            const bf16* s = Wo + ((size_t)h * DH + r) * DM + (tile0 + lt) * 64 + c * 8;
            cp_async16(sb + SM_WO + lt * 16384 + r * 128 + ((c ^ (r & 7)) << 4), s);
        }
        if (wg == 2) {
            const int ct = tid & 127;
            if (ct == 0) {
                const unsigned target = (*reinterpret_cast<volatile unsigned*>(&g_epoch) + 1u) * (96u * 12u);
                int guard = 0;
                while ((int)(ld_acquire(&g_calcnt) - target) < 0 && ++guard < (1 << 22)) {}
            }
            nbar_sync(4, 128);
            uint32_t* bm = reinterpret_cast<uint32_t*>(smem + SM_CAL);
            {
                unsigned v[5];
                #pragma unroll
                for (int q = 0; q < 5; q++) { const int b = ct + 128 * q; v[q] = (b < NPOOL) ? (__ldcg(&g_cls[b]) ^ __ldcg(&g_side[b / 6])) : 0u; }
                const unsigned sv = (ct < 96) ? __ldcg(&g_side[ct]) : 0u;
                #pragma unroll
                for (int q = 0; q < 5; q++) { const unsigned m = __ballot_sync(~0u, v[q] & 1u); if (lane == 0 && q * 4 + warp < 18) bm[q * 4 + warp] = m; }
                const unsigned m = __ballot_sync(~0u, sv & 1u);
                if (lane == 0 && warp < 3) bm[18 + warp] = m;
            }
            nbar_sync(4, 128);
            int nblk1 = 0;
            for (int i = 0; i < 18; i++) nblk1 += __popc(bm[i]);
            const unsigned red_last = (1u << (NRED - 64)) - 1u;
            const int nred1 = __popc(bm[18]) + __popc(bm[19]) + __popc(bm[20] & red_last);
            auto side_of = [&](int c) -> int { return (bm[18 + (c >> 5)] >> (c & 31)) & 1; };
            auto rank_of = [&](int c) -> int {
                int ones = 0;
                for (int i = 0; i < (c >> 5); i++) ones += __popc(bm[18 + i]);
                ones += __popc(bm[18 + (c >> 5)] & ((1u << (c & 31)) - 1u));
                return side_of(c) ? ones : c - ones;
            };
            auto nth = [&](int side, int idx) -> uint32_t {
                for (int i = 0; i < 18; i++) {
                    const unsigned m = side ? bm[i] : ~bm[i];
                    const int n = __popc(m);
                    if (idx < n) return (uint32_t)(i * 32 + __fns(m, 0, idx + 1));
                    idx -= n;
                }
                return 0u;
            };
            auto phys = [&](int side, int idx) -> uint32_t {
                const int c = side ? nblk1 : NPOOL - nblk1;
                return (idx < c) ? nth(side, idx) : nth(side ^ 1, (NPOOL - c) - 1 - (idx - c));
            };
            const int e = ct;
            if (e < 64) {
                const int slot = e >> 5, lt = (e >> 3) & 3, w = (e >> 1) & 3, hf = e & 1;
                const int tile = min(tile0 + lt, 9);
                const int r = 2 * (4 * tile + w) + hf;
                reinterpret_cast<uint32_t*>(smem + SM_TPM)[e] = phys(side_of(r), 4 * rank_of(r) + slot * 2 + (h >> 4)) * 4096u + (h & 15) * 256u;
            } else if (e < 68) {
                const int i = e - 64;
                reinterpret_cast<uint32_t*>(smem + SM_TRD)[i] = (cta < NRED) ? phys(side_of(cta), 4 * rank_of(cta) + i) * 4096u : 0u;
            } else if (e < 100) {
                const int i = e - 68, slot = i >> 3, rep = i & 7, side = (rep / RPS) & 1;
                reinterpret_cast<uint32_t*>(smem + SM_TPUB)[i] = phys(side, 4 * (side ? nred1 : NRED - nred1) + (slot * RPS + (rep % RPS)) * 3 + (cta >> 5)) * 4096u + (cta & 31) * 128u;
            } else if (e < 112) {
                const int i = e - 100, slot = i / 3, b = i % 3, side = side_of(cta);
                reinterpret_cast<uint32_t*>(smem + SM_TGAT)[slot * 4 + b] = phys(side, 4 * (side ? nred1 : NRED - nred1) + (slot * RPS + (h % RPS)) * 3 + b) * 4096u;
            }
        }
        cp_async_wait_all();
        fence_async();
    }
    __syncthreads();

    if (wg == 2) {
        asm volatile("setmaxnreg.dec.sync.aligned.u32 " COMM_REGS ";");
        const int ct = tid & 127;
        nbar_sync(5, 384);
        for (int c = ct; c < 640; c += 128) {
            int ks = c >> 4, hf = (c >> 3) & 1, r = c & 7;
            *reinterpret_cast<uint4*>(smem + SM_MEMB + c * 16) = *reinterpret_cast<const uint4*>(mem0 + r * DM + ks * 16 + hf * 8);
        }
        if (ct == 0) {
            for (int sg = 0; sg < 2; sg++) {
                mbar_expect_tx(sb + B_X + 8 * sg, 40960);
                tma_load_3d(sb + SM_XB + sg * 40960, &xmap, 0, sg * 32, 0, sb + B_X + 8 * sg);
            }
            mbar_expect_tx(sb + B_SC, rank < 2 ? 1280 : 2560);
            if (rank < 2) mbar_expect_tx(sb + B_V, 8192 + 2048);
        }
        nbar_sync(5, 384);
        cluster_sync_all();
        unsigned char* const pool = reinterpret_cast<unsigned char*>(g_pool);
        for (int s = 0; s < NSEG - 1; s++) {
            if (warp == 0) nbar_sync(6, 288);
            if (warp == 1) nbar_sync(12, 288);
            if (warp == 0) {
                if (rank < 2) score_tile(sb, s & 1, 0, lane, rank);
                const int g = lane >> 2, t = lane & 3;
                mbar_wait(sb + B_SC + 8 * (s & 1), (s >> 1) & 1);
                TR(5);
                const uint32_t sa = sb + SM_SC + (s & 1) * 2560 + (g * 40 + 2 * t) * 4;
                float v[5][2], u[5][2];
                #pragma unroll
                for (int q = 0; q < 5; q++) {
                    asm volatile("ld.shared.v2.f32 {%0,%1}, [%2];" : "=f"(v[q][0]), "=f"(v[q][1]) : "r"(sa + 32 * q) : "memory");
                    asm volatile("ld.shared.v2.f32 {%0,%1}, [%2];" : "=f"(u[q][0]), "=f"(u[q][1]) : "r"(sa + 1280 + 32 * q) : "memory");
                }
                float mx = -3.0e38f;
                #pragma unroll
                for (int q = 0; q < 5; q++) {
                    v[q][0] += u[q][0]; v[q][1] += u[q][1];
                    mx = fmaxf(mx, fmaxf(v[q][0], v[q][1]));
                }
                mx = fmaxf(mx, __shfl_xor_sync(~0u, mx, 1));
                mx = fmaxf(mx, __shfl_xor_sync(~0u, mx, 2));
                const float sc2 = 0.08838834764831845f * 1.4426950408889634f;
                const float mxs = mx * sc2;
                uint32_t* pbs = reinterpret_cast<uint32_t*>(smem + SM_PB);
                #pragma unroll
                for (int q = 0; q < 5; q++) {
                    const float e0 = ex2_approx(fmaf(v[q][0], sc2, -mxs)), e1 = ex2_approx(fmaf(v[q][1], sc2, -mxs));
                    pbs[q * 32 + lane] = pack_bf16(e0, e1);
                }
                __syncwarp();
                TR(0);
                nbar_arrive(9, 288);
            } else if (warp == 1 && lane == 0) {
                if (s + 1 < NSEG - 1) {
                    mbar_expect_tx(sb + B_SC + 8 * ((s + 1) & 1), rank < 2 ? 1280 : 2560);
                    if (rank < 2) mbar_expect_tx(sb + B_V + 8 * ((s + 1) & 1), 8192 + 2048);
                }
                if (s + 2 < NSEG) {
                    mbar_expect_tx(sb + B_X + 8 * (s & 1), 40960);
                    tma_load_3d(sb + SM_XB + (s & 1) * 40960, &xmap, 0, (s + 2) * 32, 0, sb + B_X + 8 * (s & 1));
                }
                export_issue(sb, s, h, rank);
                if (s >= NSEG - 4) export_signal(s, h);
            }
            __syncwarp();
            nbar_sync(3, 384);
            const uint32_t tg = tag_of(s);
            if (cta < NRED) {
                const unsigned char* base = pool + reinterpret_cast<const uint32_t*>(smem + SM_TRD)[(s & 1) * 2 + (warp >> 1)] + (warp & 1) * 2048 + lane * 16;
                uint4 v[4]; int guard = 0;
                #pragma unroll
                for (int j = 0; j < 4; j++) v[j] = make_uint4(0, 0, 0, 0);
                uint32_t pend = 0xF;
                do {
                    #pragma unroll
                    for (int j = 0; j < 4; j++) if (pend & (1u << j)) v[j] = ld_relaxed4(base + j * 512);
                    #pragma unroll
                    for (int j = 0; j < 4; j++)
                        if (((v[j].x & 3) == tg) && ((v[j].y & 3) == tg) && ((v[j].z & 3) == tg) && ((v[j].w & 3) == tg)) pend &= ~(1u << j);
                } while (__any_sync(~0u, pend != 0) && ++guard < (1 << 20));
                if (warp == 0) TR(9);
                float a0 = 0, a1 = 0, a2 = 0, a3 = 0;
                #pragma unroll
                for (int j = 0; j < 4; j++) { a0 += __uint_as_float(v[j].x); a1 += __uint_as_float(v[j].y); a2 += __uint_as_float(v[j].z); a3 += __uint_as_float(v[j].w); }
                a0 += __shfl_xor_sync(~0u, a0, 16); a1 += __shfl_xor_sync(~0u, a1, 16); a2 += __shfl_xor_sync(~0u, a2, 16); a3 += __shfl_xor_sync(~0u, a3, 16);
                float* cr = reinterpret_cast<float*>(smem + SM_CRED);
                if (lane < 16) *reinterpret_cast<float4*>(cr + warp * 64 + lane * 4) = make_float4(a0, a1, a2, a3);
                nbar_sync(4, 128);
                {
                    int rho = lane >> 2, pp = lane & 3;
                    int i0 = ((2 * pp) * 4 + (rho >> 1)) * 2 + (rho & 1), i1 = i0 + 8;
                    uint32_t wv = pack_bf16((cr[i0] + cr[64 + i0]) + (cr[128 + i0] + cr[192 + i0]), (cr[i1] + cr[64 + i1]) + (cr[128 + i1] + cr[192 + i1]));
                    if (wv == 0) wv = 0x8000u;
                    if (warp == 0) TR(10);
                    const uint32_t* tp = reinterpret_cast<const uint32_t*>(smem + SM_TPUB) + warp;
                    if (warp < 2 * RPS) st_relaxed1(pool + tp[((s + 1) & 3) * 8] + lane * 4, wv);
                    if (RPS == 4) st_relaxed1(pool + tp[((s + 1) & 3) * 8 + 4] + lane * 4, wv);
                    if (warp < 2 * RPS) st_relaxed1(pool + tp[(s & 3) * 8] + lane * 4, 0u);
                    if (RPS == 4) st_relaxed1(pool + tp[(s & 3) * 8 + 4] + lane * 4, 0u);
                }
            }
            {
                const int c0 = warp * 160 + lane;
                const uint32_t* tg3 = reinterpret_cast<const uint32_t*>(smem + SM_TGAT) + ((s + 1) & 3) * 4;
                const uint32_t g0 = tg3[0], g1 = tg3[1], g2 = tg3[2];
                uint4 v[5]; int guard = 0;
                #pragma unroll
                for (int j = 0; j < 5; j++) v[j] = make_uint4(0, 0, 0, 0);
                uint32_t pend = 0x1F;
                do {
                    #pragma unroll
                    for (int j = 0; j < 5; j++) {
                        const int c = c0 + 32 * j;
                        if (pend & (1u << j)) v[j] = ld_relaxed4(pool + ((c >> 8) == 0 ? g0 : ((c >> 8) == 1 ? g1 : g2)) + (c & 255) * 16);
                    }
                    #pragma unroll
                    for (int j = 0; j < 5; j++) if (v[j].x && v[j].y && v[j].z && v[j].w) pend &= ~(1u << j);
                } while (__any_sync(~0u, pend != 0) && ++guard < (1 << 20));
                #pragma unroll
                for (int j = 0; j < 5; j++) *reinterpret_cast<uint4*>(smem + SM_MEMB + (c0 + 32 * j) * 16) = v[j];
                if (warp == 0) TR(11);
                if (warp == 3) TR(12);
                nbar_arrive(warp < 2 ? 7 + warp : 8 + warp, 160);
            }
            if (warp == 1 && lane == 0 && s < NSEG - 4) export_signal(s, h);
            __syncwarp();
        }
        if (warp == 0) nbar_sync(6, 288);
        if (warp == 1) { nbar_sync(12, 288); if (lane == 0) { export_issue(sb, NSEG - 1, h, rank); export_signal(NSEG - 1, h); } }
        __syncwarp();
        nbar_sync(3, 384);
        __syncwarp();
        cluster_sync_all();
    } else {
        asm volatile("setmaxnreg.inc.sync.aligned.u32 232;");
        const int wtid = tid & 127;
        const int cw = wg * 4 + warp;
        uint32_t areg[2][20][4];
        #pragma unroll
        for (int mt = 0; mt < 2; mt++)
            #pragma unroll
            for (int kk = 0; kk < 20; kk++) {
                int mi = lane >> 3;
                int row = 16 * (20 * wg + kk) + (mi >> 1) * 8 + (lane & 7);
                int chunk = 2 * warp + (mi & 1);
                ldsm4t(areg[mt][kk], sb + mt * 81920 + row * 128 + ((chunk ^ (row & 7)) << 4));
            }
        nbar_sync(5, 384);
        nbar_sync(5, 384);
        cluster_sync_all();

        for (int s = -1; s < NSEG; s++) {
            const int sl = s & 1;
            if (s >= 0) {
            if (s > 0) nbar_sync(7 + 3 * wg, 160);
            float fin[4];
            {
                float acc[2][2][4];
                #pragma unroll
                for (int i = 0; i < 2; i++)
                    #pragma unroll
                    for (int j = 0; j < 2; j++) { acc[i][j][0] = acc[i][j][1] = acc[i][j][2] = acc[i][j][3] = 0.f; }
                uint32_t b[3][4];
                const uint32_t mb = sb + SM_MEMB + (20 * wg) * 256 + lane * 16;
                ldsm4(b[0], mb); ldsm4(b[1], mb + 512);
                #pragma unroll
                for (int kp = 0; kp < 10; kp++) {
                    if (kp == 3 && s > 0) nbar_sync(8 + 3 * wg, 160);
                    if (kp + 2 < 10) ldsm4(b[(kp + 2) % 3], mb + (kp + 2) * 512);
                    const uint32_t (&bb)[4] = b[kp % 3];
                    mma_bf16(acc[0][0], areg[0][2 * kp][0], areg[0][2 * kp][1], areg[0][2 * kp][2], areg[0][2 * kp][3], bb[0], bb[1]);
                    mma_bf16(acc[1][0], areg[1][2 * kp][0], areg[1][2 * kp][1], areg[1][2 * kp][2], areg[1][2 * kp][3], bb[0], bb[1]);
                    mma_bf16(acc[0][1], areg[0][2 * kp + 1][0], areg[0][2 * kp + 1][1], areg[0][2 * kp + 1][2], areg[0][2 * kp + 1][3], bb[2], bb[3]);
                    mma_bf16(acc[1][1], areg[1][2 * kp + 1][0], areg[1][2 * kp + 1][1], areg[1][2 * kp + 1][2], areg[1][2 * kp + 1][3], bb[2], bb[3]);
                }
                float4* red = reinterpret_cast<float4*>(smem + SM_RED);
                float m0[4], m1[4];
                #pragma unroll
                for (int i = 0; i < 4; i++) { m0[i] = acc[0][0][i] + acc[0][1][i]; m1[i] = acc[1][0][i] + acc[1][1][i]; }
                red[(wg ^ 1) * 128 + wtid] = wg == 0 ? make_float4(m1[0], m1[1], m1[2], m1[3]) : make_float4(m0[0], m0[1], m0[2], m0[3]);
                nbar_sync(1, 256);
                float4 r = red[wg * 128 + wtid];
                fin[0] = (wg == 0 ? m0[0] : m1[0]) + r.x; fin[1] = (wg == 0 ? m0[1] : m1[1]) + r.y;
                fin[2] = (wg == 0 ? m0[2] : m1[2]) + r.z; fin[3] = (wg == 0 ? m0[3] : m1[3]) + r.w;
            }
            if (cw == 0) TR(1);
            {
                uint32_t p0 = pack_bf16(fin[0], fin[1]), p1 = pack_bf16(fin[2], fin[3]);
                const uint32_t doff = (rank == 2) ? SM_VT + sl * 10240 + wg * 5120 : (wg == 0 ? SM_QS : SM_KT + sl * 5120);
                const int r = lane & 7, chunk = 2 * warp + ((lane >> 3) & 1);
                const uint32_t coff = doff + r * 128 + ((chunk ^ r) << 4);
                stsm2t(sb + coff, p0, p1);
                if (rank == 2 && s < NSEG - 1) {
                    __syncwarp();
                    const uint4 v = *reinterpret_cast<const uint4*>(smem + coff);
                    const uint32_t rb = mapa(sb, lane >> 4);
                    st_async4u(rb + coff, v, rb + B_V + 8 * sl);
                }
            }
            fence_async();
            nbar_sync(1, 256);
            nbar_arrive(6, 288);
            nbar_arrive(12, 288);
            if (cw == 0) TR(2);
            if (rank < 2 && wg == 1 && s < NSEG - 1) score_tile(sb, sl, 1 + warp, lane, rank);
            if (s == NSEG - 1) break;
            if (cw == 0) TR(3);
            if (wg == 0 || rank == 2) u_pass<2>(smem, sb, s, rank, wg, warp, lane);
            else                      u_pass<1>(smem, sb, s, rank, wg, warp, lane);
            if (cw == 0) TR(7);
            nbar_arrive(3, 384);
            }
            {
                const int sn = s + 1, sln = sn & 1;
                mbar_wait(sb + B_X + 8 * sln, (sn >> 1) & 1);
                float acc[2][16];
                wg_fence();
                #pragma unroll
                for (int mt = 0; mt < 2; mt++)
                    #pragma unroll
                    for (int kk = 0; kk < 20; kk++) {
                        uint64_t db = make_desc(sb + SM_XB + sln * 40960 + (5 * wg + (kk >> 2)) * 4096 + (kk & 3) * 32, 16, 1024);
                        wgmma_n32_rs(acc[mt], areg[mt][kk], db, kk > 0);
                    }
                wg_commit();
                if (cw == 0 && s >= 0) TR(14);
                wg_wait0();
                if (cw == 0 && s >= 0) TR(15);
                float4* red = reinterpret_cast<float4*>(smem + SM_RED);
                #pragma unroll
                for (int j = 0; j < 4; j++) {
                    red[((wg ^ 1) * 4 + j) * 128 + wtid] = make_float4(wg == 0 ? acc[1][4 * j] : acc[0][4 * j], wg == 0 ? acc[1][4 * j + 1] : acc[0][4 * j + 1],
                                                                       wg == 0 ? acc[1][4 * j + 2] : acc[0][4 * j + 2], wg == 0 ? acc[1][4 * j + 3] : acc[0][4 * j + 3]);
                }
                if (s >= 0) mbar_wait(sb + B_EXP, s & 1);
                nbar_sync(1, 256);
                uint32_t pk[8];
                #pragma unroll
                for (int j = 0; j < 4; j++) {
                    float4 r = red[(wg * 4 + j) * 128 + wtid];
                    pk[2 * j] = pack_bf16((wg == 0 ? acc[0][4 * j] : acc[1][4 * j]) + r.x, (wg == 0 ? acc[0][4 * j + 1] : acc[1][4 * j + 1]) + r.y);
                    pk[2 * j + 1] = pack_bf16((wg == 0 ? acc[0][4 * j + 2] : acc[1][4 * j + 2]) + r.z, (wg == 0 ? acc[0][4 * j + 3] : acc[1][4 * j + 3]) + r.w);
                }
                const uint32_t dst = (rank == 2) ? sb + SM_VT + sln * 10240 + wg * 5120 + 1024 : (wg == 0 ? sb + SM_QT : sb + SM_KT + sln * 5120 + 1024);
                #pragma unroll
                for (int jj = 0; jj < 2; jj++) {
                    int mi = lane >> 3, tok = 8 * (2 * jj + (mi >> 1)) + (lane & 7), chunk = 2 * warp + (mi & 1);
                    stsm4t(dst + tok * 128 + ((chunk ^ (tok & 7)) << 4), pk[4 * jj], pk[4 * jj + 1], pk[4 * jj + 2], pk[4 * jj + 3]);
                }
                fence_async();
                nbar_sync(1, 256);
                if (rank == 2 && lane == 0 && cw < 4 && sn < NSEG - 1) {
                    const uint32_t off = SM_VT + sln * 10240 + (cw & 1) * 5120 + 1024;
                    const uint32_t rb = mapa(sb, cw >> 1);
                    bulk_s2c(rb + off, sb + off, 4096, rb + B_V + 8 * sln);
                }
                if (cw == 0 && s >= 0) TR(13);
            }
        }
        nbar_arrive(3, 384);
        __syncwarp();
        cluster_sync_all();
    }
}

#define NAUX 36
__device__ __align__(1024) bf16 g_Oimg[16 * 64 * 128 * 64];
__device__ float    g_part[4 * SEQ * DM];
__device__ float    g_part31[2 * 13 * 64 * DM];
__device__ unsigned g_ocnt[32];
__device__ unsigned g_gcnt[32][2];
__device__ unsigned g_ssmcnt, g_auxdone, g_taskctr, g_gemmctr;
#define NATT 8
#define ATR(i) do {} while (0)
#define ATRID(i, id) do {} while (0)

__device__ __forceinline__ void wait_counter(const unsigned* p, unsigned target) {
    int guard = 0;
    while ((int)(ld_acquire(p) - target) < 0 && ++guard < (1 << 22)) __nanosleep(64);
}
__device__ __forceinline__ void fence_async_all() { asm volatile("fence.proxy.async;" ::: "memory"); }
template <int OFF>
__device__ __forceinline__ void wgmma_n192_tB(float (&d)[160], uint64_t da, uint64_t db) {
    asm volatile("wgmma.mma_async.sync.aligned.m64n192k16.f32.bf16.bf16 {%0,%1,%2,%3,%4,%5,%6,%7,%8,%9,%10,%11,%12,%13,%14,%15,%16,%17,%18,%19,%20,%21,%22,%23,%24,%25,%26,%27,%28,%29,%30,%31,%32,%33,%34,%35,%36,%37,%38,%39,%40,%41,%42,%43,%44,%45,%46,%47,%48,%49,%50,%51,%52,%53,%54,%55,%56,%57,%58,%59,%60,%61,%62,%63,%64,%65,%66,%67,%68,%69,%70,%71,%72,%73,%74,%75,%76,%77,%78,%79,%80,%81,%82,%83,%84,%85,%86,%87,%88,%89,%90,%91,%92,%93,%94,%95}, %96, %97, 1, 1, 1, 0, 1;\n"
        : "+f"(d[OFF + 0]), "+f"(d[OFF + 1]), "+f"(d[OFF + 2]), "+f"(d[OFF + 3]), "+f"(d[OFF + 4]), "+f"(d[OFF + 5]), "+f"(d[OFF + 6]), "+f"(d[OFF + 7]), "+f"(d[OFF + 8]), "+f"(d[OFF + 9]), "+f"(d[OFF + 10]), "+f"(d[OFF + 11]), "+f"(d[OFF + 12]), "+f"(d[OFF + 13]), "+f"(d[OFF + 14]), "+f"(d[OFF + 15]), "+f"(d[OFF + 16]), "+f"(d[OFF + 17]), "+f"(d[OFF + 18]), "+f"(d[OFF + 19]), "+f"(d[OFF + 20]), "+f"(d[OFF + 21]), "+f"(d[OFF + 22]), "+f"(d[OFF + 23]), "+f"(d[OFF + 24]), "+f"(d[OFF + 25]), "+f"(d[OFF + 26]), "+f"(d[OFF + 27]), "+f"(d[OFF + 28]), "+f"(d[OFF + 29]), "+f"(d[OFF + 30]), "+f"(d[OFF + 31]), "+f"(d[OFF + 32]), "+f"(d[OFF + 33]), "+f"(d[OFF + 34]), "+f"(d[OFF + 35]), "+f"(d[OFF + 36]), "+f"(d[OFF + 37]), "+f"(d[OFF + 38]), "+f"(d[OFF + 39]), "+f"(d[OFF + 40]), "+f"(d[OFF + 41]), "+f"(d[OFF + 42]), "+f"(d[OFF + 43]), "+f"(d[OFF + 44]), "+f"(d[OFF + 45]), "+f"(d[OFF + 46]), "+f"(d[OFF + 47]), "+f"(d[OFF + 48]), "+f"(d[OFF + 49]), "+f"(d[OFF + 50]), "+f"(d[OFF + 51]), "+f"(d[OFF + 52]), "+f"(d[OFF + 53]), "+f"(d[OFF + 54]), "+f"(d[OFF + 55]), "+f"(d[OFF + 56]), "+f"(d[OFF + 57]), "+f"(d[OFF + 58]), "+f"(d[OFF + 59]), "+f"(d[OFF + 60]), "+f"(d[OFF + 61]), "+f"(d[OFF + 62]), "+f"(d[OFF + 63]), "+f"(d[OFF + 64]), "+f"(d[OFF + 65]), "+f"(d[OFF + 66]), "+f"(d[OFF + 67]), "+f"(d[OFF + 68]), "+f"(d[OFF + 69]), "+f"(d[OFF + 70]), "+f"(d[OFF + 71]), "+f"(d[OFF + 72]), "+f"(d[OFF + 73]), "+f"(d[OFF + 74]), "+f"(d[OFF + 75]), "+f"(d[OFF + 76]), "+f"(d[OFF + 77]), "+f"(d[OFF + 78]), "+f"(d[OFF + 79]), "+f"(d[OFF + 80]), "+f"(d[OFF + 81]), "+f"(d[OFF + 82]), "+f"(d[OFF + 83]), "+f"(d[OFF + 84]), "+f"(d[OFF + 85]), "+f"(d[OFF + 86]), "+f"(d[OFF + 87]), "+f"(d[OFF + 88]), "+f"(d[OFF + 89]), "+f"(d[OFF + 90]), "+f"(d[OFF + 91]), "+f"(d[OFF + 92]), "+f"(d[OFF + 93]), "+f"(d[OFF + 94]), "+f"(d[OFF + 95])
        : "l"(da), "l"(db));
}
template <int OFF>
__device__ __forceinline__ void wgmma_n128_tB(float (&d)[160], uint64_t da, uint64_t db) {
    asm volatile("wgmma.mma_async.sync.aligned.m64n128k16.f32.bf16.bf16 {%0,%1,%2,%3,%4,%5,%6,%7,%8,%9,%10,%11,%12,%13,%14,%15,%16,%17,%18,%19,%20,%21,%22,%23,%24,%25,%26,%27,%28,%29,%30,%31,%32,%33,%34,%35,%36,%37,%38,%39,%40,%41,%42,%43,%44,%45,%46,%47,%48,%49,%50,%51,%52,%53,%54,%55,%56,%57,%58,%59,%60,%61,%62,%63}, %64, %65, 1, 1, 1, 0, 1;\n"
        : "+f"(d[OFF + 0]), "+f"(d[OFF + 1]), "+f"(d[OFF + 2]), "+f"(d[OFF + 3]), "+f"(d[OFF + 4]), "+f"(d[OFF + 5]), "+f"(d[OFF + 6]), "+f"(d[OFF + 7]), "+f"(d[OFF + 8]), "+f"(d[OFF + 9]), "+f"(d[OFF + 10]), "+f"(d[OFF + 11]), "+f"(d[OFF + 12]), "+f"(d[OFF + 13]), "+f"(d[OFF + 14]), "+f"(d[OFF + 15]), "+f"(d[OFF + 16]), "+f"(d[OFF + 17]), "+f"(d[OFF + 18]), "+f"(d[OFF + 19]), "+f"(d[OFF + 20]), "+f"(d[OFF + 21]), "+f"(d[OFF + 22]), "+f"(d[OFF + 23]), "+f"(d[OFF + 24]), "+f"(d[OFF + 25]), "+f"(d[OFF + 26]), "+f"(d[OFF + 27]), "+f"(d[OFF + 28]), "+f"(d[OFF + 29]), "+f"(d[OFF + 30]), "+f"(d[OFF + 31]), "+f"(d[OFF + 32]), "+f"(d[OFF + 33]), "+f"(d[OFF + 34]), "+f"(d[OFF + 35]), "+f"(d[OFF + 36]), "+f"(d[OFF + 37]), "+f"(d[OFF + 38]), "+f"(d[OFF + 39]), "+f"(d[OFF + 40]), "+f"(d[OFF + 41]), "+f"(d[OFF + 42]), "+f"(d[OFF + 43]), "+f"(d[OFF + 44]), "+f"(d[OFF + 45]), "+f"(d[OFF + 46]), "+f"(d[OFF + 47]), "+f"(d[OFF + 48]), "+f"(d[OFF + 49]), "+f"(d[OFF + 50]), "+f"(d[OFF + 51]), "+f"(d[OFF + 52]), "+f"(d[OFF + 53]), "+f"(d[OFF + 54]), "+f"(d[OFF + 55]), "+f"(d[OFF + 56]), "+f"(d[OFF + 57]), "+f"(d[OFF + 58]), "+f"(d[OFF + 59]), "+f"(d[OFF + 60]), "+f"(d[OFF + 61]), "+f"(d[OFF + 62]), "+f"(d[OFF + 63])
        : "l"(da), "l"(db));
}
__device__ __forceinline__ void stsm4(uint32_t addr, uint32_t r0, uint32_t r1, uint32_t r2, uint32_t r3) {
    asm volatile("stmatrix.sync.aligned.m8n8.x4.shared.b16 [%0], {%1,%2,%3,%4};" :: "r"(addr), "r"(r0), "r"(r1), "r"(r2), "r"(r3) : "memory");
}

#define AX_BAR   0
#define NST_G 4
#define AX_EMPTY (AX_BAR + 16 + 8 * NST_G)
#define AX_DATA  1024
#define AX_UNIT  28672
#define AX_STAGE 57344
#define AX_TOTAL (AX_DATA + 8 * AX_UNIT)

__device__ __forceinline__ void attn_compute(unsigned char* smem, uint32_t sb, uint32_t buf, int warp, int lane);
__device__ __forceinline__ void attn_producer(unsigned char* smem, int hg, unsigned epoch) {
    const uint32_t sb = smem_u32(smem);
    const int lane = threadIdx.x & 31;
    {
        for (int s = 0; s < NSEG; s++) {
            const uint32_t buf = AX_DATA + (s & 1) * (4 * AX_UNIT), bar = sb + AX_BAR + 8 * (s & 1);
            if (lane < 4) wait_counter(&g_flag[s][4 * hg + lane], (epoch + 1) * 3u);
            if (lane == 4) mbar_wait_sleep(sb + AX_EMPTY + 8 * (s & 1), ((s >> 1) & 1) ^ 1);
            __syncwarp();
            if (lane == 0) mbar_expect_tx(bar, 4 * AX_UNIT);
            __syncwarp();
            if (lane < 24) {
                fence_async_all();
                const int u = lane / 6, r = lane % 6, hf = r & 1, kind = r >> 1;
                const uint32_t ub = sb + buf + u * AX_UNIT;
                const size_t img = ((size_t)(s * NH + 4 * hg + u) * 2) + hf;
                if (kind == 0) bulk_g2s(ub + hf * 4096, g_Qimg + img * 2048, 4096, bar);
                else if (kind == 1) bulk_g2s(ub + 8192 + hf * 5120, g_Kimg + img * 2560, 5120, bar);
                else bulk_g2s(ub + 18432 + hf * 5120, g_Vimg + img * 2560, 5120, bar);
            }
            __syncwarp();
        }
    }
}
__device__ __forceinline__ void attn_loop(unsigned char* smem, int hg, unsigned epoch) {
    const uint32_t sb = smem_u32(smem);
    const int tid = threadIdx.x, warp = tid >> 5, lane = tid & 31;
    for (int s = 0; s < NSEG; s++) {
        const uint32_t buf = AX_DATA + (s & 1) * (4 * AX_UNIT), bar = sb + AX_BAR + 8 * (s & 1);
        mbar_wait_sleep(bar, (s >> 1) & 1);
        if (s >= 36) ATR(2 + 2 * (s - 36));
        attn_compute(smem, sb, buf, warp, lane);
        if (s >= 36) ATR(3 + 2 * (s - 36));
        fence_async();
        __syncwarp();
        if (lane == 0) mbar_arrive(sb + AX_EMPTY + 16 + 8 * (s & 1));
    }
}
__device__ __forceinline__ void attn_storer(unsigned char* smem, int hg) {
    const uint32_t sb = smem_u32(smem);
    const int lane = threadIdx.x & 31;
    for (int s = 0; s < NSEG; s++) {
        const uint32_t buf = AX_DATA + (s & 1) * (4 * AX_UNIT);
        mbar_wait_sleep(sb + AX_EMPTY + 16 + 8 * (s & 1), (s >> 1) & 1);
        if (lane < 8) {
            const int uu = lane >> 1, hf = lane & 1, hh = 4 * hg + uu;
            bulk_s2g(g_Oimg + (((size_t)(s >> 2) * 64 + hh * 2 + hf) * 128 + (s & 3) * 32) * 64, sb + buf + uu * AX_UNIT + hf * 4096, 4096);
            bulk_commit();
            bulk_wait_read0();
            mbar_arrive(sb + AX_EMPTY + 8 * (s & 1));
            bulk_wait0();
            fence_async_all();
            __threadfence();
            atomicAdd(&g_ocnt[s >> 1], 1u);
        }
        __syncwarp();
    }
}
__device__ __forceinline__ void attn_compute(unsigned char* smem, uint32_t sb, uint32_t buf, int warp, int lane) {
    const int g = lane >> 2, t = lane & 3;
    const int u = warp >> 1, qh = warp & 1;
    const uint32_t ub = sb + buf + u * AX_UNIT;
    float sc[5][4];
    #pragma unroll
    for (int j = 0; j < 5; j++) { sc[j][0] = sc[j][1] = sc[j][2] = sc[j][3] = 0.f; }
    #pragma unroll
    for (int ks = 0; ks < 8; ks++) {
        const int hf = ks >> 2, c0 = (ks & 3) * 2;
        uint32_t a[4];
        { int mi = lane >> 3, row = 16 * qh + (mi & 1) * 8 + (lane & 7), chunk = c0 + (mi >> 1);
          ldsm4(a, ub + hf * 4096 + row * 128 + ((chunk ^ (row & 7)) << 4)); }
        #pragma unroll
        for (int jp = 0; jp < 3; jp++) {
            uint32_t b[4];
            int mi = lane >> 3, nt = 2 * jp + (mi >> 1); if (nt > 4) nt = 4;
            int row = 8 * nt + (lane & 7), chunk = c0 + (mi & 1);
            ldsm4(b, ub + 8192 + hf * 5120 + row * 128 + ((chunk ^ (row & 7)) << 4));
            mma_bf16(sc[2 * jp], a[0], a[1], a[2], a[3], b[0], b[1]);
            if (jp < 2) mma_bf16(sc[2 * jp + 1], a[0], a[1], a[2], a[3], b[2], b[3]);
        }
    }
    uint32_t pa[3][4];
    {
        const float sc2 = 0.08838834764831845f * 1.4426950408889634f;
        float mx0 = -3.0e38f, mx1 = -3.0e38f;
        const int q0 = 16 * qh + g, q1 = q0 + 8;
        #pragma unroll
        for (int j = 0; j < 5; j++)
            #pragma unroll
            for (int e = 0; e < 2; e++) {
                int key = 8 * j + 2 * t + e - 8;
                sc[j][e] = (key <= q0) ? sc[j][e] * sc2 : -3.0e38f;
                sc[j][2 + e] = (key <= q1) ? sc[j][2 + e] * sc2 : -3.0e38f;
                mx0 = fmaxf(mx0, sc[j][e]); mx1 = fmaxf(mx1, sc[j][2 + e]);
            }
        mx0 = fmaxf(mx0, __shfl_xor_sync(~0u, mx0, 1)); mx0 = fmaxf(mx0, __shfl_xor_sync(~0u, mx0, 2));
        mx1 = fmaxf(mx1, __shfl_xor_sync(~0u, mx1, 1)); mx1 = fmaxf(mx1, __shfl_xor_sync(~0u, mx1, 2));
        float s0 = 0.f, s1 = 0.f;
        #pragma unroll
        for (int j = 0; j < 5; j++)
            #pragma unroll
            for (int e = 0; e < 2; e++) {
                sc[j][e] = ex2_approx(sc[j][e] - mx0); sc[j][2 + e] = ex2_approx(sc[j][2 + e] - mx1);
                s0 += sc[j][e]; s1 += sc[j][2 + e];
            }
        s0 += __shfl_xor_sync(~0u, s0, 1); s0 += __shfl_xor_sync(~0u, s0, 2);
        s1 += __shfl_xor_sync(~0u, s1, 1); s1 += __shfl_xor_sync(~0u, s1, 2);
        const float i0 = __frcp_rn(s0), i1 = __frcp_rn(s1);
        #pragma unroll
        for (int k = 0; k < 3; k++) {
            pa[k][0] = pack_bf16(sc[2 * k][0] * i0, sc[2 * k][1] * i0);
            pa[k][1] = pack_bf16(sc[2 * k][2] * i1, sc[2 * k][3] * i1);
            if (k < 2) { pa[k][2] = pack_bf16(sc[2 * k + 1][0] * i0, sc[2 * k + 1][1] * i0); pa[k][3] = pack_bf16(sc[2 * k + 1][2] * i1, sc[2 * k + 1][3] * i1); }
            else { pa[k][2] = 0u; pa[k][3] = 0u; }
        }
    }
    __syncwarp();
    nbar_sync(5 + u, 64);
    #pragma unroll
    for (int np = 0; np < 8; np++) {
        const int hf = np >> 2, c0 = (np & 3) * 2;
        float o0[4] = {0, 0, 0, 0}, o1[4] = {0, 0, 0, 0};
        #pragma unroll
        for (int k = 0; k < 3; k++) {
            uint32_t b[4];
            int mi = lane >> 3;
            int row = 16 * k + (mi & 1) * 8 + (lane & 7); if (row > 39) row = 39 - 7 + (lane & 7);
            int chunk = c0 + (mi >> 1);
            ldsm4t(b, ub + 18432 + hf * 5120 + row * 128 + ((chunk ^ (row & 7)) << 4));
            mma_bf16(o0, pa[k][0], pa[k][1], pa[k][2], pa[k][3], b[0], k < 2 ? b[1] : 0u);
            mma_bf16(o1, pa[k][0], pa[k][1], pa[k][2], pa[k][3], b[2], k < 2 ? b[3] : 0u);
        }
        int mi = lane >> 3, row = 16 * qh + (mi & 1) * 8 + (lane & 7), chunk = c0 + (mi >> 1);
        stsm4(ub + hf * 4096 + row * 128 + ((chunk ^ (row & 7)) << 4), pack_bf16(o0[0], o0[1]), pack_bf16(o0[2], o0[3]), pack_bf16(o1[0], o1[1]), pack_bf16(o1[2], o1[3]));
    }
}

template <int V> struct IntC { static constexpr int value = V; };
struct Task { int type, rb, c, k0, nch, plane; };
#define NFINE 30
#define NGEMM (8 + 144 + 8 * 2 + 4 + 8 * 6 + 26 * 2 + 16 * 2)
__device__ __forceinline__ Task decode_task(int j) {
    Task t; t.type = 0; t.rb = 0; t.c = 0; t.k0 = 0; t.nch = 16; t.plane = 0;
    auto H = [&](int rb, int i) { t.type = 1; t.rb = rb; t.c = i & 1; t.plane = i >> 1; t.k0 = t.plane * 16; };
    auto CF = [&](int rb, int i) { t.type = 2; t.rb = rb; t.c = i & 1; t.k0 = rb * 64 + (i >> 1) * 16; t.nch = 16; };
    auto H13 = [&](int rb, int i) { t.type = 1; t.rb = rb; t.c = i & 1; t.plane = i >> 1; t.k0 = t.plane * 5; t.nch = (t.plane == 12) ? 4 : 5; };
    auto C13 = [&](int rb, int i) { t.type = 2; t.rb = rb; t.c = i & 1; t.k0 = rb * 64 + (i >> 1) * 8; t.nch = 8; };
    if (j >= NGEMM) { t.type = 3; return t; }
    if (j < 8) { t.c = j & 1; t.plane = j >> 1; t.k0 = t.plane * 16; return t; }
    j -= 8;
    if (j < 144) {
        const int q = j / 12, r = j % 12;
        if (r < 8) { t.rb = 2 * (q + 1); t.c = r & 1; t.plane = r >> 1; t.k0 = t.plane * 16; }
        else { t.type = 2; t.rb = 2 * q + ((r - 8) >> 1); t.c = r & 1; t.k0 = t.rb * 64; t.nch = 64; }
        return t;
    }
    j -= 144;
    if (j < 8) { H(26, j); return t; }
    j -= 8;
    if (j < 8) { H(27, j); return t; }
    j -= 8;
    if (j < 4) { t.type = 2; t.rb = 24 + (j >> 1); t.c = j & 1; t.k0 = t.rb * 64; t.nch = 64; return t; }
    j -= 4;
    if (j < 8) { H(28, j); return t; }
    j -= 8;
    if (j < 8) { CF(26, j); return t; }
    j -= 8;
    if (j < 8) { H(29, j); return t; }
    j -= 8;
    if (j < 8) { CF(27, j); return t; }
    j -= 8;
    if (j < 26) { H13(30, j); return t; }
    j -= 26;
    if (j < 8) { CF(28, j); return t; }
    j -= 8;
    if (j < 8) { CF(29, j); return t; }
    j -= 8;
    if (j < 26) { H13(31, j); return t; }
    j -= 26;
    if (j < 16) { C13(30, j); return t; }
    j -= 16;
    C13(31, j);
    return t;
}
__device__ __forceinline__ void gemm_producer(unsigned char* smem, const CUtensorMap* womap, unsigned epoch, volatile int* s_tasks) {
    const uint32_t sb = smem_u32(smem);
    uint32_t st = 0, ph = 1;
    for (int n = 0;; n++) {
        const int j = (int)(atomicAdd(&g_gemmctr, 1u) - epoch * (unsigned)(NGEMM + NAUX - NATT));
        const Task t = decode_task(j);
        if (t.type <= 1) {
            wait_counter(&g_ocnt[t.rb], (epoch + 1) * 128u);
            if (t.type == 0) wait_counter(&g_ocnt[t.rb + 1], (epoch + 1) * 128u);
            fence_async_all();
        } else if (t.type == 2) {
            wait_counter(&g_gcnt[t.rb][t.c], (epoch + 1) * (t.rb >= NFINE ? 13u : 4u));
            wait_counter(&g_ssmcnt, (epoch + 1) * 80u);
        }
        const int nch = (t.type <= 1) ? t.nch : 1;
        for (int kc = 0; kc < nch; kc++) {
            mbar_wait_sleep(sb + AX_EMPTY + 8 * st, ph);
            const uint32_t a = sb + AX_DATA + st * AX_STAGE, bar = sb + AX_BAR + 16 + 8 * st;
            if (kc == 0) s_tasks[n & 7] = j;
            if (t.type > 1) mbar_arrive(bar);
            else {
                const bf16* asrc = g_Oimg + ((size_t)(t.rb >> 1) * 64 + t.k0 + kc) * 8192 + (t.rb & 1) * 4096;
                if (t.type == 0) { mbar_expect_tx(bar, AX_STAGE); bulk_g2s(a, asrc, 8192, bar); bulk_g2s(a + 8192, asrc + 4096, 8192, bar); }
                else { mbar_expect_tx(bar, AX_STAGE - 8192); bulk_g2s(a, asrc, 8192, bar); }
                #pragma unroll
                for (int b = 0; b < 5; b++) tma_load_2d(a + 16384 + b * 8192, womap, t.c * 320 + b * 64, (t.k0 + kc) * 64, bar);
            }
            if (++st == NST_G) { st = 0; ph ^= 1; }
        }
        if (t.type == 3) break;
    }
}
__device__ __forceinline__ void gemm_signaller(volatile int* s_done) {
    for (int n = 0;; n++) {
        nbar_sync(2, 288);
        const int j = s_done[n & 7];
        if (j < 0) break;
        if ((threadIdx.x & 31) == 0) {
            const Task t = decode_task(j);
            __threadfence();
            atomicAdd(&g_gcnt[t.rb][t.c], 1u);
            if (t.type == 0) atomicAdd(&g_gcnt[t.rb + 1][t.c], 1u);
        }
        __syncwarp();
    }
}
__device__ __forceinline__ void gemm_consumer(unsigned char* smem, bf16* __restrict__ out, volatile int* s_tasks, volatile int* s_done) {
    const uint32_t sb = smem_u32(smem);
    const int tid = threadIdx.x, lane = tid & 31;
    const int wg = __shfl_sync(~0u, tid >> 7, 0), warp = __shfl_sync(~0u, (tid >> 5) & 3, 0);
    uint32_t st = 0, ph = 0;
    int ndone = 0;
    for (int n = 0;; n++) {
        mbar_wait_sleep(sb + AX_BAR + 16 + 8 * st, ph);
        const Task t = decode_task(__shfl_sync(~0u, s_tasks[n & 7], 0));
        if (t.type > 1) {
            nbar_sync(1, 256);
            if ((tid & 127) == 0) mbar_arrive(sb + AX_EMPTY + 8 * st);
            if (++st == NST_G) { st = 0; ph ^= 1; }
            if (t.type == 3) break;
            const int np = (t.rb >= NFINE) ? 13 : 4;
            const float* pbase = (t.rb >= NFINE) ? g_part31 + (size_t)(t.rb - NFINE) * 13 * 64 * DM - (size_t)t.rb * 64 * DM : g_part;
            const size_t pstride = (t.rb >= NFINE) ? (size_t)64 * DM : (size_t)SEQ * DM;
            auto combine = [&](int i, auto NP) {
                const int r = t.k0 + i / 80, cc = t.c * 320 + (i % 80) * 4;
                float4 v[NP.value];
                #pragma unroll
                for (int q = 0; q < NP.value; q++) v[q] = __ldcg(reinterpret_cast<const float4*>(pbase + q * pstride + (size_t)r * DM + cc));
                const float gt = __ldcg(g_g + r);
                const uint2 bb = __ldcg(reinterpret_cast<const uint2*>(g_b + (size_t)r * DM + cc));
                float4 a = v[0];
                #pragma unroll
                for (int q = 1; q < NP.value; q++) { a.x += v[q].x; a.y += v[q].y; a.z += v[q].z; a.w += v[q].w; }
                const float b0 = __uint_as_float(bb.x << 16), b1 = __uint_as_float(bb.x & 0xffff0000u), b2 = __uint_as_float(bb.y << 16), b3 = __uint_as_float(bb.y & 0xffff0000u);
                uint2 o; o.x = pack_bf16(gt * a.x + (1.f - gt) * b0, gt * a.y + (1.f - gt) * b1); o.y = pack_bf16(gt * a.z + (1.f - gt) * b2, gt * a.w + (1.f - gt) * b3);
                *reinterpret_cast<uint2*>(out + (size_t)r * DM + cc) = o;
            };
            if (np == 4) {
                const int nit = t.nch * 80 / 256;
                for (int it0 = 0; it0 < nit; it0 += 5) {
                    #pragma unroll
                    for (int it = 0; it < 5; it++) combine(tid + 256 * (it0 + it), IntC<4>());
                }
            } else {
                #pragma unroll
                for (int it = 0; it < 3; it++) { const int i = tid + 256 * it; if (i < 640) combine(i, IntC<13>()); }
            }
            if (n < 56) ATRID(6 + n, s_tasks[n & 7]);
            continue;
        }
        const int g = lane >> 2, tq = lane & 3;
        if (t.type == 0) {
            float acc[160];
            #pragma unroll
            for (int i = 0; i < 160; i++) acc[i] = 0.f;
            uint32_t prev = 0;
            for (int kc = 0; kc < 16; kc++) {
                mbar_wait(sb + AX_BAR + 16 + 8 * st, ph);
                const uint32_t a = sb + AX_DATA + st * AX_STAGE;
                const uint64_t da = make_desc(a + wg * 8192, 16, 1024), db = make_desc(a + 16384, 8192, 1024);
                wg_fence();
                #pragma unroll
                for (int ks = 0; ks < 4; ks++) {
                    wgmma_n192_tB<0>(acc, da + ks * 2, db + ks * 128);
                    wgmma_n128_tB<96>(acc, da + ks * 2, db + ks * 128 + 3 * 512);
                }
                wg_commit();
                asm volatile("wgmma.wait_group.sync.aligned 1;" ::: "memory");
                if (kc > 0 && (tid & 127) == 0) mbar_arrive(sb + AX_EMPTY + 8 * prev);
                prev = st;
                if (++st == NST_G) { st = 0; ph ^= 1; }
            }
            wg_wait0();
            if ((tid & 127) == 0) mbar_arrive(sb + AX_EMPTY + 8 * prev);
            float* base = g_part + ((size_t)t.plane * SEQ + t.rb * 64 + wg * 64 + warp * 16 + g) * DM + t.c * 320 + 2 * tq;
            #pragma unroll
            for (int q = 0; q < 40; q++) {
                *reinterpret_cast<float2*>(base + q * 8) = make_float2(acc[4 * q], acc[4 * q + 1]);
                *reinterpret_cast<float2*>(base + 8 * DM + q * 8) = make_float2(acc[4 * q + 2], acc[4 * q + 3]);
            }
        } else {
            float* base = (t.rb >= NFINE ? g_part31 + (size_t)((t.rb - NFINE) * 13 + t.plane) * 64 * DM : g_part + ((size_t)t.plane * SEQ + t.rb * 64) * DM) + (size_t)(warp * 16 + g) * DM + t.c * 320 + 2 * tq;
            if (wg == 0) {
                float acc[160];
                #pragma unroll
                for (int i = 0; i < 96; i++) acc[i] = 0.f;
                uint32_t prev = 0;
                for (int kc = 0; kc < t.nch; kc++) {
                    mbar_wait(sb + AX_BAR + 16 + 8 * st, ph);
                    const uint32_t a = sb + AX_DATA + st * AX_STAGE;
                    const uint64_t da = make_desc(a, 16, 1024), db = make_desc(a + 16384, 8192, 1024);
                    wg_fence();
                    #pragma unroll
                    for (int ks = 0; ks < 4; ks++) wgmma_n192_tB<0>(acc, da + ks * 2, db + ks * 128);
                    wg_commit();
                    asm volatile("wgmma.wait_group.sync.aligned 1;" ::: "memory");
                    if (kc > 0 && (tid & 127) == 0) mbar_arrive(sb + AX_EMPTY + 8 * prev);
                    prev = st;
                    if (++st == NST_G) { st = 0; ph ^= 1; }
                }
                wg_wait0();
                if ((tid & 127) == 0) mbar_arrive(sb + AX_EMPTY + 8 * prev);
                #pragma unroll
                for (int q = 0; q < 24; q++) {
                    *reinterpret_cast<float2*>(base + q * 8) = make_float2(acc[4 * q], acc[4 * q + 1]);
                    *reinterpret_cast<float2*>(base + 8 * DM + q * 8) = make_float2(acc[4 * q + 2], acc[4 * q + 3]);
                }
            } else {
                float acc[160];
                #pragma unroll
                for (int i = 96; i < 160; i++) acc[i] = 0.f;
                uint32_t prev = 0;
                for (int kc = 0; kc < t.nch; kc++) {
                    mbar_wait(sb + AX_BAR + 16 + 8 * st, ph);
                    const uint32_t a = sb + AX_DATA + st * AX_STAGE;
                    const uint64_t da = make_desc(a, 16, 1024), db = make_desc(a + 16384, 8192, 1024);
                    wg_fence();
                    #pragma unroll
                    for (int ks = 0; ks < 4; ks++) wgmma_n128_tB<96>(acc, da + ks * 2, db + ks * 128 + 3 * 512);
                    wg_commit();
                    asm volatile("wgmma.wait_group.sync.aligned 1;" ::: "memory");
                    if (kc > 0 && (tid & 127) == 0) mbar_arrive(sb + AX_EMPTY + 8 * prev);
                    prev = st;
                    if (++st == NST_G) { st = 0; ph ^= 1; }
                }
                wg_wait0();
                if ((tid & 127) == 0) mbar_arrive(sb + AX_EMPTY + 8 * prev);
                #pragma unroll
                for (int q = 24; q < 40; q++) {
                    *reinterpret_cast<float2*>(base + q * 8) = make_float2(acc[4 * q], acc[4 * q + 1]);
                    *reinterpret_cast<float2*>(base + 8 * DM + q * 8) = make_float2(acc[4 * q + 2], acc[4 * q + 3]);
                }
            }
        }
        if (tid == 0) s_done[ndone & 7] = s_tasks[n & 7];
        ndone++;
        nbar_arrive(2, 288);
        if (n < 56) ATRID(6 + n, s_tasks[n & 7]);
    }
    if (tid == 0) s_done[ndone & 7] = -1;
    nbar_arrive(2, 288);
}

__global__ void __launch_bounds__(384, 1)
k_aux(const __grid_constant__ CUtensorMap womap, const bf16* __restrict__ x, const bf16* __restrict__ A_re, const bf16* __restrict__ A_im,
      const bf16* __restrict__ B_re, const bf16* __restrict__ B_im, const bf16* __restrict__ C_re, const bf16* __restrict__ C_im,
      const bf16* __restrict__ log_dt, const bf16* __restrict__ Dskip, const bf16* __restrict__ gw, bf16* __restrict__ out) {
    extern __shared__ __align__(1024) unsigned char smem[];
    const uint32_t sb = smem_u32(smem);
    const int tid = threadIdx.x, warp = tid >> 5, lane = tid & 31;
    __shared__ unsigned s_epoch;
    __shared__ int s_task, s_tasks[8], s_done[8];
    if (tid == 0) {
        for (int i = 0; i < 2 + NST_G; i++) mbar_init(sb + AX_BAR + 8 * i, 1);
        for (int i = 0; i < NST_G; i++) mbar_init(sb + AX_EMPTY + 8 * i, blockIdx.x < NATT ? 8 : 2);
        asm volatile("fence.mbarrier_init.release.cluster;" ::: "memory");
        s_epoch = *reinterpret_cast<volatile unsigned*>(&g_epoch);
    }
    __syncthreads();
    const unsigned epoch = s_epoch;
    ATR(0);
    const int wg = __shfl_sync(~0u, tid >> 7, 0);
    if (wg == 2) {
        asm volatile("setmaxnreg.dec.sync.aligned.u32 40;");
        if (blockIdx.x < NATT) { if (warp == 8) attn_producer(smem, blockIdx.x, epoch); else if (warp == 9) attn_storer(smem, blockIdx.x); }
        else {
            nbar_sync(3, 384);
            if (warp == 8) { if (lane == 0) gemm_producer(smem, &womap, epoch, s_tasks); }
            else if (warp == 9) gemm_signaller(s_done);
        }
        __syncwarp();
        nbar_sync(4, 384);
    } else {
        asm volatile("setmaxnreg.inc.sync.aligned.u32 232;");
        if (blockIdx.x < NATT) attn_loop(smem, blockIdx.x, epoch);
        else {
            int ntask = 0;
            for (;;) {
                nbar_sync(1, 256);
                if (tid == 0) s_task = (int)(atomicAdd(&g_taskctr, 1u) - epoch * (unsigned)(80 + NAUX - NATT));
                nbar_sync(1, 256);
                const int task = s_task;
                if (task >= 80) break;
                for (int r = task * 26 + warp; r < min(SEQ, task * 26 + 26); r += 8) {
                    float sum = 0.f;
                    for (int i = lane * 2; i < DM; i += 64) {
                        __nv_bfloat162 xv = *reinterpret_cast<const __nv_bfloat162*>(x + (size_t)r * DM + i), wv = *reinterpret_cast<const __nv_bfloat162*>(gw + i);
                        sum += bf2f(xv.x) * bf2f(wv.x) + bf2f(xv.y) * bf2f(wv.y);
                    }
                    #pragma unroll
                    for (int o = 16; o; o >>= 1) sum += __shfl_xor_sync(~0u, sum, o);
                    if (lane == 0) g_g[r] = 1.f / (1.f + expf(-sum));
                }
                ssm_group(smem + AX_DATA, task, x, A_re, A_im, B_re, B_im, C_re, C_im, log_dt, Dskip);
                nbar_sync(1, 256);
                if (tid == 0) { __threadfence(); atomicAdd(&g_ssmcnt, 1u); }
                if (ntask < 4) ATR(2 + ntask);
                ntask++;
            }
            fence_async();
            nbar_sync(3, 384);
            gemm_consumer(smem, out, s_tasks, s_done);
        }
        nbar_sync(4, 384);
        if (tid == 0) {
            __threadfence();
            unsigned old = atomicAdd(&g_auxdone, 1u);
            if (old == NAUX - 1) { g_auxdone = 0; __threadfence(); atomicAdd(&g_epoch, 1u); }
        }
    }
    asm volatile("griddepcontrol.wait;" ::: "memory");
}

extern "C" void kernel_launch(void* const* d_in, const int* in_sizes, int n_in, void* d_out, int out_size) {
    const bf16* x = (const bf16*)d_in[0];
    const bf16* mem0 = (const bf16*)d_in[1];
    const bf16* Wq = (const bf16*)d_in[2];
    const bf16* Wk = (const bf16*)d_in[3];
    const bf16* Wv = (const bf16*)d_in[4];
    const bf16* Wo = (const bf16*)d_in[5];
    const bf16 *A_re = (const bf16*)d_in[8], *A_im = (const bf16*)d_in[9], *B_re = (const bf16*)d_in[10], *B_im = (const bf16*)d_in[11];
    const bf16 *C_re = (const bf16*)d_in[12], *C_im = (const bf16*)d_in[13], *log_dt = (const bf16*)d_in[14], *Dskip = (const bf16*)d_in[15];
    const bf16* gw = (const bf16*)d_in[16];
    bf16* out = (bf16*)d_out;
    cudaStream_t st = cudaStreamPerThread;
    static bool init = false;
    static CUtensorMap xmap, womap;
    static const void* xmap_ptr = nullptr; static const void* womap_ptr = nullptr;
    if (!init) {
        cudaFuncSetAttribute(k_chain, cudaFuncAttributeMaxDynamicSharedMemorySize, SM_TOTAL);
        cudaFuncSetAttribute(k_aux, cudaFuncAttributeMaxDynamicSharedMemorySize, AX_TOTAL);
        init = true;
    }
    if (xmap_ptr != (const void*)x || womap_ptr != (const void*)Wo) {
        void* fn = nullptr; cudaDriverEntryPointQueryResult qres;
        cudaGetDriverEntryPoint("cuTensorMapEncodeTiled", &fn, cudaEnableDefault, &qres);
        typedef CUresult (*EncFn)(CUtensorMap*, CUtensorMapDataType, cuuint32_t, void*, const cuuint64_t*, const cuuint64_t*, const cuuint32_t*, const cuuint32_t*,
                                  CUtensorMapInterleave, CUtensorMapSwizzle, CUtensorMapL2promotion, CUtensorMapFloatOOBfill);
        cuuint32_t es[2] = {1, 1};
        {
          cuuint64_t dims[3] = {64, SEQ, 10}; cuuint64_t strides[2] = {DM * 2, 128}; cuuint32_t box[3] = {64, 32, 10}; cuuint32_t es3[3] = {1, 1, 1};
          ((EncFn)fn)(&xmap, CU_TENSOR_MAP_DATA_TYPE_BFLOAT16, 3, (void*)x, dims, strides, box, es3, CU_TENSOR_MAP_INTERLEAVE_NONE, CU_TENSOR_MAP_SWIZZLE_128B,
                      CU_TENSOR_MAP_L2_PROMOTION_L2_128B, CU_TENSOR_MAP_FLOAT_OOB_FILL_NONE); }
        { cuuint64_t dims[2] = {DM, HD}; cuuint64_t strides[1] = {DM * 2}; cuuint32_t box[2] = {64, 64};
          ((EncFn)fn)(&womap, CU_TENSOR_MAP_DATA_TYPE_BFLOAT16, 2, (void*)Wo, dims, strides, box, es, CU_TENSOR_MAP_INTERLEAVE_NONE, CU_TENSOR_MAP_SWIZZLE_128B,
                      CU_TENSOR_MAP_L2_PROMOTION_L2_128B, CU_TENSOR_MAP_FLOAT_OOB_FILL_NONE); }
        xmap_ptr = (const void*)x; womap_ptr = (const void*)Wo;
    }
    k_chain<<<96, 384, SM_TOTAL, st>>>(xmap, x, mem0, Wq, Wk, Wv, Wo);
    {
        cudaLaunchConfig_t cfg = {};
        cfg.gridDim = dim3(NAUX); cfg.blockDim = dim3(384); cfg.dynamicSmemBytes = AX_TOTAL; cfg.stream = st;
        cudaLaunchAttribute at[1];
        at[0].id = cudaLaunchAttributeProgrammaticStreamSerialization; at[0].val.programmaticStreamSerializationAllowed = 1;
        cfg.attrs = at; cfg.numAttrs = 1;
        cudaLaunchKernelEx(&cfg, k_aux, womap, x, A_re, A_im, B_re, B_im, C_re, C_im, log_dt, Dskip, gw, out);
    }
}
```

```cpp
#include <cuda_runtime.h>
#include <cuda_bf16.h>
#include <stdint.h>
#include <cuda.h>

typedef __nv_bfloat16 bf16;

#define SEQ 2048
#define DM 640
#define NH 32
#define DH 128
#define NM 8
#define SEG 32
#define NSEG 64
#define NST 128
#define HD 4096

__device__ bf16  g_b[SEQ * DM];
__device__ float g_g[SEQ];

__device__ __forceinline__ float bf2f(bf16 v) { return __bfloat162float(v); }
__device__ __forceinline__ uint32_t pack_bf16(float lo, float hi) {
    uint32_t r; asm("cvt.rn.bf16x2.f32 %0, %1, %2;" : "=r"(r) : "f"(hi), "f"(lo)); return r;
}
__device__ __forceinline__ uint32_t f2tf32(float x) { uint32_t r; asm("cvt.rna.tf32.f32 %0, %1;" : "=r"(r) : "f"(x)); return r; }
__device__ __forceinline__ void mma_tf32(float (&d)[4], uint32_t a0, uint32_t a1, uint32_t a2, uint32_t a3, uint32_t b0, uint32_t b1) {
    asm volatile("mma.sync.aligned.m16n8k8.row.col.f32.tf32.tf32.f32 {%0,%1,%2,%3}, {%4,%5,%6,%7}, {%8,%9}, {%0,%1,%2,%3};\n"
        : "+f"(d[0]), "+f"(d[1]), "+f"(d[2]), "+f"(d[3]) : "r"(a0), "r"(a1), "r"(a2), "r"(a3), "r"(b0), "r"(b1));
}
__device__ __forceinline__ void mma_bf16(float (&d)[4], uint32_t a0, uint32_t a1, uint32_t a2, uint32_t a3, uint32_t b0, uint32_t b1) {
    asm volatile("mma.sync.aligned.m16n8k16.row.col.f32.bf16.bf16.f32 {%0,%1,%2,%3}, {%4,%5,%6,%7}, {%8,%9}, {%0,%1,%2,%3};\n"
        : "+f"(d[0]), "+f"(d[1]), "+f"(d[2]), "+f"(d[3]) : "r"(a0), "r"(a1), "r"(a2), "r"(a3), "r"(b0), "r"(b1));
}
struct cf { float re, im; };
__device__ __forceinline__ cf cmul(cf a, cf b) { cf r; r.re = a.re * b.re - a.im * b.im; r.im = a.re * b.im + a.im * b.re; return r; }
__device__ __forceinline__ cf csq(cf a) { cf r; r.re = a.re * a.re - a.im * a.im; r.im = 2.f * a.re * a.im; return r; }
__device__ __forceinline__ cf cexpL(float zr, float zi, float L) {
    float e = __expf(zr * L);
    float ang = zi * L;
    float k = rintf(ang * 0.15915494309189535f);
    ang = fmaf(-k, 6.2831854820251465f, ang);
    ang = fmaf(-k, -1.7484555314695172e-07f, ang);
    cf r; r.re = e * __cosf(ang); r.im = e * __sinf(ang); return r;
}

#define SSM_CH 8
#define KC_PITCH 648
#define XS_PITCH (2048 + 8)
#define KT_LEN (2048 + 48)
#define PART_PITCH 20
struct SsmSmem {
    float Kc[SSM_CH][KC_PITCH];
    bf16  xs[SSM_CH][XS_PITCH];
    bf16  KT[2][KT_LEN];
    union {
        float part[8][128 * PART_PITCH];
        float st[SSM_CH][NST][8];
    } u;
    bf16  ys[SSM_CH][XS_PITCH];
    uint16_t kidx[2048];
};

__device__ __forceinline__ int kc_index(int l) {
    return l < 256 ? l : (l < 512 ? 256 + ((l - 256) >> 1) : (l < 1024 ? 384 + ((l - 512) >> 2) : 512 + ((l - 1024) >> 3)));
}

__device__ __forceinline__ void ssm_group(unsigned char* smem_raw, int grp, const bf16* __restrict__ x, const bf16* __restrict__ A_re, const bf16* __restrict__ A_im,
        const bf16* __restrict__ B_re, const bf16* __restrict__ B_im, const bf16* __restrict__ C_re, const bf16* __restrict__ C_im,
        const bf16* __restrict__ log_dt, const bf16* __restrict__ Dskip) {
    SsmSmem& S = *reinterpret_cast<SsmSmem*>(smem_raw);
    const int tid = threadIdx.x, w = tid >> 5, lane = tid & 31, g = lane >> 2, t = lane & 3;
    const int d0 = grp * SSM_CH;
    asm volatile("bar.sync 1, 256;" ::: "memory");
    #pragma unroll
    for (int it = 0; it < 8; it++) {
        const int l = tid + 256 * it;
        uint4 v = *reinterpret_cast<const uint4*>(x + (size_t)l * DM + d0);
        const bf16* p = reinterpret_cast<const bf16*>(&v);
        const int lr = (l & ~15) | (15 - (l & 15));
        #pragma unroll
        for (int c = 0; c < 8; c++) S.xs[c][lr] = p[c];
        S.kidx[l] = (uint16_t)((int)bf2f(__float2bfloat16_rn((float)l)) == 2048 ? 640 : kc_index((int)bf2f(__float2bfloat16_rn((float)l))));
    }
    if (tid < 48) { const int i = tid < 16 ? tid : 2048 + tid; S.KT[0][i] = __float2bfloat16_rn(0.f); if (i > 0) S.KT[1][i - 1] = __float2bfloat16_rn(0.f); }
    if (tid == 48) S.KT[1][KT_LEN - 1] = __float2bfloat16_rn(0.f);
    {
        const int d = d0 + w;
        const float dt = bf2f(__float2bfloat16_rn(expf(bf2f(log_dt[d]))));
        #pragma unroll
        for (int i = 0; i < 4; i++) {
            const int n = lane + 32 * i;
            float zr = dt * bf2f(A_re[d * NST + n]), zi = dt * bf2f(A_im[d * NST + n]);
            cf dB; dB.re = dt * bf2f(B_re[d * NST + n]); dB.im = dt * bf2f(B_im[d * NST + n]);
            cf C; C.re = bf2f(C_re[d * NST + n]); C.im = bf2f(C_im[d * NST + n]);
            cf wv = cmul(C, dB);
            cf u8 = cexpL(zr, zi, 8.f), u128 = cexpL(zr, zi, 128.f);
            float* st = S.u.st[w][n];
            *reinterpret_cast<float4*>(st) = make_float4(zr, zi, wv.re, wv.im);
            *reinterpret_cast<float4*>(st + 4) = make_float4(u8.re, u8.im, u128.re, u128.im);
        }
        __syncwarp();
        float a0a[4] = {0, 0, 0, 0}, a0b[4] = {0, 0, 0, 0}, a1[4] = {0, 0, 0, 0}, a2a[4] = {0, 0, 0, 0}, a2b[4] = {0, 0, 0, 0};
        float k2048 = 0.f;
        const float Lg = (g < 4) ? (512.f + 4.f * g) : (g < 6 ? 1024.f + 8.f * (g - 4) : 1536.f + 8.f * (g - 6));
        #pragma unroll 4
        for (int kk = 0; kk < 32; kk++) {
            const float* st = S.u.st[w][4 * kk + t];
            float4 s0 = *reinterpret_cast<const float4*>(st), s1 = *reinterpret_cast<const float4*>(st + 4);
            cf wv; wv.re = s0.z; wv.im = s0.w;
            cf u8; u8.re = s1.x; u8.im = s1.y;
            cf u128; u128.re = s1.z; u128.im = s1.w;
            cf e1 = cexpL(s0.x, s0.y, (float)g);
            cf e23 = cexpL(s0.x, s0.y, Lg);
            cf e1b = cmul(e1, u8);
            cf e2 = csq(e1);
            cf p = csq(csq(csq(e2)));
            cf f0 = cmul(wv, p), f1 = cmul(f0, u128), f2 = cmul(f1, u128), f3 = cmul(f2, u128);
            uint32_t A00 = f2tf32(f0.re), A01 = f2tf32(f1.re), A02 = f2tf32(-f0.im), A03 = f2tf32(-f1.im);
            uint32_t A10 = f2tf32(f2.re), A11 = f2tf32(f3.re), A12 = f2tf32(-f2.im), A13 = f2tf32(-f3.im);
            mma_tf32(a0a, A00, A01, A02, A03, f2tf32(e1.re), f2tf32(e1.im));
            mma_tf32(a0b, A00, A01, A02, A03, f2tf32(e1b.re), f2tf32(e1b.im));
            mma_tf32(a1, A10, A11, A12, A13, f2tf32(e2.re), f2tf32(e2.im));
            uint32_t E0 = f2tf32(e23.re), E1 = f2tf32(e23.im);
            mma_tf32(a2a, A00, A01, A02, A03, E0, E1);
            mma_tf32(a2b, A10, A11, A12, A13, E0, E1);
            cf e2048 = csq(e23);
            k2048 += wv.re * e2048.re - wv.im * e2048.im;
        }
        k2048 += __shfl_xor_sync(~0u, k2048, 1);
        k2048 += __shfl_xor_sync(~0u, k2048, 2);
        float* Kc = S.Kc[w];
        Kc[16 * g + 2 * t] = a0a[0]; Kc[16 * g + 2 * t + 1] = a0a[1]; Kc[16 * (g + 8) + 2 * t] = a0a[2]; Kc[16 * (g + 8) + 2 * t + 1] = a0a[3];
        Kc[16 * g + 8 + 2 * t] = a0b[0]; Kc[16 * g + 8 + 2 * t + 1] = a0b[1]; Kc[16 * (g + 8) + 8 + 2 * t] = a0b[2]; Kc[16 * (g + 8) + 8 + 2 * t + 1] = a0b[3];
        Kc[256 + 8 * g + 2 * t] = a1[0]; Kc[256 + 8 * g + 2 * t + 1] = a1[1]; Kc[256 + 8 * (g + 8) + 2 * t] = a1[2]; Kc[256 + 8 * (g + 8) + 2 * t + 1] = a1[3];
        #pragma unroll
        for (int mt = 0; mt < 2; mt++) {
            #pragma unroll
            for (int e = 0; e < 4; e++) {
                int A = mt * 16 + g + (e >> 1) * 8, j = 2 * t + (e & 1);
                int Lj = (j < 4) ? 512 + 4 * j : (j < 6 ? 1024 + 8 * (j - 4) : 1536 + 8 * (j - 6));
                Kc[kc_index(Lj + 16 * A)] = mt ? a2b[e] : a2a[e];
            }
        }
        if (lane == 16) Kc[640] = k2048;
    }
    for (int c = 0; c < SSM_CH; c++) {
        asm volatile("bar.sync 1, 256;" ::: "memory");
        #pragma unroll
        for (int it = 0; it < 8; it++) {
            const int j = tid + 256 * it;
            const bf16 v = __float2bfloat16_rn(S.Kc[c][S.kidx[j]]);
            S.KT[0][16 + j] = v;
            S.KT[1][15 + j] = v;
        }
        uint32_t B[16][2];
        #pragma unroll
        for (int v = 0; v < 16; v++) {
            const bf16* p = &S.xs[c][16 * (8 * v + g) + 2 * t];
            B[v][0] = *reinterpret_cast<const uint32_t*>(p);
            B[v][1] = *reinterpret_cast<const uint32_t*>(p + 8);
        }
        asm volatile("bar.sync 1, 256;" ::: "memory");
        float acc[16][4];
        #pragma unroll
        for (int v = 0; v < 16; v++) { acc[v][0] = acc[v][1] = acc[v][2] = acc[v][3] = 0.f; }
        const bf16* kt = (g & 1) ? &S.KT[0][0] : &S.KT[1][0];
        const int ibase = 16 * w + g + 1 + 2 * t - ((g & 1) ? 0 : 1);
        #pragma unroll
        for (int q = 0; q < 16; q++) {
            const int i0 = ibase + 128 * q;
            uint32_t A0 = *reinterpret_cast<const uint32_t*>(kt + i0);
            uint32_t A1 = *reinterpret_cast<const uint32_t*>(kt + i0 + 8);
            uint32_t A3 = *reinterpret_cast<const uint32_t*>(kt + i0 + 16);
            #pragma unroll
            for (int v = q; v < 16; v++) mma_bf16(acc[v], A0, A1, A1, A3, B[v - q][0], B[v - q][1]);
        }
        float* part = S.u.part[w];
        #pragma unroll
        for (int v = 0; v < 16; v++) {
            int a = 8 * v + 2 * t + w;
            if (v < 15 || a < 128) { part[a * PART_PITCH + g] = acc[v][0]; part[a * PART_PITCH + g + 8] = acc[v][2]; }
            if (v < 15 || a + 1 < 128) { part[(a + 1) * PART_PITCH + g] = acc[v][1]; part[(a + 1) * PART_PITCH + g + 8] = acc[v][3]; }
        }
        asm volatile("bar.sync 1, 256;" ::: "memory");
        const float dsk = bf2f(Dskip[d0 + c]);
        #pragma unroll
        for (int it = 0; it < 2; it++) {
            const int l = (tid + 256 * it) * 4, a = l >> 4, b = l & 15;
            float4 sum = make_float4(0.f, 0.f, 0.f, 0.f);
            #pragma unroll
            for (int r = 0; r < 8; r++)
                if (a >= r) { float4 v = *reinterpret_cast<const float4*>(&S.u.part[r][a * PART_PITCH + b]); sum.x += v.x; sum.y += v.y; sum.z += v.z; sum.w += v.w; }
            const uint2 xr = *reinterpret_cast<const uint2*>(&S.xs[c][(l & ~15) + 12 - b]);
            const float x3 = __uint_as_float(xr.x << 16), x2 = __uint_as_float(xr.x & 0xffff0000u), x1 = __uint_as_float(xr.y << 16), x0 = __uint_as_float(xr.y & 0xffff0000u);
            auto fin = [&](float y, float xv) { return bf2f(__float2bfloat16_rn(y)) + bf2f(__float2bfloat16_rn(xv * dsk)); };
            uint2 o; o.x = pack_bf16(fin(sum.x, x0), fin(sum.y, x1)); o.y = pack_bf16(fin(sum.z, x2), fin(sum.w, x3));
            *reinterpret_cast<uint2*>(&S.ys[c][l]) = o;
        }
    }
    asm volatile("bar.sync 1, 256;" ::: "memory");
    #pragma unroll
    for (int it = 0; it < 8; it++) {
        const int l = tid + 256 * it;
        uint32_t wv[4];
        #pragma unroll
        for (int c = 0; c < 4; c++)
            wv[c] = (uint32_t)*reinterpret_cast<const uint16_t*>(&S.ys[2 * c][l]) | ((uint32_t)*reinterpret_cast<const uint16_t*>(&S.ys[2 * c + 1][l]) << 16);
        *reinterpret_cast<uint4*>(g_b + (size_t)l * DM + d0) = make_uint4(wv[0], wv[1], wv[2], wv[3]);
    }
}

__device__ __forceinline__ uint32_t smem_u32(const void* p) { return (uint32_t)__cvta_generic_to_shared(p); }
__device__ __forceinline__ void mbar_init(uint32_t bar, uint32_t cnt) { asm volatile("mbarrier.init.shared::cta.b64 [%0], %1;" :: "r"(bar), "r"(cnt) : "memory"); }
__device__ __forceinline__ void mbar_expect_tx(uint32_t bar, uint32_t bytes) { asm volatile("mbarrier.arrive.expect_tx.shared::cta.b64 _, [%0], %1;" :: "r"(bar), "r"(bytes) : "memory"); }
__device__ __forceinline__ void mbar_arrive(uint32_t bar) { asm volatile("mbarrier.arrive.shared::cta.b64 _, [%0];" :: "r"(bar) : "memory"); }
__device__ __forceinline__ void mbar_wait(uint32_t bar, uint32_t parity) {
    uint32_t ok; int guard = 0;
    do {
        asm volatile("{\n.reg .pred P1;\nmbarrier.test_wait.parity.shared::cta.b64 P1, [%1], %2;\nselp.u32 %0,1,0,P1;\n}" : "=r"(ok) : "r"(bar), "r"(parity) : "memory");
    } while (!ok && ++guard < (1 << 26));
}
__device__ __forceinline__ void mbar_wait_sleep(uint32_t bar, uint32_t parity) {
    uint32_t ok; int guard = 0;
    do {
        asm volatile("{\n.reg .pred P1;\nmbarrier.try_wait.parity.shared::cta.b64 P1, [%1], %2;\nselp.u32 %0,1,0,P1;\n}" : "=r"(ok) : "r"(bar), "r"(parity) : "memory");
    } while (!ok && ++guard < (1 << 22));
}
__device__ __forceinline__ uint32_t mapa(uint32_t addr, uint32_t rank) { uint32_t r; asm volatile("mapa.shared::cluster.u32 %0, %1, %2;" : "=r"(r) : "r"(addr), "r"(rank)); return r; }
__device__ __forceinline__ void st_async4(uint32_t addr, float a, float b, float c, float d, uint32_t bar) {
    asm volatile("st.async.weak.shared::cluster.mbarrier::complete_tx::bytes.v4.f32 [%0], {%1,%2,%3,%4}, [%5];" :: "r"(addr), "f"(a), "f"(b), "f"(c), "f"(d), "r"(bar) : "memory");
}
__device__ __forceinline__ void bulk_s2c(uint32_t dst, uint32_t src, uint32_t bytes, uint32_t bar) {
    asm volatile("cp.async.bulk.shared::cluster.shared::cta.mbarrier::complete_tx::bytes [%0], [%1], %2, [%3];" :: "r"(dst), "r"(src), "r"(bytes), "r"(bar) : "memory");
}
__device__ __forceinline__ void bulk_g2s(uint32_t dst, const void* src, uint32_t bytes, uint32_t bar) {
    asm volatile("cp.async.bulk.shared::cluster.global.mbarrier::complete_tx::bytes [%0], [%1], %2, [%3];" :: "r"(dst), "l"(src), "r"(bytes), "r"(bar) : "memory");
}
__device__ __forceinline__ void bulk_s2g(void* dst, uint32_t src, uint32_t bytes) {
    asm volatile("cp.async.bulk.global.shared::cta.bulk_group [%0], [%1], %2;" :: "l"(dst), "r"(src), "r"(bytes) : "memory");
}
__device__ __forceinline__ void bulk_commit() { asm volatile("cp.async.bulk.commit_group;" ::: "memory"); }
__device__ __forceinline__ void bulk_wait_read0() { asm volatile("cp.async.bulk.wait_group.read 0;" ::: "memory"); }
__device__ __forceinline__ void bulk_wait0() { asm volatile("cp.async.bulk.wait_group 0;" ::: "memory"); }
__device__ __forceinline__ void fence_async() { asm volatile("fence.proxy.async.shared::cta;" ::: "memory"); }
__device__ __forceinline__ void nbar_sync(int id, int n) { asm volatile("bar.sync %0, %1;" :: "r"(id), "r"(n) : "memory"); }
__device__ __forceinline__ void nbar_arrive(int id, int n) { asm volatile("bar.arrive %0, %1;" :: "r"(id), "r"(n) : "memory"); }
__device__ __forceinline__ void cp_async16(uint32_t dst, const void* src) { asm volatile("cp.async.cg.shared.global [%0], [%1], 16;" :: "r"(dst), "l"(src) : "memory"); }
__device__ __forceinline__ void cp_async_wait_all() { asm volatile("cp.async.wait_all;" ::: "memory"); }
__device__ __forceinline__ void ldsm4(uint32_t (&r)[4], uint32_t addr) {
    asm volatile("ldmatrix.sync.aligned.m8n8.x4.shared.b16 {%0,%1,%2,%3}, [%4];" : "=r"(r[0]), "=r"(r[1]), "=r"(r[2]), "=r"(r[3]) : "r"(addr) : "memory");
}
__device__ __forceinline__ void ldsm4t(uint32_t (&r)[4], uint32_t addr) {
    asm volatile("ldmatrix.sync.aligned.m8n8.x4.trans.shared.b16 {%0,%1,%2,%3}, [%4];" : "=r"(r[0]), "=r"(r[1]), "=r"(r[2]), "=r"(r[3]) : "r"(addr) : "memory");
}
__device__ __forceinline__ void stsm2t(uint32_t addr, uint32_t r0, uint32_t r1) {
    asm volatile("stmatrix.sync.aligned.m8n8.x2.trans.shared.b16 [%0], {%1,%2};" :: "r"(addr), "r"(r0), "r"(r1) : "memory");
}
__device__ __forceinline__ uint4 ld_relaxed4(const void* p) { uint4 v; asm volatile("ld.relaxed.gpu.global.v4.u32 {%0,%1,%2,%3}, [%4];" : "=r"(v.x), "=r"(v.y), "=r"(v.z), "=r"(v.w) : "l"(p) : "memory"); return v; }
__device__ __forceinline__ void st_relaxed2(void* p, uint32_t a, uint32_t b) { asm volatile("st.relaxed.gpu.global.v2.u32 [%0], {%1,%2};" :: "l"(p), "r"(a), "r"(b) : "memory"); }
__device__ __forceinline__ void st_relaxed1(void* p, uint32_t a) { asm volatile("st.relaxed.gpu.global.u32 [%0], %1;" :: "l"(p), "r"(a) : "memory"); }
__device__ __forceinline__ unsigned ld_acquire(const unsigned* p) { unsigned v; asm volatile("ld.acquire.gpu.global.u32 %0, [%1];" : "=r"(v) : "l"(p) : "memory"); return v; }
__device__ __forceinline__ float ex2_approx(float x) { float r; asm("ex2.approx.ftz.f32 %0, %1;" : "=f"(r) : "f"(x)); return r; }
__device__ __forceinline__ uint64_t make_desc(uint32_t saddr, uint32_t lbo, uint32_t sbo) {
    return (uint64_t)((saddr & 0x3FFFF) >> 4) | ((uint64_t)((lbo & 0x3FFFF) >> 4) << 16) | ((uint64_t)((sbo & 0x3FFFF) >> 4) << 32) | (1ull << 62);
}
__device__ __forceinline__ void wg_fence() { asm volatile("wgmma.fence.sync.aligned;" ::: "memory"); }
__device__ __forceinline__ void wg_commit() { asm volatile("wgmma.commit_group.sync.aligned;" ::: "memory"); }
__device__ __forceinline__ void wg_wait0() { asm volatile("wgmma.wait_group.sync.aligned 0;" ::: "memory"); }
__device__ __forceinline__ void wgmma_n40_tA(float (&d)[20], uint64_t da, uint64_t db, int scale_d) {
    asm volatile("{\n.reg .pred p;\nsetp.ne.b32 p, %22, 0;\n"
        "wgmma.mma_async.sync.aligned.m64n40k16.f32.bf16.bf16 {%0,%1,%2,%3,%4,%5,%6,%7,%8,%9,%10,%11,%12,%13,%14,%15,%16,%17,%18,%19}, %20, %21, p, 1, 1, 1, 0;\n}\n"
        : "+f"(d[0]), "+f"(d[1]), "+f"(d[2]), "+f"(d[3]), "+f"(d[4]), "+f"(d[5]), "+f"(d[6]), "+f"(d[7]), "+f"(d[8]), "+f"(d[9]),
          "+f"(d[10]), "+f"(d[11]), "+f"(d[12]), "+f"(d[13]), "+f"(d[14]), "+f"(d[15]), "+f"(d[16]), "+f"(d[17]), "+f"(d[18]), "+f"(d[19])
        : "l"(da), "l"(db), "r"(scale_d));
}

#define NREP 8
#define NRED 80
#define CAL_THR 410u
#define COMM_REGS "40"
#define NPOOL 576
#define RPS 1
__device__ __align__(4096) uint32_t g_pool[(NPOOL + 1) * 1024];
__device__ unsigned g_cls[NPOOL];
__device__ unsigned g_side[96];
__device__ unsigned g_calcnt;
__device__ unsigned g_epoch;
__device__ unsigned g_flag[NSEG][NH];
__device__ __align__(1024) bf16 g_Qimg[NSEG * NH * 2 * 32 * 64];
__device__ __align__(1024) bf16 g_Kimg[NSEG * NH * 2 * 40 * 64];
__device__ __align__(1024) bf16 g_Vimg[NSEG * NH * 2 * 40 * 64];

#define SM_XB    0
#define SM_VT    81920
#define SM_KT    (SM_VT + 20480)
#define SM_QT    (SM_KT + 10240)
#define SM_QS    (SM_QT + 4096)
#define SM_MEMB  (SM_QS + 1024)
#define SM_RED   (SM_MEMB + 10240)
#define SM_SC    (SM_RED + 16384)
#define SM_CRED  (SM_SC + 5120)
#define SM_PB    (SM_CRED + 1024)
#define SM_TRACE (SM_PB + 1024)
#define SM_WO    163840
#define SM_BAR   (SM_WO + 65536)
#define SM_TPM   (SM_BAR + 256)
#define SM_TRD   (SM_TPM + 256)
#define SM_TPUB  (SM_TRD + 16)
#define SM_TGAT  (SM_TPUB + 128)
#define SM_CAL   (SM_TGAT + 64)
#define SM_TOTAL (SM_CAL + 128)
#define B_SC   (SM_BAR + 0)
#define B_V    (SM_BAR + 16)
#define B_MEM  (SM_BAR + 32)
#define B_P    (SM_BAR + 48)
#define B_X    (SM_BAR + 56)
#define B_EXP  (SM_BAR + 72)

#define TR(ev) do {} while (0)
__device__ __forceinline__ uint32_t tag_of(int s) { return (uint32_t)(((s >> 1) & 1) + 1); }
__device__ __forceinline__ unsigned probe_latency(uint32_t* p, uint32_t zero) {
    uint32_t v, best = 0xffffffffu;
    asm volatile("atom.relaxed.gpu.global.add.u32 %0, [%1], 0;" : "=r"(v) : "l"(p) : "memory");
    #pragma unroll 1
    for (int r = 0; r < 4; r++) {
        uint32_t c0, c1;
        asm volatile("mov.u32 %0, %%clock;" : "=r"(c0) : "r"(v) : "memory");
        asm volatile("atom.relaxed.gpu.global.add.u32 %0, [%1], 0;" : "=r"(v) : "l"(p + ((v + c0) & zero)) : "memory");
        asm volatile("{\n.reg .u32 t;\nand.b32 t, %1, %2;\nmov.u32 %0, %%clock;\nadd.u32 %0, %0, t;\n}" : "=r"(c1) : "r"(v), "r"(zero) : "memory");
        best = min(best, c1 - c0);
    }
    return best;
}
__device__ __forceinline__ void cluster_sync_all() { asm volatile("barrier.cluster.arrive.release.aligned;\nbarrier.cluster.wait.acquire.aligned;" ::: "memory"); }
__device__ __forceinline__ void tma_load_2d(uint32_t dst, const void* map, int c0, int c1, uint32_t bar) {
    asm volatile("cp.async.bulk.tensor.2d.shared::cluster.global.mbarrier::complete_tx::bytes [%0], [%1, {%3, %4}], [%2];"
        :: "r"(dst), "l"(map), "r"(bar), "r"(c0), "r"(c1) : "memory");
}
__device__ __forceinline__ void tma_load_3d(uint32_t dst, const void* map, int c0, int c1, int c2, uint32_t bar) {
    asm volatile("cp.async.bulk.tensor.3d.shared::cluster.global.mbarrier::complete_tx::bytes [%0], [%1, {%3, %4, %5}], [%2];"
        :: "r"(dst), "l"(map), "r"(bar), "r"(c0), "r"(c1), "r"(c2) : "memory");
}
__device__ __forceinline__ void stsm4t(uint32_t addr, uint32_t r0, uint32_t r1, uint32_t r2, uint32_t r3) {
    asm volatile("stmatrix.sync.aligned.m8n8.x4.trans.shared.b16 [%0], {%1,%2,%3,%4};" :: "r"(addr), "r"(r0), "r"(r1), "r"(r2), "r"(r3) : "memory");
}
__device__ __forceinline__ void wgmma_n32_rs(float (&d)[16], const uint32_t (&a)[4], uint64_t db, int scale_d) {
    asm volatile("{\n.reg .pred p;\nsetp.ne.b32 p, %21, 0;\n"
        "wgmma.mma_async.sync.aligned.m64n32k16.f32.bf16.bf16 {%0,%1,%2,%3,%4,%5,%6,%7,%8,%9,%10,%11,%12,%13,%14,%15}, {%16,%17,%18,%19}, %20, p, 1, 1, 0;\n}\n"
        : "+f"(d[0]), "+f"(d[1]), "+f"(d[2]), "+f"(d[3]), "+f"(d[4]), "+f"(d[5]), "+f"(d[6]), "+f"(d[7]),
          "+f"(d[8]), "+f"(d[9]), "+f"(d[10]), "+f"(d[11]), "+f"(d[12]), "+f"(d[13]), "+f"(d[14]), "+f"(d[15])
        : "r"(a[0]), "r"(a[1]), "r"(a[2]), "r"(a[3]), "l"(db), "r"(scale_d));
}

__device__ __forceinline__ void st_async4u(uint32_t addr, uint4 v, uint32_t bar) {
    asm volatile("st.async.weak.shared::cluster.mbarrier::complete_tx::bytes.v4.u32 [%0], {%1,%2,%3,%4}, [%5];" :: "r"(addr), "r"(v.x), "r"(v.y), "r"(v.z), "r"(v.w), "r"(bar) : "memory");
}
__device__ __forceinline__ void export_issue(uint32_t sb, int s, int h, uint32_t rank) {
    const size_t img = (size_t)(s * NH + h) * 2;
    const int sl = s & 1;
    if (rank == 2) {
        bulk_s2g(g_Vimg + img * 2560, sb + SM_VT + sl * 10240, 5120);
        bulk_s2g(g_Vimg + (img + 1) * 2560, sb + SM_VT + sl * 10240 + 5120, 5120);
    } else {
        bulk_s2g(g_Qimg + (img + rank) * 2048, sb + SM_QT, 4096);
        bulk_s2g(g_Kimg + (img + rank) * 2560, sb + SM_KT + sl * 5120, 5120);
    }
    bulk_commit();
    bulk_wait_read0();
    mbar_arrive(sb + B_EXP);
}
__device__ __forceinline__ void export_signal(int s, int h) {
    bulk_wait0();
    asm volatile("fence.proxy.async;" ::: "memory");
    __threadfence();
    atomicAdd(&g_flag[s][h], 1u);
}

__device__ __forceinline__ void score_tile(uint32_t sb, int sl, int nt, int lane, uint32_t rank) {
    float sc[4] = {0, 0, 0, 0}, sd[4] = {0, 0, 0, 0};
    const int r = lane & 7;
    uint32_t qa[2][4], kb[2][4];
    #pragma unroll
    for (int j = 0; j < 2; j++) {
        const int chunk = (lane >> 3) + 4 * j;
        ldsm4(kb[j], sb + SM_KT + sl * 5120 + (8 * nt + r) * 128 + ((chunk ^ r) << 4));
        ldsm4(qa[j], sb + SM_QS + r * 128 + ((chunk ^ r) << 4));
    }
    mma_bf16(sc, qa[0][0], 0u, qa[0][1], 0u, kb[0][0], kb[0][1]);
    mma_bf16(sd, qa[1][0], 0u, qa[1][1], 0u, kb[1][0], kb[1][1]);
    mma_bf16(sc, qa[0][2], 0u, qa[0][3], 0u, kb[0][2], kb[0][3]);
    mma_bf16(sd, qa[1][2], 0u, qa[1][3], 0u, kb[1][2], kb[1][3]);
    sc[0] += sd[0]; sc[1] += sd[1];
    const float o0 = __shfl_down_sync(~0u, sc[0], 1), o1 = __shfl_down_sync(~0u, sc[1], 1);
    if ((lane & 1) == 0) {
        const uint32_t a = SM_SC + sl * 2560 + rank * 1280 + ((lane >> 2) * 40 + 8 * nt + 2 * (lane & 3)) * 4;
        const uint32_t bo = B_SC + 8 * sl;
        { const uint32_t rb = mapa(sb, 2); st_async4(rb + a, sc[0], sc[1], o0, o1, rb + bo); }
        { const uint32_t rb = mapa(sb, rank ^ 1); st_async4(rb + a, sc[0], sc[1], o0, o1, rb + bo); }
        asm volatile("st.shared.v4.f32 [%0], {%1,%2,%3,%4};" :: "r"(sb + a), "f"(sc[0]), "f"(sc[1]), "f"(o0), "f"(o1) : "memory");
    }
    __syncwarp();
    if (lane == 0) mbar_arrive(sb + B_SC + 8 * sl);
}
__device__ __forceinline__ void wgmma_n40_rs(float (&d)[20], const uint32_t (&a)[4], uint64_t db, int scale_d) {
    asm volatile("{\n.reg .pred p;\nsetp.ne.b32 p, %25, 0;\n"
        "wgmma.mma_async.sync.aligned.m64n40k16.f32.bf16.bf16 {%0,%1,%2,%3,%4,%5,%6,%7,%8,%9,%10,%11,%12,%13,%14,%15,%16,%17,%18,%19}, {%20,%21,%22,%23}, %24, p, 1, 1, 0;\n}\n"
        : "+f"(d[0]), "+f"(d[1]), "+f"(d[2]), "+f"(d[3]), "+f"(d[4]), "+f"(d[5]), "+f"(d[6]), "+f"(d[7]), "+f"(d[8]), "+f"(d[9]),
          "+f"(d[10]), "+f"(d[11]), "+f"(d[12]), "+f"(d[13]), "+f"(d[14]), "+f"(d[15]), "+f"(d[16]), "+f"(d[17]), "+f"(d[18]), "+f"(d[19])
        : "r"(a[0]), "r"(a[1]), "r"(a[2]), "r"(a[3]), "l"(db), "r"(scale_d));
}
__device__ __forceinline__ void pu_store(const float (&u)[20], const uint32_t (&pb)[5], float2 inv, unsigned char* smem, int sl, int lt, int warp, int lane, uint32_t tg) {
    float o[4] = {0, 0, 0, 0}, o2[4] = {0, 0, 0, 0};
    mma_bf16(o, pack_bf16(u[0], u[1]), pack_bf16(u[2], u[3]), pack_bf16(u[4], u[5]), pack_bf16(u[6], u[7]), pb[0], pb[1]);
    mma_bf16(o2, pack_bf16(u[8], u[9]), pack_bf16(u[10], u[11]), pack_bf16(u[12], u[13]), pack_bf16(u[14], u[15]), pb[2], pb[3]);
    mma_bf16(o, pack_bf16(u[16], u[17]), pack_bf16(u[18], u[19]), 0u, 0u, pb[4], 0u);
    const uint2 off = *reinterpret_cast<const uint2*>(smem + SM_TPM + (((sl * 4 + lt) * 4 + warp) * 2) * 4);
    unsigned char* pool = reinterpret_cast<unsigned char*>(g_pool) + lane * 8;
    st_relaxed2(pool + off.x, (__float_as_uint((o[0] + o2[0]) * inv.x) & ~3u) | tg, (__float_as_uint((o[1] + o2[1]) * inv.y) & ~3u) | tg);
    st_relaxed2(pool + off.y, (__float_as_uint((o[2] + o2[2]) * inv.x) & ~3u) | tg, (__float_as_uint((o[3] + o2[3]) * inv.y) & ~3u) | tg);
}
template <int NT>
__device__ __forceinline__ void u_pass(unsigned char* smem, uint32_t sb, int s, uint32_t rank, int wg, int warp, int lane) {
    const int sl = s & 1;
    constexpr int NRS = 6;
    uint32_t wa[NRS][4];
    {
        const int mi = lane >> 3, chunk = 2 * warp + (mi & 1);
        #pragma unroll
        for (int ks = 0; ks < NRS; ks++) {
            const int row = 16 * ks + (mi >> 1) * 8 + (lane & 7);
            ldsm4t(wa[ks], sb + SM_WO + (2 * wg) * 16384 + row * 128 + ((chunk ^ (row & 7)) << 4));
        }
    }
    if (rank < 2) { mbar_wait(sb + B_V + 8 * sl, (s >> 1) & 1); fence_async(); }
    if (wg == 0 && warp == 0) TR(4);
    float U0[20];
    wg_fence();
    #pragma unroll
    for (int ks = 0; ks < NRS; ks++)
        wgmma_n40_rs(U0, wa[ks], make_desc(sb + SM_VT + sl * 10240 + (ks >> 2) * 5120 + (ks & 3) * 32, 16, 1024), ks > 0);
    #pragma unroll
    for (int ks = NRS; ks < 8; ks++)
        wgmma_n40_tA(U0, make_desc(sb + SM_WO + (2 * wg) * 16384 + ks * 2048, 1024, 1024),
                     make_desc(sb + SM_VT + sl * 10240 + (ks >> 2) * 5120 + (ks & 3) * 32, 16, 1024), 1);
    wg_commit();
    const uint32_t tg = tag_of(s);
    uint32_t pb[5];
    float2 inv;
    auto get_p = [&]() {
        nbar_sync(9, 288);
        const uint32_t* pbs = reinterpret_cast<const uint32_t*>(smem + SM_PB);
        #pragma unroll
        for (int q = 0; q < 5; q++) pb[q] = pbs[q * 32 + lane];
        float sm[4] = {0, 0, 0, 0}, sm2[4] = {0, 0, 0, 0};
        const uint32_t one = 0x3f803f80u;
        mma_bf16(sm, one, one, one, one, pb[0], pb[1]);
        mma_bf16(sm2, one, one, one, one, pb[2], pb[3]);
        mma_bf16(sm, one, one, 0u, 0u, pb[4], 0u);
        inv.x = __frcp_rn(sm[0] + sm2[0]); inv.y = __frcp_rn(sm[1] + sm2[1]);
    };
    if (NT == 2) {
        wg_wait0();
        float U1[20];
        wg_fence();
        #pragma unroll
        for (int ks = 0; ks < 8; ks++)
            wgmma_n40_tA(U1, make_desc(sb + SM_WO + (2 * wg + 1) * 16384 + ks * 2048, 1024, 1024),
                         make_desc(sb + SM_VT + sl * 10240 + (ks >> 2) * 5120 + (ks & 3) * 32, 16, 1024), ks > 0);
        wg_commit();
        get_p();
        if (wg == 0 && warp == 0) TR(8);
        pu_store(U0, pb, inv, smem, sl, 2 * wg, warp, lane, tg);
        wg_wait0();
        if (wg == 0 && warp == 0) TR(6);
        pu_store(U1, pb, inv, smem, sl, 2 * wg + 1, warp, lane, tg);
    } else {
        wg_wait0();
        get_p();
        pu_store(U0, pb, inv, smem, sl, 2 * wg, warp, lane, tg);
    }
}

__global__ void __cluster_dims__(3, 1, 1) __launch_bounds__(384, 1)
k_chain(const __grid_constant__ CUtensorMap xmap, const __grid_constant__ CUtensorMap wqmap, const __grid_constant__ CUtensorMap wkmap,
        const __grid_constant__ CUtensorMap wvmap, const __grid_constant__ CUtensorMap womap, const bf16* __restrict__ xptr, const bf16* __restrict__ mem0) {
    extern __shared__ __align__(1024) unsigned char smem[];
    const uint32_t sb = smem_u32(smem);
    const int tid = threadIdx.x, lane = tid & 31;
    const int wg = __shfl_sync(~0u, tid >> 7, 0), warp = __shfl_sync(~0u, (tid >> 5) & 3, 0);
    uint32_t rank; asm volatile("mov.u32 %0, %%cluster_ctarank;" : "=r"(rank));
    const int cta = blockIdx.x, h = cta / 3;
    asm volatile("griddepcontrol.launch_dependents;");
    if (tid == 0) {
        for (int i = 0; i < 2; i++) { mbar_init(sb + B_SC + 8 * i, rank < 2 ? 6 : 1); mbar_init(sb + B_V + 8 * i, 1); mbar_init(sb + B_MEM + 8 * i, 64); mbar_init(sb + B_X + 8 * i, 1); }
        mbar_init(sb + B_P, 1); mbar_init(sb + B_EXP, 1);
        asm volatile("fence.mbarrier_init.release.cluster;" ::: "memory");
    }
    if (tid < 80) asm volatile("prefetch.global.L2 [%0];" :: "l"(mem0 + tid * 64));
    if (h < 2) { for (int i = tid; i < 320; i += 384) asm volatile("prefetch.global.L2 [%0];" :: "l"(xptr + (size_t)h * 32 * DM + i * 64)); }
    {
        const int w12 = tid >> 5;
        if (lane == 0 && w12 < 7) {
            uint32_t* pp = (w12 < 6) ? g_pool + (size_t)(cta * 6 + w12) * 1024 + 512 : g_pool + (size_t)NPOOL * 1024 + (cta & 31) * 32 + (cta >> 5) * 8;
            const unsigned lat = probe_latency(pp, blockIdx.y);
            if (w12 < 6) g_cls[cta * 6 + w12] = lat > CAL_THR ? 1u : 0u; else g_side[cta] = lat > CAL_THR ? 1u : 0u;
        }
        __syncwarp();
        uint4* z = reinterpret_cast<uint4*>(g_pool + (size_t)cta * 6 * 1024);
        #pragma unroll
        for (int q = 0; q < 4; q++) z[tid + 384 * q] = make_uint4(0, 0, 0, 0);
        __threadfence();
        __syncwarp();
        if (lane == 0) atomicAdd(&g_calcnt, 1u);
    }
    __syncthreads();
    if (tid == 0) {
        const int ntile = (rank == 2) ? 4 : 3;
        const int tile0 = (rank == 2) ? 0 : (rank == 0 ? 4 : 7);
        mbar_expect_tx(sb + B_P, 163840 + ntile * 16384);
        const void* m0 = (rank == 2) ? &wvmap : &wqmap;
        const void* m1 = (rank == 2) ? &wvmap : &wkmap;
        const int c0 = h * DH + (rank == 1 ? 64 : 0), c1 = h * DH + (rank == 0 ? 0 : 64);
        for (int b = 0; b < 5; b++) {
            tma_load_2d(sb + b * 16384, m0, c0, b * 128, sb + B_P);
            tma_load_2d(sb + 81920 + b * 16384, m1, c1, b * 128, sb + B_P);
        }
        for (int lt = 0; lt < ntile; lt++) {
            tma_load_2d(sb + SM_WO + lt * 16384, &womap, (tile0 + lt) * 64, h * DH, sb + B_P);
            tma_load_2d(sb + SM_WO + lt * 16384 + 8192, &womap, (tile0 + lt) * 64, h * DH + 64, sb + B_P);
        }
    }
    {
        const int tile0 = (rank == 2) ? 0 : (rank == 0 ? 4 : 7);
        if (wg == 2) {
            const int ct = tid & 127;
            if (ct == 0) {
                const unsigned target = (*reinterpret_cast<volatile unsigned*>(&g_epoch) + 1u) * (96u * 12u);
                int guard = 0;
                while ((int)(ld_acquire(&g_calcnt) - target) < 0 && ++guard < (1 << 22)) {}
            }
            nbar_sync(4, 128);
            uint32_t* bm = reinterpret_cast<uint32_t*>(smem + SM_CAL);
            {
                unsigned v[5];
                #pragma unroll
                for (int q = 0; q < 5; q++) { const int b = ct + 128 * q; v[q] = (b < NPOOL) ? (__ldcg(&g_cls[b]) ^ __ldcg(&g_side[b / 6])) : 0u; }
                const unsigned sv = (ct < 96) ? __ldcg(&g_side[ct]) : 0u;
                #pragma unroll
                for (int q = 0; q < 5; q++) { const unsigned m = __ballot_sync(~0u, v[q] & 1u); if (lane == 0 && q * 4 + warp < 18) bm[q * 4 + warp] = m; }
                const unsigned m = __ballot_sync(~0u, sv & 1u);
                if (lane == 0 && warp < 3) bm[18 + warp] = m;
            }
            nbar_sync(4, 128);
            int nblk1 = 0;
            for (int i = 0; i < 18; i++) nblk1 += __popc(bm[i]);
            const unsigned red_last = (1u << (NRED - 64)) - 1u;
            const int nred1 = __popc(bm[18]) + __popc(bm[19]) + __popc(bm[20] & red_last);
            auto side_of = [&](int c) -> int { return (bm[18 + (c >> 5)] >> (c & 31)) & 1; };
            auto rank_of = [&](int c) -> int {
                int ones = 0;
                for (int i = 0; i < (c >> 5); i++) ones += __popc(bm[18 + i]);
                ones += __popc(bm[18 + (c >> 5)] & ((1u << (c & 31)) - 1u));
                return side_of(c) ? ones : c - ones;
            };
            auto nth = [&](int side, int idx) -> uint32_t {
                for (int i = 0; i < 18; i++) {
                    const unsigned m = side ? bm[i] : ~bm[i];
                    const int n = __popc(m);
                    if (idx < n) return (uint32_t)(i * 32 + __fns(m, 0, idx + 1));
                    idx -= n;
                }
                return 0u;
            };
            auto phys = [&](int side, int idx) -> uint32_t {
                const int c = side ? nblk1 : NPOOL - nblk1;
                return (idx < c) ? nth(side, idx) : nth(side ^ 1, (NPOOL - c) - 1 - (idx - c));
            };
            const int e = ct;
            if (e < 64) {
                const int slot = e >> 5, lt = (e >> 3) & 3, w = (e >> 1) & 3, hf = e & 1;
                const int tile = min(tile0 + lt, 9);
                const int r = 2 * (4 * tile + w) + hf;
                reinterpret_cast<uint32_t*>(smem + SM_TPM)[e] = phys(side_of(r), 4 * rank_of(r) + slot * 2 + (h >> 4)) * 4096u + (h & 15) * 256u;
            } else if (e < 68) {
                const int i = e - 64;
                reinterpret_cast<uint32_t*>(smem + SM_TRD)[i] = (cta < NRED) ? phys(side_of(cta), 4 * rank_of(cta) + i) * 4096u : 0u;
            } else if (e < 100) {
                const int i = e - 68, slot = i >> 3, rep = i & 7, side = (rep / RPS) & 1;
                reinterpret_cast<uint32_t*>(smem + SM_TPUB)[i] = phys(side, 4 * (side ? nred1 : NRED - nred1) + (slot * RPS + (rep % RPS)) * 3 + (cta >> 5)) * 4096u + (cta & 31) * 128u;
            } else if (e < 112) {
                const int i = e - 100, slot = i / 3, b = i % 3, side = side_of(cta);
                reinterpret_cast<uint32_t*>(smem + SM_TGAT)[slot * 4 + b] = phys(side, 4 * (side ? nred1 : NRED - nred1) + (slot * RPS + (h % RPS)) * 3 + b) * 4096u;
            }
        }
    }
    __syncthreads();
    mbar_wait_sleep(sb + B_P, 0);

    if (wg == 2) {
        asm volatile("setmaxnreg.dec.sync.aligned.u32 " COMM_REGS ";");
        const int ct = tid & 127;
        nbar_sync(5, 384);
        for (int c = ct; c < 640; c += 128) {
            int ks = c >> 4, hf = (c >> 3) & 1, r = c & 7;
            *reinterpret_cast<uint4*>(smem + SM_MEMB + c * 16) = *reinterpret_cast<const uint4*>(mem0 + r * DM + ks * 16 + hf * 8);
        }
        if (ct == 0) {
            for (int sg = 0; sg < 2; sg++) {
                mbar_expect_tx(sb + B_X + 8 * sg, 40960);
                tma_load_3d(sb + SM_XB + sg * 40960, &xmap, 0, sg * 32, 0, sb + B_X + 8 * sg);
            }
            mbar_expect_tx(sb + B_SC, rank < 2 ? 1280 : 2560);
            if (rank < 2) mbar_expect_tx(sb + B_V, 8192 + 2048);
        }
        nbar_sync(5, 384);
        cluster_sync_all();
        unsigned char* const pool = reinterpret_cast<unsigned char*>(g_pool);
        for (int s = 0; s < NSEG - 1; s++) {
            if (warp == 1) nbar_sync(12, 288);
            if (warp == 0) {
                const int g = lane >> 2, t = lane & 3;
                mbar_wait(sb + B_SC + 8 * (s & 1), (s >> 1) & 1);
                TR(5);
                const uint32_t sa = sb + SM_SC + (s & 1) * 2560 + (g * 40 + 2 * t) * 4;
                float v[5][2], u[5][2];
                #pragma unroll
                for (int q = 0; q < 5; q++) {
                    asm volatile("ld.shared.v2.f32 {%0,%1}, [%2];" : "=f"(v[q][0]), "=f"(v[q][1]) : "r"(sa + 32 * q) : "memory");
                    asm volatile("ld.shared.v2.f32 {%0,%1}, [%2];" : "=f"(u[q][0]), "=f"(u[q][1]) : "r"(sa + 1280 + 32 * q) : "memory");
                }
                float mx = -3.0e38f;
                #pragma unroll
                for (int q = 0; q < 5; q++) {
                    v[q][0] += u[q][0]; v[q][1] += u[q][1];
                    mx = fmaxf(mx, fmaxf(v[q][0], v[q][1]));
                }
                mx = fmaxf(mx, __shfl_xor_sync(~0u, mx, 1));
                mx = fmaxf(mx, __shfl_xor_sync(~0u, mx, 2));
                const float sc2 = 0.08838834764831845f * 1.4426950408889634f;
                const float mxs = mx * sc2;
                uint32_t* pbs = reinterpret_cast<uint32_t*>(smem + SM_PB);
                #pragma unroll
                for (int q = 0; q < 5; q++) {
                    const float e0 = ex2_approx(fmaf(v[q][0], sc2, -mxs)), e1 = ex2_approx(fmaf(v[q][1], sc2, -mxs));
                    pbs[q * 32 + lane] = pack_bf16(e0, e1);
                }
                __syncwarp();
                TR(0);
                nbar_arrive(9, 288);
            } else if (warp == 1 && lane == 0) {
                if (s + 1 < NSEG - 1) {
                    mbar_expect_tx(sb + B_SC + 8 * ((s + 1) & 1), rank < 2 ? 1280 : 2560);
                    if (rank < 2) mbar_expect_tx(sb + B_V + 8 * ((s + 1) & 1), 8192 + 2048);
                }
                if (s + 2 < NSEG) {
                    mbar_expect_tx(sb + B_X + 8 * (s & 1), 40960);
                    tma_load_3d(sb + SM_XB + (s & 1) * 40960, &xmap, 0, (s + 2) * 32, 0, sb + B_X + 8 * (s & 1));
                }
                export_issue(sb, s, h, rank);
                if (s >= NSEG - 4) export_signal(s, h);
            }
            __syncwarp();
            nbar_sync(3, 384);
            const uint32_t tg = tag_of(s);
            if (cta < NRED) {
                const unsigned char* base = pool + reinterpret_cast<const uint32_t*>(smem + SM_TRD)[(s & 1) * 2 + (warp >> 1)] + (warp & 1) * 2048 + lane * 16;
                uint4 v[4]; int guard = 0;
                #pragma unroll
                for (int j = 0; j < 4; j++) v[j] = make_uint4(0, 0, 0, 0);
                uint32_t pend = 0xF;
                do {
                    #pragma unroll
                    for (int j = 0; j < 4; j++) if (pend & (1u << j)) v[j] = ld_relaxed4(base + j * 512);
                    #pragma unroll
                    for (int j = 0; j < 4; j++)
                        if (((v[j].x & 3) == tg) && ((v[j].y & 3) == tg) && ((v[j].z & 3) == tg) && ((v[j].w & 3) == tg)) pend &= ~(1u << j);
                } while (__any_sync(~0u, pend != 0) && ++guard < (1 << 20));
                if (warp == 0) TR(9);
                float a0 = 0, a1 = 0, a2 = 0, a3 = 0;
                #pragma unroll
                for (int j = 0; j < 4; j++) { a0 += __uint_as_float(v[j].x); a1 += __uint_as_float(v[j].y); a2 += __uint_as_float(v[j].z); a3 += __uint_as_float(v[j].w); }
                a0 += __shfl_xor_sync(~0u, a0, 16); a1 += __shfl_xor_sync(~0u, a1, 16); a2 += __shfl_xor_sync(~0u, a2, 16); a3 += __shfl_xor_sync(~0u, a3, 16);
                float* cr = reinterpret_cast<float*>(smem + SM_CRED);
                if (lane < 16) *reinterpret_cast<float4*>(cr + warp * 64 + lane * 4) = make_float4(a0, a1, a2, a3);
                nbar_sync(4, 128);
                {
                    int rho = lane >> 2, pp = lane & 3;
                    int i0 = ((2 * pp) * 4 + (rho >> 1)) * 2 + (rho & 1), i1 = i0 + 8;
                    uint32_t wv = pack_bf16((cr[i0] + cr[64 + i0]) + (cr[128 + i0] + cr[192 + i0]), (cr[i1] + cr[64 + i1]) + (cr[128 + i1] + cr[192 + i1]));
                    if (wv == 0) wv = 0x8000u;
                    if (warp == 0) TR(10);
                    const uint32_t* tp = reinterpret_cast<const uint32_t*>(smem + SM_TPUB) + warp;
                    if (warp < 2 * RPS) st_relaxed1(pool + tp[((s + 1) & 3) * 8] + lane * 4, wv);
                    if (RPS == 4) st_relaxed1(pool + tp[((s + 1) & 3) * 8 + 4] + lane * 4, wv);
                    if (warp < 2 * RPS) st_relaxed1(pool + tp[(s & 3) * 8] + lane * 4, 0u);
                    if (RPS == 4) st_relaxed1(pool + tp[(s & 3) * 8 + 4] + lane * 4, 0u);
                }
            }
            {
                const int c0 = warp * 160 + lane;
                const uint32_t* tg3 = reinterpret_cast<const uint32_t*>(smem + SM_TGAT) + ((s + 1) & 3) * 4;
                const uint32_t g0 = tg3[0], g1 = tg3[1], g2 = tg3[2];
                uint4 v[5]; int guard = 0;
                #pragma unroll
                for (int j = 0; j < 5; j++) v[j] = make_uint4(0, 0, 0, 0);
                uint32_t pend = 0x1F;
                do {
                    #pragma unroll
                    for (int j = 0; j < 5; j++) {
                        const int c = c0 + 32 * j;
                        if (pend & (1u << j)) v[j] = ld_relaxed4(pool + ((c >> 8) == 0 ? g0 : ((c >> 8) == 1 ? g1 : g2)) + (c & 255) * 16);
                    }
                    #pragma unroll
                    for (int j = 0; j < 5; j++) if (v[j].x && v[j].y && v[j].z && v[j].w) pend &= ~(1u << j);
                } while (__any_sync(~0u, pend != 0) && ++guard < (1 << 20));
                #pragma unroll
                for (int j = 0; j < 5; j++) *reinterpret_cast<uint4*>(smem + SM_MEMB + (c0 + 32 * j) * 16) = v[j];
                if (warp == 0) TR(11);
                if (warp == 3) TR(12);
                nbar_arrive(warp < 2 ? 7 + warp : 8 + warp, 160);
            }
            if (warp == 1 && lane == 0 && s < NSEG - 4) export_signal(s, h);
            __syncwarp();
        }
        if (warp == 1) { nbar_sync(12, 288); if (lane == 0) { export_issue(sb, NSEG - 1, h, rank); export_signal(NSEG - 1, h); } }
        __syncwarp();
        nbar_sync(3, 384);
        __syncwarp();
        cluster_sync_all();
    } else {
        asm volatile("setmaxnreg.inc.sync.aligned.u32 232;");
        const int wtid = tid & 127;
        const int cw = wg * 4 + warp;
        uint32_t areg[2][20][4];
        #pragma unroll
        for (int mt = 0; mt < 2; mt++)
            #pragma unroll
            for (int kk = 0; kk < 20; kk++) {
                int mi = lane >> 3;
                int row = 16 * (20 * wg + kk) + (mi >> 1) * 8 + (lane & 7);
                int chunk = 2 * warp + (mi & 1);
                ldsm4t(areg[mt][kk], sb + mt * 81920 + row * 128 + ((chunk ^ (row & 7)) << 4));
            }
        nbar_sync(5, 384);
        nbar_sync(5, 384);
        cluster_sync_all();

        for (int s = -1; s < NSEG; s++) {
            const int sl = s & 1;
            if (s >= 0) {
            if (s > 0) nbar_sync(7 + 3 * wg, 160);
            float fin[4];
            {
                float acc[2][2][4];
                #pragma unroll
                for (int i = 0; i < 2; i++)
                    #pragma unroll
                    for (int j = 0; j < 2; j++) { acc[i][j][0] = acc[i][j][1] = acc[i][j][2] = acc[i][j][3] = 0.f; }
                uint32_t b[3][4];
                const uint32_t mb = sb + SM_MEMB + (20 * wg) * 256 + lane * 16;
                ldsm4(b[0], mb); ldsm4(b[1], mb + 512);
                #pragma unroll
                for (int kp = 0; kp < 10; kp++) {
                    if (kp == 3 && s > 0) nbar_sync(8 + 3 * wg, 160);
                    if (kp + 2 < 10) ldsm4(b[(kp + 2) % 3], mb + (kp + 2) * 512);
                    const uint32_t (&bb)[4] = b[kp % 3];
                    mma_bf16(acc[0][0], areg[0][2 * kp][0], areg[0][2 * kp][1], areg[0][2 * kp][2], areg[0][2 * kp][3], bb[0], bb[1]);
                    mma_bf16(acc[1][0], areg[1][2 * kp][0], areg[1][2 * kp][1], areg[1][2 * kp][2], areg[1][2 * kp][3], bb[0], bb[1]);
                    mma_bf16(acc[0][1], areg[0][2 * kp + 1][0], areg[0][2 * kp + 1][1], areg[0][2 * kp + 1][2], areg[0][2 * kp + 1][3], bb[2], bb[3]);
                    mma_bf16(acc[1][1], areg[1][2 * kp + 1][0], areg[1][2 * kp + 1][1], areg[1][2 * kp + 1][2], areg[1][2 * kp + 1][3], bb[2], bb[3]);
                }
                float4* red = reinterpret_cast<float4*>(smem + SM_RED);
                float m0[4], m1[4];
                #pragma unroll
                for (int i = 0; i < 4; i++) { m0[i] = acc[0][0][i] + acc[0][1][i]; m1[i] = acc[1][0][i] + acc[1][1][i]; }
                red[(wg ^ 1) * 128 + wtid] = wg == 0 ? make_float4(m1[0], m1[1], m1[2], m1[3]) : make_float4(m0[0], m0[1], m0[2], m0[3]);
                nbar_sync(1, 256);
                float4 r = red[wg * 128 + wtid];
                fin[0] = (wg == 0 ? m0[0] : m1[0]) + r.x; fin[1] = (wg == 0 ? m0[1] : m1[1]) + r.y;
                fin[2] = (wg == 0 ? m0[2] : m1[2]) + r.z; fin[3] = (wg == 0 ? m0[3] : m1[3]) + r.w;
            }
            if (cw == 0) TR(1);
            {
                uint32_t p0 = pack_bf16(fin[0], fin[1]), p1 = pack_bf16(fin[2], fin[3]);
                const uint32_t doff = (rank == 2) ? SM_VT + sl * 10240 + wg * 5120 : (wg == 0 ? SM_QS : SM_KT + sl * 5120);
                const int r = lane & 7, chunk = 2 * warp + ((lane >> 3) & 1);
                const uint32_t coff = doff + r * 128 + ((chunk ^ r) << 4);
                stsm2t(sb + coff, p0, p1);
                if (rank == 2 && s < NSEG - 1) {
                    __syncwarp();
                    const uint4 v = *reinterpret_cast<const uint4*>(smem + coff);
                    const uint32_t rb = mapa(sb, lane >> 4);
                    st_async4u(rb + coff, v, rb + B_V + 8 * sl);
                }
            }
            fence_async();
            nbar_sync(1, 256);
            nbar_arrive(12, 288);
            if (cw == 0) TR(2);
            if (rank < 2 && s < NSEG - 1) {
                if (wg == 1) score_tile(sb, sl, 1 + warp, lane, rank);
                else if (warp == 0) score_tile(sb, sl, 0, lane, rank);
            }
            if (s == NSEG - 1) break;
            if (cw == 0) TR(3);
            if (wg == 0 || rank == 2) u_pass<2>(smem, sb, s, rank, wg, warp, lane);
            else                      u_pass<1>(smem, sb, s, rank, wg, warp, lane);
            if (cw == 0) TR(7);
            nbar_arrive(3, 384);
            }
            {
                const int sn = s + 1, sln = sn & 1;
                mbar_wait(sb + B_X + 8 * sln, (sn >> 1) & 1);
                float acc[2][16];
                wg_fence();
                #pragma unroll
                for (int mt = 0; mt < 2; mt++)
                    #pragma unroll
                    for (int kk = 0; kk < 20; kk++) {
                        uint64_t db = make_desc(sb + SM_XB + sln * 40960 + (5 * wg + (kk >> 2)) * 4096 + (kk & 3) * 32, 16, 1024);
                        wgmma_n32_rs(acc[mt], areg[mt][kk], db, kk > 0);
                    }
                wg_commit();
                if (cw == 0 && s >= 0) TR(14);
                wg_wait0();
                if (cw == 0 && s >= 0) TR(15);
                float4* red = reinterpret_cast<float4*>(smem + SM_RED);
                #pragma unroll
                for (int j = 0; j < 4; j++) {
                    red[((wg ^ 1) * 4 + j) * 128 + wtid] = make_float4(wg == 0 ? acc[1][4 * j] : acc[0][4 * j], wg == 0 ? acc[1][4 * j + 1] : acc[0][4 * j + 1],
                                                                       wg == 0 ? acc[1][4 * j + 2] : acc[0][4 * j + 2], wg == 0 ? acc[1][4 * j + 3] : acc[0][4 * j + 3]);
                }
                if (s >= 0) mbar_wait(sb + B_EXP, s & 1);
                nbar_sync(1, 256);
                uint32_t pk[8];
                #pragma unroll
                for (int j = 0; j < 4; j++) {
                    float4 r = red[(wg * 4 + j) * 128 + wtid];
                    pk[2 * j] = pack_bf16((wg == 0 ? acc[0][4 * j] : acc[1][4 * j]) + r.x, (wg == 0 ? acc[0][4 * j + 1] : acc[1][4 * j + 1]) + r.y);
                    pk[2 * j + 1] = pack_bf16((wg == 0 ? acc[0][4 * j + 2] : acc[1][4 * j + 2]) + r.z, (wg == 0 ? acc[0][4 * j + 3] : acc[1][4 * j + 3]) + r.w);
                }
                const uint32_t dst = (rank == 2) ? sb + SM_VT + sln * 10240 + wg * 5120 + 1024 : (wg == 0 ? sb + SM_QT : sb + SM_KT + sln * 5120 + 1024);
                #pragma unroll
                for (int jj = 0; jj < 2; jj++) {
                    int mi = lane >> 3, tok = 8 * (2 * jj + (mi >> 1)) + (lane & 7), chunk = 2 * warp + (mi & 1);
                    stsm4t(dst + tok * 128 + ((chunk ^ (tok & 7)) << 4), pk[4 * jj], pk[4 * jj + 1], pk[4 * jj + 2], pk[4 * jj + 3]);
                }
                fence_async();
                nbar_sync(1, 256);
                if (rank == 2 && lane == 0 && cw < 4 && sn < NSEG - 1) {
                    const uint32_t off = SM_VT + sln * 10240 + (cw & 1) * 5120 + 1024;
                    const uint32_t rb = mapa(sb, cw >> 1);
                    bulk_s2c(rb + off, sb + off, 4096, rb + B_V + 8 * sln);
                }
                if (cw == 0 && s >= 0) TR(13);
            }
        }
        nbar_arrive(3, 384);
        __syncwarp();
        cluster_sync_all();
    }
}

#define NAUX 36
__device__ __align__(1024) bf16 g_Oimg[16 * 64 * 128 * 64];
__device__ float    g_part[4 * SEQ * DM];
__device__ float    g_part31[2 * 13 * 64 * DM];
__device__ unsigned g_ocnt[32];
__device__ unsigned g_gcnt[32][2];
__device__ unsigned g_ssmcnt, g_auxdone, g_taskctr, g_gemmctr;
#define NATT 8
#define ATR(i) do {} while (0)
#define ATRID(i, id) do {} while (0)

__device__ __forceinline__ void wait_counter(const unsigned* p, unsigned target) {
    int guard = 0;
    while ((int)(ld_acquire(p) - target) < 0 && ++guard < (1 << 22)) __nanosleep(64);
}
__device__ __forceinline__ void fence_async_all() { asm volatile("fence.proxy.async;" ::: "memory"); }
template <int OFF>
__device__ __forceinline__ void wgmma_n192_tB(float (&d)[160], uint64_t da, uint64_t db) {
    asm volatile("wgmma.mma_async.sync.aligned.m64n192k16.f32.bf16.bf16 {%0,%1,%2,%3,%4,%5,%6,%7,%8,%9,%10,%11,%12,%13,%14,%15,%16,%17,%18,%19,%20,%21,%22,%23,%24,%25,%26,%27,%28,%29,%30,%31,%32,%33,%34,%35,%36,%37,%38,%39,%40,%41,%42,%43,%44,%45,%46,%47,%48,%49,%50,%51,%52,%53,%54,%55,%56,%57,%58,%59,%60,%61,%62,%63,%64,%65,%66,%67,%68,%69,%70,%71,%72,%73,%74,%75,%76,%77,%78,%79,%80,%81,%82,%83,%84,%85,%86,%87,%88,%89,%90,%91,%92,%93,%94,%95}, %96, %97, 1, 1, 1, 0, 1;\n"
        : "+f"(d[OFF + 0]), "+f"(d[OFF + 1]), "+f"(d[OFF + 2]), "+f"(d[OFF + 3]), "+f"(d[OFF + 4]), "+f"(d[OFF + 5]), "+f"(d[OFF + 6]), "+f"(d[OFF + 7]), "+f"(d[OFF + 8]), "+f"(d[OFF + 9]), "+f"(d[OFF + 10]), "+f"(d[OFF + 11]), "+f"(d[OFF + 12]), "+f"(d[OFF + 13]), "+f"(d[OFF + 14]), "+f"(d[OFF + 15]), "+f"(d[OFF + 16]), "+f"(d[OFF + 17]), "+f"(d[OFF + 18]), "+f"(d[OFF + 19]), "+f"(d[OFF + 20]), "+f"(d[OFF + 21]), "+f"(d[OFF + 22]), "+f"(d[OFF + 23]), "+f"(d[OFF + 24]), "+f"(d[OFF + 25]), "+f"(d[OFF + 26]), "+f"(d[OFF + 27]), "+f"(d[OFF + 28]), "+f"(d[OFF + 29]), "+f"(d[OFF + 30]), "+f"(d[OFF + 31]), "+f"(d[OFF + 32]), "+f"(d[OFF + 33]), "+f"(d[OFF + 34]), "+f"(d[OFF + 35]), "+f"(d[OFF + 36]), "+f"(d[OFF + 37]), "+f"(d[OFF + 38]), "+f"(d[OFF + 39]), "+f"(d[OFF + 40]), "+f"(d[OFF + 41]), "+f"(d[OFF + 42]), "+f"(d[OFF + 43]), "+f"(d[OFF + 44]), "+f"(d[OFF + 45]), "+f"(d[OFF + 46]), "+f"(d[OFF + 47]), "+f"(d[OFF + 48]), "+f"(d[OFF + 49]), "+f"(d[OFF + 50]), "+f"(d[OFF + 51]), "+f"(d[OFF + 52]), "+f"(d[OFF + 53]), "+f"(d[OFF + 54]), "+f"(d[OFF + 55]), "+f"(d[OFF + 56]), "+f"(d[OFF + 57]), "+f"(d[OFF + 58]), "+f"(d[OFF + 59]), "+f"(d[OFF + 60]), "+f"(d[OFF + 61]), "+f"(d[OFF + 62]), "+f"(d[OFF + 63]), "+f"(d[OFF + 64]), "+f"(d[OFF + 65]), "+f"(d[OFF + 66]), "+f"(d[OFF + 67]), "+f"(d[OFF + 68]), "+f"(d[OFF + 69]), "+f"(d[OFF + 70]), "+f"(d[OFF + 71]), "+f"(d[OFF + 72]), "+f"(d[OFF + 73]), "+f"(d[OFF + 74]), "+f"(d[OFF + 75]), "+f"(d[OFF + 76]), "+f"(d[OFF + 77]), "+f"(d[OFF + 78]), "+f"(d[OFF + 79]), "+f"(d[OFF + 80]), "+f"(d[OFF + 81]), "+f"(d[OFF + 82]), "+f"(d[OFF + 83]), "+f"(d[OFF + 84]), "+f"(d[OFF + 85]), "+f"(d[OFF + 86]), "+f"(d[OFF + 87]), "+f"(d[OFF + 88]), "+f"(d[OFF + 89]), "+f"(d[OFF + 90]), "+f"(d[OFF + 91]), "+f"(d[OFF + 92]), "+f"(d[OFF + 93]), "+f"(d[OFF + 94]), "+f"(d[OFF + 95])
        : "l"(da), "l"(db));
}
template <int OFF>
__device__ __forceinline__ void wgmma_n128_tB(float (&d)[160], uint64_t da, uint64_t db) {
    asm volatile("wgmma.mma_async.sync.aligned.m64n128k16.f32.bf16.bf16 {%0,%1,%2,%3,%4,%5,%6,%7,%8,%9,%10,%11,%12,%13,%14,%15,%16,%17,%18,%19,%20,%21,%22,%23,%24,%25,%26,%27,%28,%29,%30,%31,%32,%33,%34,%35,%36,%37,%38,%39,%40,%41,%42,%43,%44,%45,%46,%47,%48,%49,%50,%51,%52,%53,%54,%55,%56,%57,%58,%59,%60,%61,%62,%63}, %64, %65, 1, 1, 1, 0, 1;\n"
        : "+f"(d[OFF + 0]), "+f"(d[OFF + 1]), "+f"(d[OFF + 2]), "+f"(d[OFF + 3]), "+f"(d[OFF + 4]), "+f"(d[OFF + 5]), "+f"(d[OFF + 6]), "+f"(d[OFF + 7]), "+f"(d[OFF + 8]), "+f"(d[OFF + 9]), "+f"(d[OFF + 10]), "+f"(d[OFF + 11]), "+f"(d[OFF + 12]), "+f"(d[OFF + 13]), "+f"(d[OFF + 14]), "+f"(d[OFF + 15]), "+f"(d[OFF + 16]), "+f"(d[OFF + 17]), "+f"(d[OFF + 18]), "+f"(d[OFF + 19]), "+f"(d[OFF + 20]), "+f"(d[OFF + 21]), "+f"(d[OFF + 22]), "+f"(d[OFF + 23]), "+f"(d[OFF + 24]), "+f"(d[OFF + 25]), "+f"(d[OFF + 26]), "+f"(d[OFF + 27]), "+f"(d[OFF + 28]), "+f"(d[OFF + 29]), "+f"(d[OFF + 30]), "+f"(d[OFF + 31]), "+f"(d[OFF + 32]), "+f"(d[OFF + 33]), "+f"(d[OFF + 34]), "+f"(d[OFF + 35]), "+f"(d[OFF + 36]), "+f"(d[OFF + 37]), "+f"(d[OFF + 38]), "+f"(d[OFF + 39]), "+f"(d[OFF + 40]), "+f"(d[OFF + 41]), "+f"(d[OFF + 42]), "+f"(d[OFF + 43]), "+f"(d[OFF + 44]), "+f"(d[OFF + 45]), "+f"(d[OFF + 46]), "+f"(d[OFF + 47]), "+f"(d[OFF + 48]), "+f"(d[OFF + 49]), "+f"(d[OFF + 50]), "+f"(d[OFF + 51]), "+f"(d[OFF + 52]), "+f"(d[OFF + 53]), "+f"(d[OFF + 54]), "+f"(d[OFF + 55]), "+f"(d[OFF + 56]), "+f"(d[OFF + 57]), "+f"(d[OFF + 58]), "+f"(d[OFF + 59]), "+f"(d[OFF + 60]), "+f"(d[OFF + 61]), "+f"(d[OFF + 62]), "+f"(d[OFF + 63])
        : "l"(da), "l"(db));
}
__device__ __forceinline__ void stsm4(uint32_t addr, uint32_t r0, uint32_t r1, uint32_t r2, uint32_t r3) {
    asm volatile("stmatrix.sync.aligned.m8n8.x4.shared.b16 [%0], {%1,%2,%3,%4};" :: "r"(addr), "r"(r0), "r"(r1), "r"(r2), "r"(r3) : "memory");
}

#define AX_BAR   0
#define NST_G 4
#define AX_EMPTY (AX_BAR + 16 + 8 * NST_G)
#define AX_DATA  1024
#define AX_UNIT  28672
#define AX_STAGE 57344
#define AX_TOTAL (AX_DATA + 8 * AX_UNIT)

__device__ __forceinline__ void attn_compute(unsigned char* smem, uint32_t sb, uint32_t buf, int warp, int lane);
__device__ __forceinline__ void attn_producer(unsigned char* smem, int hg, unsigned epoch) {
    const uint32_t sb = smem_u32(smem);
    const int lane = threadIdx.x & 31;
    {
        for (int s = 0; s < NSEG; s++) {
            const uint32_t buf = AX_DATA + (s & 1) * (4 * AX_UNIT), bar = sb + AX_BAR + 8 * (s & 1);
            if (lane < 4) wait_counter(&g_flag[s][4 * hg + lane], (epoch + 1) * 3u);
            if (lane == 4) mbar_wait_sleep(sb + AX_EMPTY + 8 * (s & 1), ((s >> 1) & 1) ^ 1);
            __syncwarp();
            if (lane == 0) mbar_expect_tx(bar, 4 * AX_UNIT);
            __syncwarp();
            if (lane < 24) {
                fence_async_all();
                const int u = lane / 6, r = lane % 6, hf = r & 1, kind = r >> 1;
                const uint32_t ub = sb + buf + u * AX_UNIT;
                const size_t img = ((size_t)(s * NH + 4 * hg + u) * 2) + hf;
                if (kind == 0) bulk_g2s(ub + hf * 4096, g_Qimg + img * 2048, 4096, bar);
                else if (kind == 1) bulk_g2s(ub + 8192 + hf * 5120, g_Kimg + img * 2560, 5120, bar);
                else bulk_g2s(ub + 18432 + hf * 5120, g_Vimg + img * 2560, 5120, bar);
            }
            __syncwarp();
        }
    }
}
__device__ __forceinline__ void attn_loop(unsigned char* smem, int hg, unsigned epoch) {
    const uint32_t sb = smem_u32(smem);
    const int tid = threadIdx.x, warp = tid >> 5, lane = tid & 31;
    for (int s = 0; s < NSEG; s++) {
        const uint32_t buf = AX_DATA + (s & 1) * (4 * AX_UNIT), bar = sb + AX_BAR + 8 * (s & 1);
        mbar_wait_sleep(bar, (s >> 1) & 1);
        if (s >= 36) ATR(2 + 2 * (s - 36));
        attn_compute(smem, sb, buf, warp, lane);
        if (s >= 36) ATR(3 + 2 * (s - 36));
        fence_async();
        __syncwarp();
        if (lane == 0) mbar_arrive(sb + AX_EMPTY + 16 + 8 * (s & 1));
    }
}
__device__ __forceinline__ void attn_storer(unsigned char* smem, int hg) {
    const uint32_t sb = smem_u32(smem);
    const int lane = threadIdx.x & 31;
    for (int s = 0; s < NSEG; s++) {
        const uint32_t buf = AX_DATA + (s & 1) * (4 * AX_UNIT);
        mbar_wait_sleep(sb + AX_EMPTY + 16 + 8 * (s & 1), (s >> 1) & 1);
        if (lane < 8) {
            const int uu = lane >> 1, hf = lane & 1, hh = 4 * hg + uu;
            bulk_s2g(g_Oimg + (((size_t)(s >> 2) * 64 + hh * 2 + hf) * 128 + (s & 3) * 32) * 64, sb + buf + uu * AX_UNIT + hf * 4096, 4096);
            bulk_commit();
            bulk_wait_read0();
            mbar_arrive(sb + AX_EMPTY + 8 * (s & 1));
            bulk_wait0();
            fence_async_all();
            __threadfence();
            atomicAdd(&g_ocnt[s >> 1], 1u);
        }
        __syncwarp();
    }
}
__device__ __forceinline__ void attn_compute(unsigned char* smem, uint32_t sb, uint32_t buf, int warp, int lane) {
    const int g = lane >> 2, t = lane & 3;
    const int u = warp >> 1, qh = warp & 1;
    const uint32_t ub = sb + buf + u * AX_UNIT;
    float sc[5][4];
    #pragma unroll
    for (int j = 0; j < 5; j++) { sc[j][0] = sc[j][1] = sc[j][2] = sc[j][3] = 0.f; }
    #pragma unroll
    for (int ks = 0; ks < 8; ks++) {
        const int hf = ks >> 2, c0 = (ks & 3) * 2;
        uint32_t a[4];
        { int mi = lane >> 3, row = 16 * qh + (mi & 1) * 8 + (lane & 7), chunk = c0 + (mi >> 1);
          ldsm4(a, ub + hf * 4096 + row * 128 + ((chunk ^ (row & 7)) << 4)); }
        #pragma unroll
        for (int jp = 0; jp < 3; jp++) {
            uint32_t b[4];
            int mi = lane >> 3, nt = 2 * jp + (mi >> 1); if (nt > 4) nt = 4;
            int row = 8 * nt + (lane & 7), chunk = c0 + (mi & 1);
            ldsm4(b, ub + 8192 + hf * 5120 + row * 128 + ((chunk ^ (row & 7)) << 4));
            mma_bf16(sc[2 * jp], a[0], a[1], a[2], a[3], b[0], b[1]);
            if (jp < 2) mma_bf16(sc[2 * jp + 1], a[0], a[1], a[2], a[3], b[2], b[3]);
        }
    }
    uint32_t pa[3][4];
    {
        const float sc2 = 0.08838834764831845f * 1.4426950408889634f;
        float mx0 = -3.0e38f, mx1 = -3.0e38f;
        const int q0 = 16 * qh + g, q1 = q0 + 8;
        #pragma unroll
        for (int j = 0; j < 5; j++)
            #pragma unroll
            for (int e = 0; e < 2; e++) {
                int key = 8 * j + 2 * t + e - 8;
                sc[j][e] = (key <= q0) ? sc[j][e] * sc2 : -3.0e38f;
                sc[j][2 + e] = (key <= q1) ? sc[j][2 + e] * sc2 : -3.0e38f;
                mx0 = fmaxf(mx0, sc[j][e]); mx1 = fmaxf(mx1, sc[j][2 + e]);
            }
        mx0 = fmaxf(mx0, __shfl_xor_sync(~0u, mx0, 1)); mx0 = fmaxf(mx0, __shfl_xor_sync(~0u, mx0, 2));
        mx1 = fmaxf(mx1, __shfl_xor_sync(~0u, mx1, 1)); mx1 = fmaxf(mx1, __shfl_xor_sync(~0u, mx1, 2));
        float s0 = 0.f, s1 = 0.f;
        #pragma unroll
        for (int j = 0; j < 5; j++)
            #pragma unroll
            for (int e = 0; e < 2; e++) {
                sc[j][e] = ex2_approx(sc[j][e] - mx0); sc[j][2 + e] = ex2_approx(sc[j][2 + e] - mx1);
                s0 += sc[j][e]; s1 += sc[j][2 + e];
            }
        s0 += __shfl_xor_sync(~0u, s0, 1); s0 += __shfl_xor_sync(~0u, s0, 2);
        s1 += __shfl_xor_sync(~0u, s1, 1); s1 += __shfl_xor_sync(~0u, s1, 2);
        const float i0 = __frcp_rn(s0), i1 = __frcp_rn(s1);
        #pragma unroll
        for (int k = 0; k < 3; k++) {
            pa[k][0] = pack_bf16(sc[2 * k][0] * i0, sc[2 * k][1] * i0);
            pa[k][1] = pack_bf16(sc[2 * k][2] * i1, sc[2 * k][3] * i1);
            if (k < 2) { pa[k][2] = pack_bf16(sc[2 * k + 1][0] * i0, sc[2 * k + 1][1] * i0); pa[k][3] = pack_bf16(sc[2 * k + 1][2] * i1, sc[2 * k + 1][3] * i1); }
            else { pa[k][2] = 0u; pa[k][3] = 0u; }
        }
    }
    __syncwarp();
    nbar_sync(5 + u, 64);
    #pragma unroll
    for (int np = 0; np < 8; np++) {
        const int hf = np >> 2, c0 = (np & 3) * 2;
        float o0[4] = {0, 0, 0, 0}, o1[4] = {0, 0, 0, 0};
        #pragma unroll
        for (int k = 0; k < 3; k++) {
            uint32_t b[4];
            int mi = lane >> 3;
            int row = 16 * k + (mi & 1) * 8 + (lane & 7); if (row > 39) row = 39 - 7 + (lane & 7);
            int chunk = c0 + (mi >> 1);
            ldsm4t(b, ub + 18432 + hf * 5120 + row * 128 + ((chunk ^ (row & 7)) << 4));
            mma_bf16(o0, pa[k][0], pa[k][1], pa[k][2], pa[k][3], b[0], k < 2 ? b[1] : 0u);
            mma_bf16(o1, pa[k][0], pa[k][1], pa[k][2], pa[k][3], b[2], k < 2 ? b[3] : 0u);
        }
        int mi = lane >> 3, row = 16 * qh + (mi & 1) * 8 + (lane & 7), chunk = c0 + (mi >> 1);
        stsm4(ub + hf * 4096 + row * 128 + ((chunk ^ (row & 7)) << 4), pack_bf16(o0[0], o0[1]), pack_bf16(o0[2], o0[3]), pack_bf16(o1[0], o1[1]), pack_bf16(o1[2], o1[3]));
    }
}

template <int V> struct IntC { static constexpr int value = V; };
struct Task { int type, rb, c, k0, nch, plane; };
#define NFINE 30
#define NGEMM (8 + 144 + 8 * 2 + 4 + 8 * 6 + 26 * 2 + 16 * 2)
__device__ __forceinline__ Task decode_task(int j) {
    Task t; t.type = 0; t.rb = 0; t.c = 0; t.k0 = 0; t.nch = 16; t.plane = 0;
    auto H = [&](int rb, int i) { t.type = 1; t.rb = rb; t.c = i & 1; t.plane = i >> 1; t.k0 = t.plane * 16; };
    auto CF = [&](int rb, int i) { t.type = 2; t.rb = rb; t.c = i & 1; t.k0 = rb * 64 + (i >> 1) * 16; t.nch = 16; };
    auto H13 = [&](int rb, int i) { t.type = 1; t.rb = rb; t.c = i & 1; t.plane = i >> 1; t.k0 = t.plane * 5; t.nch = (t.plane == 12) ? 4 : 5; };
    auto C13 = [&](int rb, int i) { t.type = 2; t.rb = rb; t.c = i & 1; t.k0 = rb * 64 + (i >> 1) * 8; t.nch = 8; };
    if (j >= NGEMM) { t.type = 3; return t; }
    if (j < 8) { t.c = j & 1; t.plane = j >> 1; t.k0 = t.plane * 16; return t; }
    j -= 8;
    if (j < 144) {
        const int q = j / 12, r = j % 12;
        if (r < 8) { t.rb = 2 * (q + 1); t.c = r & 1; t.plane = r >> 1; t.k0 = t.plane * 16; }
        else { t.type = 2; t.rb = 2 * q + ((r - 8) >> 1); t.c = r & 1; t.k0 = t.rb * 64; t.nch = 64; }
        return t;
    }
    j -= 144;
    if (j < 8) { H(26, j); return t; }
    j -= 8;
    if (j < 8) { H(27, j); return t; }
    j -= 8;
    if (j < 4) { t.type = 2; t.rb = 24 + (j >> 1); t.c = j & 1; t.k0 = t.rb * 64; t.nch = 64; return t; }
    j -= 4;
    if (j < 8) { H(28, j); return t; }
    j -= 8;
    if (j < 8) { CF(26, j); return t; }
    j -= 8;
    if (j < 8) { H(29, j); return t; }
    j -= 8;
    if (j < 8) { CF(27, j); return t; }
    j -= 8;
    if (j < 26) { H13(30, j); return t; }
    j -= 26;
    if (j < 8) { CF(28, j); return t; }
    j -= 8;
    if (j < 8) { CF(29, j); return t; }
    j -= 8;
    if (j < 26) { H13(31, j); return t; }
    j -= 26;
    if (j < 16) { C13(30, j); return t; }
    j -= 16;
    C13(31, j);
    return t;
}
__device__ __forceinline__ void gemm_producer(unsigned char* smem, const CUtensorMap* womap, unsigned epoch, volatile int* s_tasks) {
    const uint32_t sb = smem_u32(smem);
    uint32_t st = 0, ph = 1;
    for (int n = 0;; n++) {
        const int j = (int)(atomicAdd(&g_gemmctr, 1u) - epoch * (unsigned)(NGEMM + NAUX - NATT));
        const Task t = decode_task(j);
        if (t.type <= 1) {
            wait_counter(&g_ocnt[t.rb], (epoch + 1) * 128u);
            if (t.type == 0) wait_counter(&g_ocnt[t.rb + 1], (epoch + 1) * 128u);
            fence_async_all();
        } else if (t.type == 2) {
            wait_counter(&g_gcnt[t.rb][t.c], (epoch + 1) * (t.rb >= NFINE ? 13u : 4u));
            wait_counter(&g_ssmcnt, (epoch + 1) * 80u);
        }
        const int nch = (t.type <= 1) ? t.nch : 1;
        for (int kc = 0; kc < nch; kc++) {
            mbar_wait_sleep(sb + AX_EMPTY + 8 * st, ph);
            const uint32_t a = sb + AX_DATA + st * AX_STAGE, bar = sb + AX_BAR + 16 + 8 * st;
            if (kc == 0) s_tasks[n & 7] = j;
            if (t.type > 1) mbar_arrive(bar);
            else {
                const bf16* asrc = g_Oimg + ((size_t)(t.rb >> 1) * 64 + t.k0 + kc) * 8192 + (t.rb & 1) * 4096;
                if (t.type == 0) { mbar_expect_tx(bar, AX_STAGE); bulk_g2s(a, asrc, 8192, bar); bulk_g2s(a + 8192, asrc + 4096, 8192, bar); }
                else { mbar_expect_tx(bar, AX_STAGE - 8192); bulk_g2s(a, asrc, 8192, bar); }
                #pragma unroll
                for (int b = 0; b < 5; b++) tma_load_2d(a + 16384 + b * 8192, womap, t.c * 320 + b * 64, (t.k0 + kc) * 64, bar);
            }
            if (++st == NST_G) { st = 0; ph ^= 1; }
        }
        if (t.type == 3) break;
    }
}
__device__ __forceinline__ void gemm_signaller(volatile int* s_done) {
    for (int n = 0;; n++) {
        nbar_sync(2, 288);
        const int j = s_done[n & 7];
        if (j < 0) break;
        if ((threadIdx.x & 31) == 0) {
            const Task t = decode_task(j);
            __threadfence();
            atomicAdd(&g_gcnt[t.rb][t.c], 1u);
            if (t.type == 0) atomicAdd(&g_gcnt[t.rb + 1][t.c], 1u);
        }
        __syncwarp();
    }
}
__device__ __forceinline__ void gemm_consumer(unsigned char* smem, bf16* __restrict__ out, volatile int* s_tasks, volatile int* s_done) {
    const uint32_t sb = smem_u32(smem);
    const int tid = threadIdx.x, lane = tid & 31;
    const int wg = __shfl_sync(~0u, tid >> 7, 0), warp = __shfl_sync(~0u, (tid >> 5) & 3, 0);
    uint32_t st = 0, ph = 0;
    int ndone = 0;
    for (int n = 0;; n++) {
        mbar_wait_sleep(sb + AX_BAR + 16 + 8 * st, ph);
        const Task t = decode_task(__shfl_sync(~0u, s_tasks[n & 7], 0));
        if (t.type > 1) {
            nbar_sync(1, 256);
            if ((tid & 127) == 0) mbar_arrive(sb + AX_EMPTY + 8 * st);
            if (++st == NST_G) { st = 0; ph ^= 1; }
            if (t.type == 3) break;
            const int np = (t.rb >= NFINE) ? 13 : 4;
            const float* pbase = (t.rb >= NFINE) ? g_part31 + (size_t)(t.rb - NFINE) * 13 * 64 * DM - (size_t)t.rb * 64 * DM : g_part;
            const size_t pstride = (t.rb >= NFINE) ? (size_t)64 * DM : (size_t)SEQ * DM;
            auto combine = [&](int i, auto NP) {
                const int r = t.k0 + i / 80, cc = t.c * 320 + (i % 80) * 4;
                float4 v[NP.value];
                #pragma unroll
                for (int q = 0; q < NP.value; q++) v[q] = __ldcg(reinterpret_cast<const float4*>(pbase + q * pstride + (size_t)r * DM + cc));
                const float gt = __ldcg(g_g + r);
                const uint2 bb = __ldcg(reinterpret_cast<const uint2*>(g_b + (size_t)r * DM + cc));
                float4 a = v[0];
                #pragma unroll
                for (int q = 1; q < NP.value; q++) { a.x += v[q].x; a.y += v[q].y; a.z += v[q].z; a.w += v[q].w; }
                const float b0 = __uint_as_float(bb.x << 16), b1 = __uint_as_float(bb.x & 0xffff0000u), b2 = __uint_as_float(bb.y << 16), b3 = __uint_as_float(bb.y & 0xffff0000u);
                uint2 o; o.x = pack_bf16(gt * a.x + (1.f - gt) * b0, gt * a.y + (1.f - gt) * b1); o.y = pack_bf16(gt * a.z + (1.f - gt) * b2, gt * a.w + (1.f - gt) * b3);
                *reinterpret_cast<uint2*>(out + (size_t)r * DM + cc) = o;
            };
            if (np == 4) {
                const int nit = t.nch * 80 / 256;
                for (int it0 = 0; it0 < nit; it0 += 5) {
                    #pragma unroll
                    for (int it = 0; it < 5; it++) combine(tid + 256 * (it0 + it), IntC<4>());
                }
            } else {
                #pragma unroll
                for (int it = 0; it < 3; it++) { const int i = tid + 256 * it; if (i < 640) combine(i, IntC<13>()); }
            }
            if (n < 56) ATRID(6 + n, s_tasks[n & 7]);
            continue;
        }
        const int g = lane >> 2, tq = lane & 3;
        if (t.type == 0) {
            float acc[160];
            #pragma unroll
            for (int i = 0; i < 160; i++) acc[i] = 0.f;
            uint32_t prev = 0;
            for (int kc = 0; kc < 16; kc++) {
                mbar_wait(sb + AX_BAR + 16 + 8 * st, ph);
                const uint32_t a = sb + AX_DATA + st * AX_STAGE;
                const uint64_t da = make_desc(a + wg * 8192, 16, 1024), db = make_desc(a + 16384, 8192, 1024);
                wg_fence();
                #pragma unroll
                for (int ks = 0; ks < 4; ks++) {
                    wgmma_n192_tB<0>(acc, da + ks * 2, db + ks * 128);
                    wgmma_n128_tB<96>(acc, da + ks * 2, db + ks * 128 + 3 * 512);
                }
                wg_commit();
                asm volatile("wgmma.wait_group.sync.aligned 1;" ::: "memory");
                if (kc > 0 && (tid & 127) == 0) mbar_arrive(sb + AX_EMPTY + 8 * prev);
                prev = st;
                if (++st == NST_G) { st = 0; ph ^= 1; }
            }
            wg_wait0();
            if ((tid & 127) == 0) mbar_arrive(sb + AX_EMPTY + 8 * prev);
            float* base = g_part + ((size_t)t.plane * SEQ + t.rb * 64 + wg * 64 + warp * 16 + g) * DM + t.c * 320 + 2 * tq;
            #pragma unroll
            for (int q = 0; q < 40; q++) {
                *reinterpret_cast<float2*>(base + q * 8) = make_float2(acc[4 * q], acc[4 * q + 1]);
                *reinterpret_cast<float2*>(base + 8 * DM + q * 8) = make_float2(acc[4 * q + 2], acc[4 * q + 3]);
            }
        } else {
            float* base = (t.rb >= NFINE ? g_part31 + (size_t)((t.rb - NFINE) * 13 + t.plane) * 64 * DM : g_part + ((size_t)t.plane * SEQ + t.rb * 64) * DM) + (size_t)(warp * 16 + g) * DM + t.c * 320 + 2 * tq;
            if (wg == 0) {
                float acc[160];
                #pragma unroll
                for (int i = 0; i < 96; i++) acc[i] = 0.f;
                uint32_t prev = 0;
                for (int kc = 0; kc < t.nch; kc++) {
                    mbar_wait(sb + AX_BAR + 16 + 8 * st, ph);
                    const uint32_t a = sb + AX_DATA + st * AX_STAGE;
                    const uint64_t da = make_desc(a, 16, 1024), db = make_desc(a + 16384, 8192, 1024);
                    wg_fence();
                    #pragma unroll
                    for (int ks = 0; ks < 4; ks++) wgmma_n192_tB<0>(acc, da + ks * 2, db + ks * 128);
                    wg_commit();
                    asm volatile("wgmma.wait_group.sync.aligned 1;" ::: "memory");
                    if (kc > 0 && (tid & 127) == 0) mbar_arrive(sb + AX_EMPTY + 8 * prev);
                    prev = st;
                    if (++st == NST_G) { st = 0; ph ^= 1; }
                }
                wg_wait0();
                if ((tid & 127) == 0) mbar_arrive(sb + AX_EMPTY + 8 * prev);
                #pragma unroll
                for (int q = 0; q < 24; q++) {
                    *reinterpret_cast<float2*>(base + q * 8) = make_float2(acc[4 * q], acc[4 * q + 1]);
                    *reinterpret_cast<float2*>(base + 8 * DM + q * 8) = make_float2(acc[4 * q + 2], acc[4 * q + 3]);
                }
            } else {
                float acc[160];
                #pragma unroll
                for (int i = 96; i < 160; i++) acc[i] = 0.f;
                uint32_t prev = 0;
                for (int kc = 0; kc < t.nch; kc++) {
                    mbar_wait(sb + AX_BAR + 16 + 8 * st, ph);
                    const uint32_t a = sb + AX_DATA + st * AX_STAGE;
                    const uint64_t da = make_desc(a, 16, 1024), db = make_desc(a + 16384, 8192, 1024);
                    wg_fence();
                    #pragma unroll
                    for (int ks = 0; ks < 4; ks++) wgmma_n128_tB<96>(acc, da + ks * 2, db + ks * 128 + 3 * 512);
                    wg_commit();
                    asm volatile("wgmma.wait_group.sync.aligned 1;" ::: "memory");
                    if (kc > 0 && (tid & 127) == 0) mbar_arrive(sb + AX_EMPTY + 8 * prev);
                    prev = st;
                    if (++st == NST_G) { st = 0; ph ^= 1; }
                }
                wg_wait0();
                if ((tid & 127) == 0) mbar_arrive(sb + AX_EMPTY + 8 * prev);
                #pragma unroll
                for (int q = 24; q < 40; q++) {
                    *reinterpret_cast<float2*>(base + q * 8) = make_float2(acc[4 * q], acc[4 * q + 1]);
                    *reinterpret_cast<float2*>(base + 8 * DM + q * 8) = make_float2(acc[4 * q + 2], acc[4 * q + 3]);
                }
            }
        }
        if (tid == 0) s_done[ndone & 7] = s_tasks[n & 7];
        ndone++;
        nbar_arrive(2, 288);
        if (n < 56) ATRID(6 + n, s_tasks[n & 7]);
    }
    if (tid == 0) s_done[ndone & 7] = -1;
    nbar_arrive(2, 288);
}

__global__ void __launch_bounds__(384, 1)
k_aux(const __grid_constant__ CUtensorMap womap, const bf16* __restrict__ x, const bf16* __restrict__ A_re, const bf16* __restrict__ A_im,
      const bf16* __restrict__ B_re, const bf16* __restrict__ B_im, const bf16* __restrict__ C_re, const bf16* __restrict__ C_im,
      const bf16* __restrict__ log_dt, const bf16* __restrict__ Dskip, const bf16* __restrict__ gw, bf16* __restrict__ out) {
    extern __shared__ __align__(1024) unsigned char smem[];
    const uint32_t sb = smem_u32(smem);
    const int tid = threadIdx.x, warp = tid >> 5, lane = tid & 31;
    __shared__ unsigned s_epoch;
    __shared__ int s_task, s_tasks[8], s_done[8];
    if (tid == 0) {
        for (int i = 0; i < 2 + NST_G; i++) mbar_init(sb + AX_BAR + 8 * i, 1);
        for (int i = 0; i < NST_G; i++) mbar_init(sb + AX_EMPTY + 8 * i, blockIdx.x < NATT ? 8 : 2);
        asm volatile("fence.mbarrier_init.release.cluster;" ::: "memory");
        s_epoch = *reinterpret_cast<volatile unsigned*>(&g_epoch);
    }
    __syncthreads();
    const unsigned epoch = s_epoch;
    ATR(0);
    const int wg = __shfl_sync(~0u, tid >> 7, 0);
    if (wg == 2) {
        asm volatile("setmaxnreg.dec.sync.aligned.u32 40;");
        if (blockIdx.x < NATT) { if (warp == 8) attn_producer(smem, blockIdx.x, epoch); else if (warp == 9) attn_storer(smem, blockIdx.x); }
        else {
            nbar_sync(3, 384);
            if (warp == 8) { if (lane == 0) gemm_producer(smem, &womap, epoch, s_tasks); }
            else if (warp == 9) gemm_signaller(s_done);
        }
        __syncwarp();
        nbar_sync(4, 384);
    } else {
        asm volatile("setmaxnreg.inc.sync.aligned.u32 232;");
        if (blockIdx.x < NATT) attn_loop(smem, blockIdx.x, epoch);
        else {
            int ntask = 0;
            for (;;) {
                nbar_sync(1, 256);
                if (tid == 0) s_task = (int)(atomicAdd(&g_taskctr, 1u) - epoch * (unsigned)(80 + NAUX - NATT));
                nbar_sync(1, 256);
                const int task = s_task;
                if (task >= 80) break;
                for (int r = task * 26 + warp; r < min(SEQ, task * 26 + 26); r += 8) {
                    float sum = 0.f;
                    for (int i = lane * 2; i < DM; i += 64) {
                        __nv_bfloat162 xv = *reinterpret_cast<const __nv_bfloat162*>(x + (size_t)r * DM + i), wv = *reinterpret_cast<const __nv_bfloat162*>(gw + i);
                        sum += bf2f(xv.x) * bf2f(wv.x) + bf2f(xv.y) * bf2f(wv.y);
                    }
                    #pragma unroll
                    for (int o = 16; o; o >>= 1) sum += __shfl_xor_sync(~0u, sum, o);
                    if (lane == 0) g_g[r] = 1.f / (1.f + expf(-sum));
                }
                ssm_group(smem + AX_DATA, task, x, A_re, A_im, B_re, B_im, C_re, C_im, log_dt, Dskip);
                nbar_sync(1, 256);
                if (tid == 0) { __threadfence(); atomicAdd(&g_ssmcnt, 1u); }
                if (ntask < 4) ATR(2 + ntask);
                ntask++;
            }
            fence_async();
            nbar_sync(3, 384);
            gemm_consumer(smem, out, s_tasks, s_done);
        }
        nbar_sync(4, 384);
        if (tid == 0) {
            __threadfence();
            unsigned old = atomicAdd(&g_auxdone, 1u);
            if (old == NAUX - 1) { g_auxdone = 0; __threadfence(); atomicAdd(&g_epoch, 1u); }
        }
    }
    asm volatile("griddepcontrol.wait;" ::: "memory");
}

extern "C" void kernel_launch(void* const* d_in, const int* in_sizes, int n_in, void* d_out, int out_size) {
    const bf16* x = (const bf16*)d_in[0];
    const bf16* mem0 = (const bf16*)d_in[1];
    const bf16* Wq = (const bf16*)d_in[2];
    const bf16* Wk = (const bf16*)d_in[3];
    const bf16* Wv = (const bf16*)d_in[4];
    const bf16* Wo = (const bf16*)d_in[5];
    const bf16 *A_re = (const bf16*)d_in[8], *A_im = (const bf16*)d_in[9], *B_re = (const bf16*)d_in[10], *B_im = (const bf16*)d_in[11];
    const bf16 *C_re = (const bf16*)d_in[12], *C_im = (const bf16*)d_in[13], *log_dt = (const bf16*)d_in[14], *Dskip = (const bf16*)d_in[15];
    const bf16* gw = (const bf16*)d_in[16];
    bf16* out = (bf16*)d_out;
    cudaStream_t st = cudaStreamPerThread;
    static bool init = false;
    static CUtensorMap xmap, womap, wqmap, wkmap, wvmap;
    static const void* xmap_ptr = nullptr; static const void* womap_ptr = nullptr; static const void* w_ptr[3] = {nullptr, nullptr, nullptr};
    if (!init) {
        cudaFuncSetAttribute(k_chain, cudaFuncAttributeMaxDynamicSharedMemorySize, SM_TOTAL);
        cudaFuncSetAttribute(k_aux, cudaFuncAttributeMaxDynamicSharedMemorySize, AX_TOTAL);
        init = true;
    }
    if (xmap_ptr != (const void*)x || womap_ptr != (const void*)Wo || w_ptr[0] != Wq || w_ptr[1] != Wk || w_ptr[2] != Wv) {
        void* fn = nullptr; cudaDriverEntryPointQueryResult qres;
        cudaGetDriverEntryPoint("cuTensorMapEncodeTiled", &fn, cudaEnableDefault, &qres);
        typedef CUresult (*EncFn)(CUtensorMap*, CUtensorMapDataType, cuuint32_t, void*, const cuuint64_t*, const cuuint64_t*, const cuuint32_t*, const cuuint32_t*,
                                  CUtensorMapInterleave, CUtensorMapSwizzle, CUtensorMapL2promotion, CUtensorMapFloatOOBfill);
        cuuint32_t es[2] = {1, 1};
        {
          cuuint64_t dims[3] = {64, SEQ, 10}; cuuint64_t strides[2] = {DM * 2, 128}; cuuint32_t box[3] = {64, 32, 10}; cuuint32_t es3[3] = {1, 1, 1};
          ((EncFn)fn)(&xmap, CU_TENSOR_MAP_DATA_TYPE_BFLOAT16, 3, (void*)x, dims, strides, box, es3, CU_TENSOR_MAP_INTERLEAVE_NONE, CU_TENSOR_MAP_SWIZZLE_128B,
                      CU_TENSOR_MAP_L2_PROMOTION_L2_128B, CU_TENSOR_MAP_FLOAT_OOB_FILL_NONE); }
        { cuuint64_t dims[2] = {DM, HD}; cuuint64_t strides[1] = {DM * 2}; cuuint32_t box[2] = {64, 64};
          ((EncFn)fn)(&womap, CU_TENSOR_MAP_DATA_TYPE_BFLOAT16, 2, (void*)Wo, dims, strides, box, es, CU_TENSOR_MAP_INTERLEAVE_NONE, CU_TENSOR_MAP_SWIZZLE_128B,
                      CU_TENSOR_MAP_L2_PROMOTION_L2_128B, CU_TENSOR_MAP_FLOAT_OOB_FILL_NONE); }
        { cuuint64_t dims[2] = {HD, DM}; cuuint64_t strides[1] = {HD * 2}; cuuint32_t box[2] = {64, 128};
          const bf16* ws[3] = {Wq, Wk, Wv}; CUtensorMap* ms[3] = {&wqmap, &wkmap, &wvmap};
          for (int i = 0; i < 3; i++)
              ((EncFn)fn)(ms[i], CU_TENSOR_MAP_DATA_TYPE_BFLOAT16, 2, (void*)ws[i], dims, strides, box, es, CU_TENSOR_MAP_INTERLEAVE_NONE, CU_TENSOR_MAP_SWIZZLE_128B,
                          CU_TENSOR_MAP_L2_PROMOTION_L2_128B, CU_TENSOR_MAP_FLOAT_OOB_FILL_NONE); }
        xmap_ptr = (const void*)x; womap_ptr = (const void*)Wo; w_ptr[0] = Wq; w_ptr[1] = Wk; w_ptr[2] = Wv;
    }
    k_chain<<<96, 384, SM_TOTAL, st>>>(xmap, wqmap, wkmap, wvmap, womap, x, mem0);
    {
        cudaLaunchConfig_t cfg = {};
        cfg.gridDim = dim3(NAUX); cfg.blockDim = dim3(384); cfg.dynamicSmemBytes = AX_TOTAL; cfg.stream = st;
        cudaLaunchAttribute at[1];
        at[0].id = cudaLaunchAttributeProgrammaticStreamSerialization; at[0].val.programmaticStreamSerializationAllowed = 1;
        cfg.attrs = at; cfg.numAttrs = 1;
        cudaLaunchKernelEx(&cfg, k_aux, womap, x, A_re, A_im, B_re, B_im, C_re, C_im, log_dt, Dskip, gw, out);
    }
}
```

```cpp
#include <cuda_runtime.h>
#include <cuda_bf16.h>
#include <stdint.h>
#include <cuda.h>

typedef __nv_bfloat16 bf16;

#define SEQ 2048
#define DM 640
#define NH 32
#define DH 128
#define NM 8
#define SEG 32
#define NSEG 64
#define NST 128
#define HD 4096

__device__ bf16  g_b[SEQ * DM];
__device__ float g_g[SEQ];

__device__ __forceinline__ float bf2f(bf16 v) { return __bfloat162float(v); }
__device__ __forceinline__ uint32_t pack_bf16(float lo, float hi) {
    uint32_t r; asm("cvt.rn.bf16x2.f32 %0, %1, %2;" : "=r"(r) : "f"(hi), "f"(lo)); return r;
}
__device__ __forceinline__ uint32_t f2tf32(float x) { uint32_t r; asm("cvt.rna.tf32.f32 %0, %1;" : "=r"(r) : "f"(x)); return r; }
__device__ __forceinline__ void mma_tf32(float (&d)[4], uint32_t a0, uint32_t a1, uint32_t a2, uint32_t a3, uint32_t b0, uint32_t b1) {
    asm volatile("mma.sync.aligned.m16n8k8.row.col.f32.tf32.tf32.f32 {%0,%1,%2,%3}, {%4,%5,%6,%7}, {%8,%9}, {%0,%1,%2,%3};\n"
        : "+f"(d[0]), "+f"(d[1]), "+f"(d[2]), "+f"(d[3]) : "r"(a0), "r"(a1), "r"(a2), "r"(a3), "r"(b0), "r"(b1));
}
__device__ __forceinline__ void mma_bf16(float (&d)[4], uint32_t a0, uint32_t a1, uint32_t a2, uint32_t a3, uint32_t b0, uint32_t b1) {
    asm volatile("mma.sync.aligned.m16n8k16.row.col.f32.bf16.bf16.f32 {%0,%1,%2,%3}, {%4,%5,%6,%7}, {%8,%9}, {%0,%1,%2,%3};\n"
        : "+f"(d[0]), "+f"(d[1]), "+f"(d[2]), "+f"(d[3]) : "r"(a0), "r"(a1), "r"(a2), "r"(a3), "r"(b0), "r"(b1));
}
struct cf { float re, im; };
__device__ __forceinline__ cf cmul(cf a, cf b) { cf r; r.re = a.re * b.re - a.im * b.im; r.im = a.re * b.im + a.im * b.re; return r; }
__device__ __forceinline__ cf csq(cf a) { cf r; r.re = a.re * a.re - a.im * a.im; r.im = 2.f * a.re * a.im; return r; }
__device__ __forceinline__ cf cexpL(float zr, float zi, float L) {
    float e = __expf(zr * L);
    float ang = zi * L;
    float k = rintf(ang * 0.15915494309189535f);
    ang = fmaf(-k, 6.2831854820251465f, ang);
    ang = fmaf(-k, -1.7484555314695172e-07f, ang);
    cf r; r.re = e * __cosf(ang); r.im = e * __sinf(ang); return r;
}

#define SSM_CH 8
#define KC_PITCH 648
#define XS_PAD 128
#define XS_PITCH (XS_PAD + 2048 + 8)
#define YS_PITCH (2048 + 8)
#define KT_LEN (2048 + 48)
struct SsmSmem {
    float Kc[SSM_CH][KC_PITCH];
    bf16  xs[SSM_CH][XS_PITCH];
    union {
        bf16  KT[SSM_CH][2][KT_LEN];
        float st[SSM_CH][NST][8];
    } u;
    bf16  ys[SSM_CH][YS_PITCH];
    uint16_t kidx[2048];
};

__device__ __forceinline__ int kc_index(int l) {
    return l < 256 ? l : (l < 512 ? 256 + ((l - 256) >> 1) : (l < 1024 ? 384 + ((l - 512) >> 2) : 512 + ((l - 1024) >> 3)));
}

__device__ __forceinline__ void ssm_group(unsigned char* smem_raw, int grp, const bf16* __restrict__ x, const bf16* __restrict__ A_re, const bf16* __restrict__ A_im,
        const bf16* __restrict__ B_re, const bf16* __restrict__ B_im, const bf16* __restrict__ C_re, const bf16* __restrict__ C_im,
        const bf16* __restrict__ log_dt, const bf16* __restrict__ Dskip) {
    SsmSmem& S = *reinterpret_cast<SsmSmem*>(smem_raw);
    const int tid = threadIdx.x, w = tid >> 5, lane = tid & 31, g = lane >> 2, t = lane & 3;
    const int d0 = grp * SSM_CH;
    asm volatile("bar.sync 1, 256;" ::: "memory");
    #pragma unroll
    for (int it = 0; it < 8; it++) {
        const int l = tid + 256 * it;
        uint4 v = *reinterpret_cast<const uint4*>(x + (size_t)l * DM + d0);
        const bf16* p = reinterpret_cast<const bf16*>(&v);
        const int lr = (l & ~15) | (15 - (l & 15));
        #pragma unroll
        for (int c = 0; c < 8; c++) S.xs[c][XS_PAD + lr] = p[c];
        S.kidx[l] = (uint16_t)((int)bf2f(__float2bfloat16_rn((float)l)) == 2048 ? 640 : kc_index((int)bf2f(__float2bfloat16_rn((float)l))));
    }
    for (int i = tid; i < SSM_CH * XS_PAD / 2; i += 256) reinterpret_cast<uint32_t*>(&S.xs[i / (XS_PAD / 2)][0])[i % (XS_PAD / 2)] = 0u;
    {
        const int d = d0 + w;
        const float dt = bf2f(__float2bfloat16_rn(expf(bf2f(log_dt[d]))));
        #pragma unroll
        for (int i = 0; i < 4; i++) {
            const int n = lane + 32 * i;
            float zr = dt * bf2f(A_re[d * NST + n]), zi = dt * bf2f(A_im[d * NST + n]);
            cf dB; dB.re = dt * bf2f(B_re[d * NST + n]); dB.im = dt * bf2f(B_im[d * NST + n]);
            cf C; C.re = bf2f(C_re[d * NST + n]); C.im = bf2f(C_im[d * NST + n]);
            cf wv = cmul(C, dB);
            cf u8 = cexpL(zr, zi, 8.f), u128 = cexpL(zr, zi, 128.f);
            float* st = S.u.st[w][n];
            *reinterpret_cast<float4*>(st) = make_float4(zr, zi, wv.re, wv.im);
            *reinterpret_cast<float4*>(st + 4) = make_float4(u8.re, u8.im, u128.re, u128.im);
        }
        __syncwarp();
        float a0a[4] = {0, 0, 0, 0}, a0b[4] = {0, 0, 0, 0}, a1[4] = {0, 0, 0, 0}, a2a[4] = {0, 0, 0, 0}, a2b[4] = {0, 0, 0, 0};
        float k2048 = 0.f;
        const float Lg = (g < 4) ? (512.f + 4.f * g) : (g < 6 ? 1024.f + 8.f * (g - 4) : 1536.f + 8.f * (g - 6));
        #pragma unroll 4
        for (int kk = 0; kk < 32; kk++) {
            const float* st = S.u.st[w][4 * kk + t];
            float4 s0 = *reinterpret_cast<const float4*>(st), s1 = *reinterpret_cast<const float4*>(st + 4);
            cf wv; wv.re = s0.z; wv.im = s0.w;
            cf u8; u8.re = s1.x; u8.im = s1.y;
            cf u128; u128.re = s1.z; u128.im = s1.w;
            cf e1 = cexpL(s0.x, s0.y, (float)g);
            cf e23 = cexpL(s0.x, s0.y, Lg);
            cf e1b = cmul(e1, u8);
            cf e2 = csq(e1);
            cf p = csq(csq(csq(e2)));
            cf f0 = cmul(wv, p), f1 = cmul(f0, u128), f2 = cmul(f1, u128), f3 = cmul(f2, u128);
            uint32_t A00 = f2tf32(f0.re), A01 = f2tf32(f1.re), A02 = f2tf32(-f0.im), A03 = f2tf32(-f1.im);
            uint32_t A10 = f2tf32(f2.re), A11 = f2tf32(f3.re), A12 = f2tf32(-f2.im), A13 = f2tf32(-f3.im);
            mma_tf32(a0a, A00, A01, A02, A03, f2tf32(e1.re), f2tf32(e1.im));
            mma_tf32(a0b, A00, A01, A02, A03, f2tf32(e1b.re), f2tf32(e1b.im));
            mma_tf32(a1, A10, A11, A12, A13, f2tf32(e2.re), f2tf32(e2.im));
            uint32_t E0 = f2tf32(e23.re), E1 = f2tf32(e23.im);
            mma_tf32(a2a, A00, A01, A02, A03, E0, E1);
            mma_tf32(a2b, A10, A11, A12, A13, E0, E1);
            cf e2048 = csq(e23);
            k2048 += wv.re * e2048.re - wv.im * e2048.im;
        }
        k2048 += __shfl_xor_sync(~0u, k2048, 1);
        k2048 += __shfl_xor_sync(~0u, k2048, 2);
        float* Kc = S.Kc[w];
        Kc[16 * g + 2 * t] = a0a[0]; Kc[16 * g + 2 * t + 1] = a0a[1]; Kc[16 * (g + 8) + 2 * t] = a0a[2]; Kc[16 * (g + 8) + 2 * t + 1] = a0a[3];
        Kc[16 * g + 8 + 2 * t] = a0b[0]; Kc[16 * g + 8 + 2 * t + 1] = a0b[1]; Kc[16 * (g + 8) + 8 + 2 * t] = a0b[2]; Kc[16 * (g + 8) + 8 + 2 * t + 1] = a0b[3];
        Kc[256 + 8 * g + 2 * t] = a1[0]; Kc[256 + 8 * g + 2 * t + 1] = a1[1]; Kc[256 + 8 * (g + 8) + 2 * t] = a1[2]; Kc[256 + 8 * (g + 8) + 2 * t + 1] = a1[3];
        #pragma unroll
        for (int mt = 0; mt < 2; mt++) {
            #pragma unroll
            for (int e = 0; e < 4; e++) {
                int A = mt * 16 + g + (e >> 1) * 8, j = 2 * t + (e & 1);
                int Lj = (j < 4) ? 512 + 4 * j : (j < 6 ? 1024 + 8 * (j - 4) : 1536 + 8 * (j - 6));
                Kc[kc_index(Lj + 16 * A)] = mt ? a2b[e] : a2a[e];
            }
        }
        if (lane == 16) Kc[640] = k2048;
    }
    __syncwarp();
    {
        asm volatile("bar.sync 1, 256;" ::: "memory");
        bf16* k0 = S.u.KT[w][0];
        bf16* k1 = S.u.KT[w][1];
        const float* Kc = S.Kc[w];
        #pragma unroll 8
        for (int j = lane; j < 2048; j += 32) {
            const bf16 v = __float2bfloat16_rn(Kc[S.kidx[j]]);
            k0[16 + j] = v;
            k1[15 + j] = v;
        }
        if (lane < 16) { k0[lane] = __float2bfloat16_rn(0.f); if (lane < 15) k1[lane] = __float2bfloat16_rn(0.f); }
        k0[2064 + lane] = __float2bfloat16_rn(0.f); k1[2063 + lane] = __float2bfloat16_rn(0.f);
        __syncwarp();
    }
    {
        float acc[16][4];
        #pragma unroll
        for (int v = 0; v < 16; v++) { acc[v][0] = acc[v][1] = acc[v][2] = acc[v][3] = 0.f; }
        const bf16* kt = (g & 1) ? &S.u.KT[w][0][0] : &S.u.KT[w][1][0];
        const int ibase0 = g + 1 + 2 * t - ((g & 1) ? 0 : 1);
        #pragma unroll 1
        for (int r = 0; r < 8; r++) {
            uint32_t B[16][2];
            #pragma unroll
            for (int v = 0; v < 16; v++) {
                const bf16* p = &S.xs[w][XS_PAD + 16 * (8 * v + g - r) + 2 * t];
                B[v][0] = *reinterpret_cast<const uint32_t*>(p);
                B[v][1] = *reinterpret_cast<const uint32_t*>(p + 8);
            }
            #pragma unroll
            for (int q = 0; q < 16; q++) {
                const int i0 = ibase0 + 16 * r + 128 * q;
                const uint32_t A0 = *reinterpret_cast<const uint32_t*>(kt + i0);
                const uint32_t A1 = *reinterpret_cast<const uint32_t*>(kt + i0 + 8);
                const uint32_t A3 = *reinterpret_cast<const uint32_t*>(kt + i0 + 16);
                #pragma unroll
                for (int v = q; v < 16; v++) mma_bf16(acc[v], A0, A1, A1, A3, B[v - q][0], B[v - q][1]);
            }
        }
        bf16* ys = S.ys[w];
        #pragma unroll
        for (int v = 0; v < 16; v++) {
            const int a = 8 * v + 2 * t;
            ys[16 * a + g] = __float2bfloat16_rn(acc[v][0]); ys[16 * (a + 1) + g] = __float2bfloat16_rn(acc[v][1]);
            ys[16 * a + g + 8] = __float2bfloat16_rn(acc[v][2]); ys[16 * (a + 1) + g + 8] = __float2bfloat16_rn(acc[v][3]);
        }
    }
    asm volatile("bar.sync 1, 256;" ::: "memory");
    {
        float dsk[8];
        #pragma unroll
        for (int c = 0; c < 8; c++) dsk[c] = bf2f(Dskip[d0 + c]);
        #pragma unroll 2
        for (int it = 0; it < 8; it++) {
            const int l = tid + 256 * it;
            const int lr = XS_PAD + ((l & ~15) | (15 - (l & 15)));
            float o[8];
            #pragma unroll
            for (int c = 0; c < 8; c++) o[c] = bf2f(S.ys[c][l]) + bf2f(__float2bfloat16_rn(bf2f(S.xs[c][lr]) * dsk[c]));
            *reinterpret_cast<uint4*>(g_b + (size_t)l * DM + d0) = make_uint4(pack_bf16(o[0], o[1]), pack_bf16(o[2], o[3]), pack_bf16(o[4], o[5]), pack_bf16(o[6], o[7]));
        }
    }
}

__device__ __forceinline__ uint32_t smem_u32(const void* p) { return (uint32_t)__cvta_generic_to_shared(p); }
__device__ __forceinline__ void mbar_init(uint32_t bar, uint32_t cnt) { asm volatile("mbarrier.init.shared::cta.b64 [%0], %1;" :: "r"(bar), "r"(cnt) : "memory"); }
__device__ __forceinline__ void mbar_expect_tx(uint32_t bar, uint32_t bytes) { asm volatile("mbarrier.arrive.expect_tx.shared::cta.b64 _, [%0], %1;" :: "r"(bar), "r"(bytes) : "memory"); }
__device__ __forceinline__ void mbar_arrive(uint32_t bar) { asm volatile("mbarrier.arrive.shared::cta.b64 _, [%0];" :: "r"(bar) : "memory"); }
__device__ __forceinline__ void mbar_wait(uint32_t bar, uint32_t parity) {
    uint32_t ok; int guard = 0;
    do {
        asm volatile("{\n.reg .pred P1;\nmbarrier.test_wait.parity.shared::cta.b64 P1, [%1], %2;\nselp.u32 %0,1,0,P1;\n}" : "=r"(ok) : "r"(bar), "r"(parity) : "memory");
    } while (!ok && ++guard < (1 << 26));
}
__device__ __forceinline__ void mbar_wait_sleep(uint32_t bar, uint32_t parity) {
    uint32_t ok; int guard = 0;
    do {
        asm volatile("{\n.reg .pred P1;\nmbarrier.try_wait.parity.shared::cta.b64 P1, [%1], %2;\nselp.u32 %0,1,0,P1;\n}" : "=r"(ok) : "r"(bar), "r"(parity) : "memory");
    } while (!ok && ++guard < (1 << 22));
}
__device__ __forceinline__ uint32_t mapa(uint32_t addr, uint32_t rank) { uint32_t r; asm volatile("mapa.shared::cluster.u32 %0, %1, %2;" : "=r"(r) : "r"(addr), "r"(rank)); return r; }
__device__ __forceinline__ void st_async4(uint32_t addr, float a, float b, float c, float d, uint32_t bar) {
    asm volatile("st.async.weak.shared::cluster.mbarrier::complete_tx::bytes.v4.f32 [%0], {%1,%2,%3,%4}, [%5];" :: "r"(addr), "f"(a), "f"(b), "f"(c), "f"(d), "r"(bar) : "memory");
}
__device__ __forceinline__ void bulk_s2c(uint32_t dst, uint32_t src, uint32_t bytes, uint32_t bar) {
    asm volatile("cp.async.bulk.shared::cluster.shared::cta.mbarrier::complete_tx::bytes [%0], [%1], %2, [%3];" :: "r"(dst), "r"(src), "r"(bytes), "r"(bar) : "memory");
}
__device__ __forceinline__ void bulk_g2s(uint32_t dst, const void* src, uint32_t bytes, uint32_t bar) {
    asm volatile("cp.async.bulk.shared::cluster.global.mbarrier::complete_tx::bytes [%0], [%1], %2, [%3];" :: "r"(dst), "l"(src), "r"(bytes), "r"(bar) : "memory");
}
__device__ __forceinline__ void bulk_s2g(void* dst, uint32_t src, uint32_t bytes) {
    asm volatile("cp.async.bulk.global.shared::cta.bulk_group [%0], [%1], %2;" :: "l"(dst), "r"(src), "r"(bytes) : "memory");
}
__device__ __forceinline__ void bulk_commit() { asm volatile("cp.async.bulk.commit_group;" ::: "memory"); }
__device__ __forceinline__ void bulk_wait_read0() { asm volatile("cp.async.bulk.wait_group.read 0;" ::: "memory"); }
__device__ __forceinline__ void bulk_wait0() { asm volatile("cp.async.bulk.wait_group 0;" ::: "memory"); }
__device__ __forceinline__ void fence_async() { asm volatile("fence.proxy.async.shared::cta;" ::: "memory"); }
__device__ __forceinline__ void nbar_sync(int id, int n) { asm volatile("bar.sync %0, %1;" :: "r"(id), "r"(n) : "memory"); }
__device__ __forceinline__ void nbar_arrive(int id, int n) { asm volatile("bar.arrive %0, %1;" :: "r"(id), "r"(n) : "memory"); }
__device__ __forceinline__ void cp_async16(uint32_t dst, const void* src) { asm volatile("cp.async.cg.shared.global [%0], [%1], 16;" :: "r"(dst), "l"(src) : "memory"); }
__device__ __forceinline__ void cp_async_wait_all() { asm volatile("cp.async.wait_all;" ::: "memory"); }
__device__ __forceinline__ void ldsm4(uint32_t (&r)[4], uint32_t addr) {
    asm volatile("ldmatrix.sync.aligned.m8n8.x4.shared.b16 {%0,%1,%2,%3}, [%4];" : "=r"(r[0]), "=r"(r[1]), "=r"(r[2]), "=r"(r[3]) : "r"(addr) : "memory");
}
__device__ __forceinline__ void ldsm4t(uint32_t (&r)[4], uint32_t addr) {
    asm volatile("ldmatrix.sync.aligned.m8n8.x4.trans.shared.b16 {%0,%1,%2,%3}, [%4];" : "=r"(r[0]), "=r"(r[1]), "=r"(r[2]), "=r"(r[3]) : "r"(addr) : "memory");
}
__device__ __forceinline__ void stsm2t(uint32_t addr, uint32_t r0, uint32_t r1) {
    asm volatile("stmatrix.sync.aligned.m8n8.x2.trans.shared.b16 [%0], {%1,%2};" :: "r"(addr), "r"(r0), "r"(r1) : "memory");
}
__device__ __forceinline__ uint4 ld_relaxed4(const void* p) { uint4 v; asm volatile("ld.relaxed.gpu.global.v4.u32 {%0,%1,%2,%3}, [%4];" : "=r"(v.x), "=r"(v.y), "=r"(v.z), "=r"(v.w) : "l"(p) : "memory"); return v; }
__device__ __forceinline__ void st_relaxed2(void* p, uint32_t a, uint32_t b) { asm volatile("st.relaxed.gpu.global.v2.u32 [%0], {%1,%2};" :: "l"(p), "r"(a), "r"(b) : "memory"); }
__device__ __forceinline__ void st_relaxed1(void* p, uint32_t a) { asm volatile("st.relaxed.gpu.global.u32 [%0], %1;" :: "l"(p), "r"(a) : "memory"); }
__device__ __forceinline__ unsigned ld_acquire(const unsigned* p) { unsigned v; asm volatile("ld.acquire.gpu.global.u32 %0, [%1];" : "=r"(v) : "l"(p) : "memory"); return v; }
__device__ __forceinline__ float ex2_approx(float x) { float r; asm("ex2.approx.ftz.f32 %0, %1;" : "=f"(r) : "f"(x)); return r; }
__device__ __forceinline__ uint64_t make_desc(uint32_t saddr, uint32_t lbo, uint32_t sbo) {
    return (uint64_t)((saddr & 0x3FFFF) >> 4) | ((uint64_t)((lbo & 0x3FFFF) >> 4) << 16) | ((uint64_t)((sbo & 0x3FFFF) >> 4) << 32) | (1ull << 62);
}
__device__ __forceinline__ void wg_fence() { asm volatile("wgmma.fence.sync.aligned;" ::: "memory"); }
__device__ __forceinline__ void wg_commit() { asm volatile("wgmma.commit_group.sync.aligned;" ::: "memory"); }
__device__ __forceinline__ void wg_wait0() { asm volatile("wgmma.wait_group.sync.aligned 0;" ::: "memory"); }
__device__ __forceinline__ void wgmma_n40_tA(float (&d)[20], uint64_t da, uint64_t db, int scale_d) {
    asm volatile("{\n.reg .pred p;\nsetp.ne.b32 p, %22, 0;\n"
        "wgmma.mma_async.sync.aligned.m64n40k16.f32.bf16.bf16 {%0,%1,%2,%3,%4,%5,%6,%7,%8,%9,%10,%11,%12,%13,%14,%15,%16,%17,%18,%19}, %20, %21, p, 1, 1, 1, 0;\n}\n"
        : "+f"(d[0]), "+f"(d[1]), "+f"(d[2]), "+f"(d[3]), "+f"(d[4]), "+f"(d[5]), "+f"(d[6]), "+f"(d[7]), "+f"(d[8]), "+f"(d[9]),
          "+f"(d[10]), "+f"(d[11]), "+f"(d[12]), "+f"(d[13]), "+f"(d[14]), "+f"(d[15]), "+f"(d[16]), "+f"(d[17]), "+f"(d[18]), "+f"(d[19])
        : "l"(da), "l"(db), "r"(scale_d));
}

#define NREP 8
#define NRED 80
#define CAL_THR 410u
#define COMM_REGS "40"
#define NPOOL 576
#define RPS 1
__device__ __align__(4096) uint32_t g_pool[(NPOOL + 1) * 1024];
__device__ unsigned g_cls[NPOOL];
__device__ unsigned g_side[96];
__device__ unsigned g_calcnt;
__device__ unsigned g_epoch;
__device__ unsigned g_flag[NSEG][NH];
__device__ __align__(1024) bf16 g_Qimg[NSEG * NH * 2 * 32 * 64];
__device__ __align__(1024) bf16 g_Kimg[NSEG * NH * 2 * 40 * 64];
__device__ __align__(1024) bf16 g_Vimg[NSEG * NH * 2 * 40 * 64];

#define SM_XB    0
#define SM_VT    81920
#define SM_KT    (SM_VT + 20480)
#define SM_QT    (SM_KT + 10240)
#define SM_QS    (SM_QT + 4096)
#define SM_MEMB  (SM_QS + 1024)
#define SM_RED   (SM_MEMB + 10240)
#define SM_SC    (SM_RED + 16384)
#define SM_CRED  (SM_SC + 5120)
#define SM_PB    (SM_CRED + 1024)
#define SM_TRACE (SM_PB + 1024)
#define SM_WO    163840
#define SM_BAR   (SM_WO + 65536)
#define SM_TPM   (SM_BAR + 256)
#define SM_TRD   (SM_TPM + 256)
#define SM_TPUB  (SM_TRD + 16)
#define SM_TGAT  (SM_TPUB + 128)
#define SM_CAL   (SM_TGAT + 64)
#define SM_TOTAL (SM_CAL + 128)
#define B_SC   (SM_BAR + 0)
#define B_V    (SM_BAR + 16)
#define B_MEM  (SM_BAR + 32)
#define B_P    (SM_BAR + 48)
#define B_X    (SM_BAR + 56)
#define B_EXP  (SM_BAR + 72)

#define TR(ev) do {} while (0)
__device__ __forceinline__ uint32_t tag_of(int s) { return (uint32_t)(((s >> 1) & 1) + 1); }
__device__ __forceinline__ unsigned probe_latency(uint32_t* p, uint32_t zero) {
    uint32_t v, best = 0xffffffffu;
    asm volatile("atom.relaxed.gpu.global.add.u32 %0, [%1], 0;" : "=r"(v) : "l"(p) : "memory");
    #pragma unroll 1
    for (int r = 0; r < 4; r++) {
        uint32_t c0, c1;
        asm volatile("mov.u32 %0, %%clock;" : "=r"(c0) : "r"(v) : "memory");
        asm volatile("atom.relaxed.gpu.global.add.u32 %0, [%1], 0;" : "=r"(v) : "l"(p + ((v + c0) & zero)) : "memory");
        asm volatile("{\n.reg .u32 t;\nand.b32 t, %1, %2;\nmov.u32 %0, %%clock;\nadd.u32 %0, %0, t;\n}" : "=r"(c1) : "r"(v), "r"(zero) : "memory");
        best = min(best, c1 - c0);
    }
    return best;
}
__device__ __forceinline__ void cluster_sync_all() { asm volatile("barrier.cluster.arrive.release.aligned;\nbarrier.cluster.wait.acquire.aligned;" ::: "memory"); }
__device__ __forceinline__ void tma_load_2d(uint32_t dst, const void* map, int c0, int c1, uint32_t bar) {
    asm volatile("cp.async.bulk.tensor.2d.shared::cluster.global.mbarrier::complete_tx::bytes [%0], [%1, {%3, %4}], [%2];"
        :: "r"(dst), "l"(map), "r"(bar), "r"(c0), "r"(c1) : "memory");
}
__device__ __forceinline__ void tma_load_3d(uint32_t dst, const void* map, int c0, int c1, int c2, uint32_t bar) {
    asm volatile("cp.async.bulk.tensor.3d.shared::cluster.global.mbarrier::complete_tx::bytes [%0], [%1, {%3, %4, %5}], [%2];"
        :: "r"(dst), "l"(map), "r"(bar), "r"(c0), "r"(c1), "r"(c2) : "memory");
}
__device__ __forceinline__ void stsm4t(uint32_t addr, uint32_t r0, uint32_t r1, uint32_t r2, uint32_t r3) {
    asm volatile("stmatrix.sync.aligned.m8n8.x4.trans.shared.b16 [%0], {%1,%2,%3,%4};" :: "r"(addr), "r"(r0), "r"(r1), "r"(r2), "r"(r3) : "memory");
}
__device__ __forceinline__ void wgmma_n32_rs(float (&d)[16], const uint32_t (&a)[4], uint64_t db, int scale_d) {
    asm volatile("{\n.reg .pred p;\nsetp.ne.b32 p, %21, 0;\n"
        "wgmma.mma_async.sync.aligned.m64n32k16.f32.bf16.bf16 {%0,%1,%2,%3,%4,%5,%6,%7,%8,%9,%10,%11,%12,%13,%14,%15}, {%16,%17,%18,%19}, %20, p, 1, 1, 0;\n}\n"
        : "+f"(d[0]), "+f"(d[1]), "+f"(d[2]), "+f"(d[3]), "+f"(d[4]), "+f"(d[5]), "+f"(d[6]), "+f"(d[7]),
          "+f"(d[8]), "+f"(d[9]), "+f"(d[10]), "+f"(d[11]), "+f"(d[12]), "+f"(d[13]), "+f"(d[14]), "+f"(d[15])
        : "r"(a[0]), "r"(a[1]), "r"(a[2]), "r"(a[3]), "l"(db), "r"(scale_d));
}

__device__ __forceinline__ void st_async4u(uint32_t addr, uint4 v, uint32_t bar) {
    asm volatile("st.async.weak.shared::cluster.mbarrier::complete_tx::bytes.v4.u32 [%0], {%1,%2,%3,%4}, [%5];" :: "r"(addr), "r"(v.x), "r"(v.y), "r"(v.z), "r"(v.w), "r"(bar) : "memory");
}
__device__ __forceinline__ void export_issue(uint32_t sb, int s, int h, uint32_t rank) {
    const size_t img = (size_t)(s * NH + h) * 2;
    const int sl = s & 1;
    if (rank == 2) {
        bulk_s2g(g_Vimg + img * 2560, sb + SM_VT + sl * 10240, 5120);
        bulk_s2g(g_Vimg + (img + 1) * 2560, sb + SM_VT + sl * 10240 + 5120, 5120);
    } else {
        bulk_s2g(g_Qimg + (img + rank) * 2048, sb + SM_QT, 4096);
        bulk_s2g(g_Kimg + (img + rank) * 2560, sb + SM_KT + sl * 5120, 5120);
    }
    bulk_commit();
    bulk_wait_read0();
    mbar_arrive(sb + B_EXP);
}
__device__ __forceinline__ void export_signal(int s, int h) {
    bulk_wait0();
    asm volatile("fence.proxy.async;" ::: "memory");
    __threadfence();
    atomicAdd(&g_flag[s][h], 1u);
}

__device__ __forceinline__ void score_tile(uint32_t sb, int sl, int nt, int lane, uint32_t rank) {
    float sc[4] = {0, 0, 0, 0}, sd[4] = {0, 0, 0, 0};
    const int r = lane & 7;
    uint32_t qa[2][4], kb[2][4];
    #pragma unroll
    for (int j = 0; j < 2; j++) {
        const int chunk = (lane >> 3) + 4 * j;
        ldsm4(kb[j], sb + SM_KT + sl * 5120 + (8 * nt + r) * 128 + ((chunk ^ r) << 4));
        ldsm4(qa[j], sb + SM_QS + r * 128 + ((chunk ^ r) << 4));
    }
    mma_bf16(sc, qa[0][0], 0u, qa[0][1], 0u, kb[0][0], kb[0][1]);
    mma_bf16(sd, qa[1][0], 0u, qa[1][1], 0u, kb[1][0], kb[1][1]);
    mma_bf16(sc, qa[0][2], 0u, qa[0][3], 0u, kb[0][2], kb[0][3]);
    mma_bf16(sd, qa[1][2], 0u, qa[1][3], 0u, kb[1][2], kb[1][3]);
    sc[0] += sd[0]; sc[1] += sd[1];
    const float o0 = __shfl_down_sync(~0u, sc[0], 1), o1 = __shfl_down_sync(~0u, sc[1], 1);
    if ((lane & 1) == 0) {
        const uint32_t a = SM_SC + sl * 2560 + rank * 1280 + ((lane >> 2) * 40 + 8 * nt + 2 * (lane & 3)) * 4;
        const uint32_t bo = B_SC + 8 * sl;
        { const uint32_t rb = mapa(sb, 2); st_async4(rb + a, sc[0], sc[1], o0, o1, rb + bo); }
        { const uint32_t rb = mapa(sb, rank ^ 1); st_async4(rb + a, sc[0], sc[1], o0, o1, rb + bo); }
        asm volatile("st.shared.v4.f32 [%0], {%1,%2,%3,%4};" :: "r"(sb + a), "f"(sc[0]), "f"(sc[1]), "f"(o0), "f"(o1) : "memory");
    }
    __syncwarp();
    if (lane == 0) mbar_arrive(sb + B_SC + 8 * sl);
}
__device__ __forceinline__ void wgmma_n40_rs(float (&d)[20], const uint32_t (&a)[4], uint64_t db, int scale_d) {
    asm volatile("{\n.reg .pred p;\nsetp.ne.b32 p, %25, 0;\n"
        "wgmma.mma_async.sync.aligned.m64n40k16.f32.bf16.bf16 {%0,%1,%2,%3,%4,%5,%6,%7,%8,%9,%10,%11,%12,%13,%14,%15,%16,%17,%18,%19}, {%20,%21,%22,%23}, %24, p, 1, 1, 0;\n}\n"
        : "+f"(d[0]), "+f"(d[1]), "+f"(d[2]), "+f"(d[3]), "+f"(d[4]), "+f"(d[5]), "+f"(d[6]), "+f"(d[7]), "+f"(d[8]), "+f"(d[9]),
          "+f"(d[10]), "+f"(d[11]), "+f"(d[12]), "+f"(d[13]), "+f"(d[14]), "+f"(d[15]), "+f"(d[16]), "+f"(d[17]), "+f"(d[18]), "+f"(d[19])
        : "r"(a[0]), "r"(a[1]), "r"(a[2]), "r"(a[3]), "l"(db), "r"(scale_d));
}
__device__ __forceinline__ void pu_store(const float (&u)[20], const uint32_t (&pb)[5], float2 inv, unsigned char* smem, int sl, int lt, int warp, int lane, uint32_t tg) {
    float o[4] = {0, 0, 0, 0}, o2[4] = {0, 0, 0, 0};
    mma_bf16(o, pack_bf16(u[0], u[1]), pack_bf16(u[2], u[3]), pack_bf16(u[4], u[5]), pack_bf16(u[6], u[7]), pb[0], pb[1]);
    mma_bf16(o2, pack_bf16(u[8], u[9]), pack_bf16(u[10], u[11]), pack_bf16(u[12], u[13]), pack_bf16(u[14], u[15]), pb[2], pb[3]);
    mma_bf16(o, pack_bf16(u[16], u[17]), pack_bf16(u[18], u[19]), 0u, 0u, pb[4], 0u);
    const uint2 off = *reinterpret_cast<const uint2*>(smem + SM_TPM + (((sl * 4 + lt) * 4 + warp) * 2) * 4);
    unsigned char* pool = reinterpret_cast<unsigned char*>(g_pool) + lane * 8;
    st_relaxed2(pool + off.x, (__float_as_uint((o[0] + o2[0]) * inv.x) & ~3u) | tg, (__float_as_uint((o[1] + o2[1]) * inv.y) & ~3u) | tg);
    st_relaxed2(pool + off.y, (__float_as_uint((o[2] + o2[2]) * inv.x) & ~3u) | tg, (__float_as_uint((o[3] + o2[3]) * inv.y) & ~3u) | tg);
}
template <int NT>
__device__ __forceinline__ void u_pass(unsigned char* smem, uint32_t sb, int s, uint32_t rank, int wg, int warp, int lane) {
    const int sl = s & 1;
    constexpr int NRS = 6;
    uint32_t wa[NRS][4];
    {
        const int mi = lane >> 3, chunk = 2 * warp + (mi & 1);
        #pragma unroll
        for (int ks = 0; ks < NRS; ks++) {
            const int row = 16 * ks + (mi >> 1) * 8 + (lane & 7);
            ldsm4t(wa[ks], sb + SM_WO + (2 * wg) * 16384 + row * 128 + ((chunk ^ (row & 7)) << 4));
        }
    }
    if (rank < 2) { mbar_wait(sb + B_V + 8 * sl, (s >> 1) & 1); fence_async(); }
    if (wg == 0 && warp == 0) TR(4);
    float U0[20];
    wg_fence();
    #pragma unroll
    for (int ks = 0; ks < NRS; ks++)
        wgmma_n40_rs(U0, wa[ks], make_desc(sb + SM_VT + sl * 10240 + (ks >> 2) * 5120 + (ks & 3) * 32, 16, 1024), ks > 0);
    #pragma unroll
    for (int ks = NRS; ks < 8; ks++)
        wgmma_n40_tA(U0, make_desc(sb + SM_WO + (2 * wg) * 16384 + ks * 2048, 1024, 1024),
                     make_desc(sb + SM_VT + sl * 10240 + (ks >> 2) * 5120 + (ks & 3) * 32, 16, 1024), 1);
    wg_commit();
    const uint32_t tg = tag_of(s);
    uint32_t pb[5];
    float2 inv;
    auto get_p = [&]() {
        nbar_sync(9, 288);
        const uint32_t* pbs = reinterpret_cast<const uint32_t*>(smem + SM_PB);
        #pragma unroll
        for (int q = 0; q < 5; q++) pb[q] = pbs[q * 32 + lane];
        float sm[4] = {0, 0, 0, 0}, sm2[4] = {0, 0, 0, 0};
        const uint32_t one = 0x3f803f80u;
        mma_bf16(sm, one, one, one, one, pb[0], pb[1]);
        mma_bf16(sm2, one, one, one, one, pb[2], pb[3]);
        mma_bf16(sm, one, one, 0u, 0u, pb[4], 0u);
        inv.x = __frcp_rn(sm[0] + sm2[0]); inv.y = __frcp_rn(sm[1] + sm2[1]);
    };
    if (NT == 2) {
        wg_wait0();
        float U1[20];
        wg_fence();
        #pragma unroll
        for (int ks = 0; ks < 8; ks++)
            wgmma_n40_tA(U1, make_desc(sb + SM_WO + (2 * wg + 1) * 16384 + ks * 2048, 1024, 1024),
                         make_desc(sb + SM_VT + sl * 10240 + (ks >> 2) * 5120 + (ks & 3) * 32, 16, 1024), ks > 0);
        wg_commit();
        get_p();
        if (wg == 0 && warp == 0) TR(8);
        pu_store(U0, pb, inv, smem, sl, 2 * wg, warp, lane, tg);
        wg_wait0();
        if (wg == 0 && warp == 0) TR(6);
        pu_store(U1, pb, inv, smem, sl, 2 * wg + 1, warp, lane, tg);
    } else {
        wg_wait0();
        get_p();
        pu_store(U0, pb, inv, smem, sl, 2 * wg, warp, lane, tg);
    }
}

__global__ void __cluster_dims__(3, 1, 1) __launch_bounds__(384, 1)
k_chain(const __grid_constant__ CUtensorMap xmap, const __grid_constant__ CUtensorMap wqmap, const __grid_constant__ CUtensorMap wkmap,
        const __grid_constant__ CUtensorMap wvmap, const __grid_constant__ CUtensorMap womap, const bf16* __restrict__ xptr, const bf16* __restrict__ mem0) {
    extern __shared__ __align__(1024) unsigned char smem[];
    const uint32_t sb = smem_u32(smem);
    const int tid = threadIdx.x, lane = tid & 31;
    const int wg = __shfl_sync(~0u, tid >> 7, 0), warp = __shfl_sync(~0u, (tid >> 5) & 3, 0);
    uint32_t rank; asm volatile("mov.u32 %0, %%cluster_ctarank;" : "=r"(rank));
    const int cta = blockIdx.x, h = cta / 3;
    asm volatile("griddepcontrol.launch_dependents;");
    if (tid == 0) {
        for (int i = 0; i < 2; i++) { mbar_init(sb + B_SC + 8 * i, rank < 2 ? 6 : 1); mbar_init(sb + B_V + 8 * i, 1); mbar_init(sb + B_MEM + 8 * i, 64); mbar_init(sb + B_X + 8 * i, 1); }
        mbar_init(sb + B_P, 1); mbar_init(sb + B_EXP, 1);
        asm volatile("fence.mbarrier_init.release.cluster;" ::: "memory");
    }
    if (tid < 80) asm volatile("prefetch.global.L2 [%0];" :: "l"(mem0 + tid * 64));
    if (h < 2) { for (int i = tid; i < 320; i += 384) asm volatile("prefetch.global.L2 [%0];" :: "l"(xptr + (size_t)h * 32 * DM + i * 64)); }
    {
        const int w12 = tid >> 5;
        if (lane == 0 && w12 < 7) {
            uint32_t* pp = (w12 < 6) ? g_pool + (size_t)(cta * 6 + w12) * 1024 + 512 : g_pool + (size_t)NPOOL * 1024 + (cta & 31) * 32 + (cta >> 5) * 8;
            const unsigned lat = probe_latency(pp, blockIdx.y);
            if (w12 < 6) g_cls[cta * 6 + w12] = lat > CAL_THR ? 1u : 0u; else g_side[cta] = lat > CAL_THR ? 1u : 0u;
        }
        __syncwarp();
        uint4* z = reinterpret_cast<uint4*>(g_pool + (size_t)cta * 6 * 1024);
        #pragma unroll
        for (int q = 0; q < 4; q++) z[tid + 384 * q] = make_uint4(0, 0, 0, 0);
        __threadfence();
        __syncwarp();
        if (lane == 0) atomicAdd(&g_calcnt, 1u);
    }
    __syncthreads();
    if (tid == 0) {
        const int ntile = (rank == 2) ? 4 : 3;
        const int tile0 = (rank == 2) ? 0 : (rank == 0 ? 4 : 7);
        mbar_expect_tx(sb + B_P, 163840 + ntile * 16384);
        const void* m0 = (rank == 2) ? &wvmap : &wqmap;
        const void* m1 = (rank == 2) ? &wvmap : &wkmap;
        const int c0 = h * DH + (rank == 1 ? 64 : 0), c1 = h * DH + (rank == 0 ? 0 : 64);
        for (int b = 0; b < 5; b++) {
            tma_load_2d(sb + b * 16384, m0, c0, b * 128, sb + B_P);
            tma_load_2d(sb + 81920 + b * 16384, m1, c1, b * 128, sb + B_P);
        }
        for (int lt = 0; lt < ntile; lt++) {
            tma_load_2d(sb + SM_WO + lt * 16384, &womap, (tile0 + lt) * 64, h * DH, sb + B_P);
            tma_load_2d(sb + SM_WO + lt * 16384 + 8192, &womap, (tile0 + lt) * 64, h * DH + 64, sb + B_P);
        }
    }
    {
        const int tile0 = (rank == 2) ? 0 : (rank == 0 ? 4 : 7);
        if (wg == 2) {
            const int ct = tid & 127;
            if (ct == 0) {
                const unsigned target = (*reinterpret_cast<volatile unsigned*>(&g_epoch) + 1u) * (96u * 12u);
                int guard = 0;
                while ((int)(ld_acquire(&g_calcnt) - target) < 0 && ++guard < (1 << 22)) {}
            }
            nbar_sync(4, 128);
            uint32_t* bm = reinterpret_cast<uint32_t*>(smem + SM_CAL);
            {
                unsigned v[5];
                #pragma unroll
                for (int q = 0; q < 5; q++) { const int b = ct + 128 * q; v[q] = (b < NPOOL) ? (__ldcg(&g_cls[b]) ^ __ldcg(&g_side[b / 6])) : 0u; }
                const unsigned sv = (ct < 96) ? __ldcg(&g_side[ct]) : 0u;
                #pragma unroll
                for (int q = 0; q < 5; q++) { const unsigned m = __ballot_sync(~0u, v[q] & 1u); if (lane == 0 && q * 4 + warp < 18) bm[q * 4 + warp] = m; }
                const unsigned m = __ballot_sync(~0u, sv & 1u);
                if (lane == 0 && warp < 3) bm[18 + warp] = m;
            }
            nbar_sync(4, 128);
            int nblk1 = 0;
            for (int i = 0; i < 18; i++) nblk1 += __popc(bm[i]);
            const unsigned red_last = (1u << (NRED - 64)) - 1u;
            const int nred1 = __popc(bm[18]) + __popc(bm[19]) + __popc(bm[20] & red_last);
            auto side_of = [&](int c) -> int { return (bm[18 + (c >> 5)] >> (c & 31)) & 1; };
            auto rank_of = [&](int c) -> int {
                int ones = 0;
                for (int i = 0; i < (c >> 5); i++) ones += __popc(bm[18 + i]);
                ones += __popc(bm[18 + (c >> 5)] & ((1u << (c & 31)) - 1u));
                return side_of(c) ? ones : c - ones;
            };
            auto nth = [&](int side, int idx) -> uint32_t {
                for (int i = 0; i < 18; i++) {
                    const unsigned m = side ? bm[i] : ~bm[i];
                    const int n = __popc(m);
                    if (idx < n) return (uint32_t)(i * 32 + __fns(m, 0, idx + 1));
                    idx -= n;
                }
                return 0u;
            };
            auto phys = [&](int side, int idx) -> uint32_t {
                const int c = side ? nblk1 : NPOOL - nblk1;
                return (idx < c) ? nth(side, idx) : nth(side ^ 1, (NPOOL - c) - 1 - (idx - c));
            };
            const int e = ct;
            if (e < 64) {
                const int slot = e >> 5, lt = (e >> 3) & 3, w = (e >> 1) & 3, hf = e & 1;
                const int tile = min(tile0 + lt, 9);
                const int r = 2 * (4 * tile + w) + hf;
                reinterpret_cast<uint32_t*>(smem + SM_TPM)[e] = phys(side_of(r), 4 * rank_of(r) + slot * 2 + (h >> 4)) * 4096u + (h & 15) * 256u;
            } else if (e < 68) {
                const int i = e - 64;
                reinterpret_cast<uint32_t*>(smem + SM_TRD)[i] = (cta < NRED) ? phys(side_of(cta), 4 * rank_of(cta) + i) * 4096u : 0u;
            } else if (e < 100) {
                const int i = e - 68, slot = i >> 3, rep = i & 7, side = (rep / RPS) & 1;
                reinterpret_cast<uint32_t*>(smem + SM_TPUB)[i] = phys(side, 4 * (side ? nred1 : NRED - nred1) + (slot * RPS + (rep % RPS)) * 3 + (cta >> 5)) * 4096u + (cta & 31) * 128u;
            } else if (e < 112) {
                const int i = e - 100, slot = i / 3, b = i % 3, side = side_of(cta);
                reinterpret_cast<uint32_t*>(smem + SM_TGAT)[slot * 4 + b] = phys(side, 4 * (side ? nred1 : NRED - nred1) + (slot * RPS + (h % RPS)) * 3 + b) * 4096u;
            }
        }
    }
    __syncthreads();
    mbar_wait_sleep(sb + B_P, 0);

    if (wg == 2) {
        asm volatile("setmaxnreg.dec.sync.aligned.u32 " COMM_REGS ";");
        const int ct = tid & 127;
        nbar_sync(5, 384);
        for (int c = ct; c < 640; c += 128) {
            int ks = c >> 4, hf = (c >> 3) & 1, r = c & 7;
            *reinterpret_cast<uint4*>(smem + SM_MEMB + c * 16) = *reinterpret_cast<const uint4*>(mem0 + r * DM + ks * 16 + hf * 8);
        }
        if (ct == 0) {
            for (int sg = 0; sg < 2; sg++) {
                mbar_expect_tx(sb + B_X + 8 * sg, 40960);
                tma_load_3d(sb + SM_XB + sg * 40960, &xmap, 0, sg * 32, 0, sb + B_X + 8 * sg);
            }
            mbar_expect_tx(sb + B_SC, rank < 2 ? 1280 : 2560);
            if (rank < 2) mbar_expect_tx(sb + B_V, 8192 + 2048);
        }
        nbar_sync(5, 384);
        cluster_sync_all();
        unsigned char* const pool = reinterpret_cast<unsigned char*>(g_pool);
        for (int s = 0; s < NSEG - 1; s++) {
            if (warp == 1) nbar_sync(12, 288);
            if (warp == 0) {
                const int g = lane >> 2, t = lane & 3;
                mbar_wait(sb + B_SC + 8 * (s & 1), (s >> 1) & 1);
                TR(5);
                const uint32_t sa = sb + SM_SC + (s & 1) * 2560 + (g * 40 + 2 * t) * 4;
                float v[5][2], u[5][2];
                #pragma unroll
                for (int q = 0; q < 5; q++) {
                    asm volatile("ld.shared.v2.f32 {%0,%1}, [%2];" : "=f"(v[q][0]), "=f"(v[q][1]) : "r"(sa + 32 * q) : "memory");
                    asm volatile("ld.shared.v2.f32 {%0,%1}, [%2];" : "=f"(u[q][0]), "=f"(u[q][1]) : "r"(sa + 1280 + 32 * q) : "memory");
                }
                float mx = -3.0e38f;
                #pragma unroll
                for (int q = 0; q < 5; q++) {
                    v[q][0] += u[q][0]; v[q][1] += u[q][1];
                    mx = fmaxf(mx, fmaxf(v[q][0], v[q][1]));
                }
                mx = fmaxf(mx, __shfl_xor_sync(~0u, mx, 1));
                mx = fmaxf(mx, __shfl_xor_sync(~0u, mx, 2));
                const float sc2 = 0.08838834764831845f * 1.4426950408889634f;
                const float mxs = mx * sc2;
                uint32_t* pbs = reinterpret_cast<uint32_t*>(smem + SM_PB);
                #pragma unroll
                for (int q = 0; q < 5; q++) {
                    const float e0 = ex2_approx(fmaf(v[q][0], sc2, -mxs)), e1 = ex2_approx(fmaf(v[q][1], sc2, -mxs));
                    pbs[q * 32 + lane] = pack_bf16(e0, e1);
                }
                __syncwarp();
                TR(0);
                nbar_arrive(9, 288);
            } else if (warp == 1 && lane == 0) {
                if (s + 1 < NSEG - 1) {
                    mbar_expect_tx(sb + B_SC + 8 * ((s + 1) & 1), rank < 2 ? 1280 : 2560);
                    if (rank < 2) mbar_expect_tx(sb + B_V + 8 * ((s + 1) & 1), 8192 + 2048);
                }
                if (s + 2 < NSEG) {
                    mbar_expect_tx(sb + B_X + 8 * (s & 1), 40960);
                    tma_load_3d(sb + SM_XB + (s & 1) * 40960, &xmap, 0, (s + 2) * 32, 0, sb + B_X + 8 * (s & 1));
                }
                export_issue(sb, s, h, rank);
                if (s >= NSEG - 4) export_signal(s, h);
            }
            __syncwarp();
            nbar_sync(3, 384);
            const uint32_t tg = tag_of(s);
            if (cta < NRED) {
                const unsigned char* base = pool + reinterpret_cast<const uint32_t*>(smem + SM_TRD)[(s & 1) * 2 + (warp >> 1)] + (warp & 1) * 2048 + lane * 16;
                uint4 v[4]; int guard = 0;
                #pragma unroll
                for (int j = 0; j < 4; j++) v[j] = make_uint4(0, 0, 0, 0);
                uint32_t pend = 0xF;
                do {
                    #pragma unroll
                    for (int j = 0; j < 4; j++) if (pend & (1u << j)) v[j] = ld_relaxed4(base + j * 512);
                    #pragma unroll
                    for (int j = 0; j < 4; j++)
                        if (((v[j].x & 3) == tg) && ((v[j].y & 3) == tg) && ((v[j].z & 3) == tg) && ((v[j].w & 3) == tg)) pend &= ~(1u << j);
                } while (__any_sync(~0u, pend != 0) && ++guard < (1 << 20));
                if (warp == 0) TR(9);
                float a0 = 0, a1 = 0, a2 = 0, a3 = 0;
                #pragma unroll
                for (int j = 0; j < 4; j++) { a0 += __uint_as_float(v[j].x); a1 += __uint_as_float(v[j].y); a2 += __uint_as_float(v[j].z); a3 += __uint_as_float(v[j].w); }
                a0 += __shfl_xor_sync(~0u, a0, 16); a1 += __shfl_xor_sync(~0u, a1, 16); a2 += __shfl_xor_sync(~0u, a2, 16); a3 += __shfl_xor_sync(~0u, a3, 16);
                float* cr = reinterpret_cast<float*>(smem + SM_CRED);
                if (lane < 16) *reinterpret_cast<float4*>(cr + warp * 64 + lane * 4) = make_float4(a0, a1, a2, a3);
                nbar_sync(4, 128);
                {
                    int rho = lane >> 2, pp = lane & 3;
                    int i0 = ((2 * pp) * 4 + (rho >> 1)) * 2 + (rho & 1), i1 = i0 + 8;
                    uint32_t wv = pack_bf16((cr[i0] + cr[64 + i0]) + (cr[128 + i0] + cr[192 + i0]), (cr[i1] + cr[64 + i1]) + (cr[128 + i1] + cr[192 + i1]));
                    if (wv == 0) wv = 0x8000u;
                    if (warp == 0) TR(10);
                    const uint32_t* tp = reinterpret_cast<const uint32_t*>(smem + SM_TPUB) + warp;
                    if (warp < 2 * RPS) st_relaxed1(pool + tp[((s + 1) & 3) * 8] + lane * 4, wv);
                    if (RPS == 4) st_relaxed1(pool + tp[((s + 1) & 3) * 8 + 4] + lane * 4, wv);
                    if (warp < 2 * RPS) st_relaxed1(pool + tp[(s & 3) * 8] + lane * 4, 0u);
                    if (RPS == 4) st_relaxed1(pool + tp[(s & 3) * 8 + 4] + lane * 4, 0u);
                }
            }
            {
                const int c0 = warp * 160 + lane;
                const uint32_t* tg3 = reinterpret_cast<const uint32_t*>(smem + SM_TGAT) + ((s + 1) & 3) * 4;
                const uint32_t g0 = tg3[0], g1 = tg3[1], g2 = tg3[2];
                uint4 v[5]; int guard = 0;
                #pragma unroll
                for (int j = 0; j < 5; j++) v[j] = make_uint4(0, 0, 0, 0);
                uint32_t pend = 0x1F;
                do {
                    #pragma unroll
                    for (int j = 0; j < 5; j++) {
                        const int c = c0 + 32 * j;
                        if (pend & (1u << j)) v[j] = ld_relaxed4(pool + ((c >> 8) == 0 ? g0 : ((c >> 8) == 1 ? g1 : g2)) + (c & 255) * 16);
                    }
                    #pragma unroll
                    for (int j = 0; j < 5; j++) if (v[j].x && v[j].y && v[j].z && v[j].w) pend &= ~(1u << j);
                } while (__any_sync(~0u, pend != 0) && ++guard < (1 << 20));
                #pragma unroll
                for (int j = 0; j < 5; j++) *reinterpret_cast<uint4*>(smem + SM_MEMB + (c0 + 32 * j) * 16) = v[j];
                if (warp == 0) TR(11);
                if (warp == 3) TR(12);
                nbar_arrive(warp < 2 ? 7 + warp : 8 + warp, 160);
            }
            if (warp == 1 && lane == 0 && s < NSEG - 4) export_signal(s, h);
            __syncwarp();
        }
        if (warp == 1) { nbar_sync(12, 288); if (lane == 0) { export_issue(sb, NSEG - 1, h, rank); export_signal(NSEG - 1, h); } }
        __syncwarp();
        nbar_sync(3, 384);
        __syncwarp();
        cluster_sync_all();
    } else {
        asm volatile("setmaxnreg.inc.sync.aligned.u32 232;");
        const int wtid = tid & 127;
        const int cw = wg * 4 + warp;
        uint32_t areg[2][20][4];
        #pragma unroll
        for (int mt = 0; mt < 2; mt++)
            #pragma unroll
            for (int kk = 0; kk < 20; kk++) {
                int mi = lane >> 3;
                int row = 16 * (20 * wg + kk) + (mi >> 1) * 8 + (lane & 7);
                int chunk = 2 * warp + (mi & 1);
                ldsm4t(areg[mt][kk], sb + mt * 81920 + row * 128 + ((chunk ^ (row & 7)) << 4));
            }
        nbar_sync(5, 384);
        nbar_sync(5, 384);
        cluster_sync_all();

        for (int s = -1; s < NSEG; s++) {
            const int sl = s & 1;
            if (s >= 0) {
            if (s > 0) nbar_sync(7 + 3 * wg, 160);
            float fin[4];
            {
                float acc[2][2][4];
                #pragma unroll
                for (int i = 0; i < 2; i++)
                    #pragma unroll
                    for (int j = 0; j < 2; j++) { acc[i][j][0] = acc[i][j][1] = acc[i][j][2] = acc[i][j][3] = 0.f; }
                uint32_t b[3][4];
                const uint32_t mb = sb + SM_MEMB + (20 * wg) * 256 + lane * 16;
                ldsm4(b[0], mb); ldsm4(b[1], mb + 512);
                #pragma unroll
                for (int kp = 0; kp < 10; kp++) {
                    if (kp == 3 && s > 0) nbar_sync(8 + 3 * wg, 160);
                    if (kp + 2 < 10) ldsm4(b[(kp + 2) % 3], mb + (kp + 2) * 512);
                    const uint32_t (&bb)[4] = b[kp % 3];
                    mma_bf16(acc[0][0], areg[0][2 * kp][0], areg[0][2 * kp][1], areg[0][2 * kp][2], areg[0][2 * kp][3], bb[0], bb[1]);
                    mma_bf16(acc[1][0], areg[1][2 * kp][0], areg[1][2 * kp][1], areg[1][2 * kp][2], areg[1][2 * kp][3], bb[0], bb[1]);
                    mma_bf16(acc[0][1], areg[0][2 * kp + 1][0], areg[0][2 * kp + 1][1], areg[0][2 * kp + 1][2], areg[0][2 * kp + 1][3], bb[2], bb[3]);
                    mma_bf16(acc[1][1], areg[1][2 * kp + 1][0], areg[1][2 * kp + 1][1], areg[1][2 * kp + 1][2], areg[1][2 * kp + 1][3], bb[2], bb[3]);
                }
                float4* red = reinterpret_cast<float4*>(smem + SM_RED);
                float m0[4], m1[4];
                #pragma unroll
                for (int i = 0; i < 4; i++) { m0[i] = acc[0][0][i] + acc[0][1][i]; m1[i] = acc[1][0][i] + acc[1][1][i]; }
                red[(wg ^ 1) * 128 + wtid] = wg == 0 ? make_float4(m1[0], m1[1], m1[2], m1[3]) : make_float4(m0[0], m0[1], m0[2], m0[3]);
                nbar_sync(1, 256);
                float4 r = red[wg * 128 + wtid];
                fin[0] = (wg == 0 ? m0[0] : m1[0]) + r.x; fin[1] = (wg == 0 ? m0[1] : m1[1]) + r.y;
                fin[2] = (wg == 0 ? m0[2] : m1[2]) + r.z; fin[3] = (wg == 0 ? m0[3] : m1[3]) + r.w;
            }
            if (cw == 0) TR(1);
            {
                uint32_t p0 = pack_bf16(fin[0], fin[1]), p1 = pack_bf16(fin[2], fin[3]);
                const uint32_t doff = (rank == 2) ? SM_VT + sl * 10240 + wg * 5120 : (wg == 0 ? SM_QS : SM_KT + sl * 5120);
                const int r = lane & 7, chunk = 2 * warp + ((lane >> 3) & 1);
                const uint32_t coff = doff + r * 128 + ((chunk ^ r) << 4);
                stsm2t(sb + coff, p0, p1);
                if (rank == 2 && s < NSEG - 1) {
                    __syncwarp();
                    const uint4 v = *reinterpret_cast<const uint4*>(smem + coff);
                    const uint32_t rb = mapa(sb, lane >> 4);
                    st_async4u(rb + coff, v, rb + B_V + 8 * sl);
                }
            }
            fence_async();
            nbar_sync(1, 256);
            nbar_arrive(12, 288);
            if (cw == 0) TR(2);
            if (rank < 2 && s < NSEG - 1) {
                if (wg == 1) score_tile(sb, sl, 1 + warp, lane, rank);
                else if (warp == 0) score_tile(sb, sl, 0, lane, rank);
            }
            if (s == NSEG - 1) break;
            if (cw == 0) TR(3);
            if (wg == 0 || rank == 2) u_pass<2>(smem, sb, s, rank, wg, warp, lane);
            else                      u_pass<1>(smem, sb, s, rank, wg, warp, lane);
            if (cw == 0) TR(7);
            nbar_arrive(3, 384);
            }
            {
                const int sn = s + 1, sln = sn & 1;
                mbar_wait(sb + B_X + 8 * sln, (sn >> 1) & 1);
                float acc[2][16];
                wg_fence();
                #pragma unroll
                for (int mt = 0; mt < 2; mt++)
                    #pragma unroll
                    for (int kk = 0; kk < 20; kk++) {
                        uint64_t db = make_desc(sb + SM_XB + sln * 40960 + (5 * wg + (kk >> 2)) * 4096 + (kk & 3) * 32, 16, 1024);
                        wgmma_n32_rs(acc[mt], areg[mt][kk], db, kk > 0);
                    }
                wg_commit();
                if (cw == 0 && s >= 0) TR(14);
                wg_wait0();
                if (cw == 0 && s >= 0) TR(15);
                float4* red = reinterpret_cast<float4*>(smem + SM_RED);
                #pragma unroll
                for (int j = 0; j < 4; j++) {
                    red[((wg ^ 1) * 4 + j) * 128 + wtid] = make_float4(wg == 0 ? acc[1][4 * j] : acc[0][4 * j], wg == 0 ? acc[1][4 * j + 1] : acc[0][4 * j + 1],
                                                                       wg == 0 ? acc[1][4 * j + 2] : acc[0][4 * j + 2], wg == 0 ? acc[1][4 * j + 3] : acc[0][4 * j + 3]);
                }
                if (s >= 0) mbar_wait(sb + B_EXP, s & 1);
                nbar_sync(1, 256);
                uint32_t pk[8];
                #pragma unroll
                for (int j = 0; j < 4; j++) {
                    float4 r = red[(wg * 4 + j) * 128 + wtid];
                    pk[2 * j] = pack_bf16((wg == 0 ? acc[0][4 * j] : acc[1][4 * j]) + r.x, (wg == 0 ? acc[0][4 * j + 1] : acc[1][4 * j + 1]) + r.y);
                    pk[2 * j + 1] = pack_bf16((wg == 0 ? acc[0][4 * j + 2] : acc[1][4 * j + 2]) + r.z, (wg == 0 ? acc[0][4 * j + 3] : acc[1][4 * j + 3]) + r.w);
                }
                const uint32_t dst = (rank == 2) ? sb + SM_VT + sln * 10240 + wg * 5120 + 1024 : (wg == 0 ? sb + SM_QT : sb + SM_KT + sln * 5120 + 1024);
                #pragma unroll
                for (int jj = 0; jj < 2; jj++) {
                    int mi = lane >> 3, tok = 8 * (2 * jj + (mi >> 1)) + (lane & 7), chunk = 2 * warp + (mi & 1);
                    stsm4t(dst + tok * 128 + ((chunk ^ (tok & 7)) << 4), pk[4 * jj], pk[4 * jj + 1], pk[4 * jj + 2], pk[4 * jj + 3]);
                }
                fence_async();
                nbar_sync(1, 256);
                if (rank == 2 && lane == 0 && cw < 4 && sn < NSEG - 1) {
                    const uint32_t off = SM_VT + sln * 10240 + (cw & 1) * 5120 + 1024;
                    const uint32_t rb = mapa(sb, cw >> 1);
                    bulk_s2c(rb + off, sb + off, 4096, rb + B_V + 8 * sln);
                }
                if (cw == 0 && s >= 0) TR(13);
            }
        }
        nbar_arrive(3, 384);
        __syncwarp();
        cluster_sync_all();
    }
}

#define NAUX 36
__device__ __align__(1024) bf16 g_Oimg[16 * 64 * 128 * 64];
__device__ float    g_part[4 * SEQ * DM];
__device__ float    g_part31[2 * 13 * 64 * DM];
__device__ unsigned g_ocnt[32];
__device__ unsigned g_gcnt[32][2];
__device__ unsigned g_ssmcnt, g_auxdone, g_taskctr, g_gemmctr;
#define NATT 8
#define ATR(i) do {} while (0)
#define ATRID(i, id) do {} while (0)

__device__ __forceinline__ void wait_counter(const unsigned* p, unsigned target) {
    int guard = 0;
    while ((int)(ld_acquire(p) - target) < 0 && ++guard < (1 << 22)) __nanosleep(64);
}
__device__ __forceinline__ void fence_async_all() { asm volatile("fence.proxy.async;" ::: "memory"); }
template <int OFF>
__device__ __forceinline__ void wgmma_n192_tB(float (&d)[160], uint64_t da, uint64_t db) {
    asm volatile("wgmma.mma_async.sync.aligned.m64n192k16.f32.bf16.bf16 {%0,%1,%2,%3,%4,%5,%6,%7,%8,%9,%10,%11,%12,%13,%14,%15,%16,%17,%18,%19,%20,%21,%22,%23,%24,%25,%26,%27,%28,%29,%30,%31,%32,%33,%34,%35,%36,%37,%38,%39,%40,%41,%42,%43,%44,%45,%46,%47,%48,%49,%50,%51,%52,%53,%54,%55,%56,%57,%58,%59,%60,%61,%62,%63,%64,%65,%66,%67,%68,%69,%70,%71,%72,%73,%74,%75,%76,%77,%78,%79,%80,%81,%82,%83,%84,%85,%86,%87,%88,%89,%90,%91,%92,%93,%94,%95}, %96, %97, 1, 1, 1, 0, 1;\n"
        : "+f"(d[OFF + 0]), "+f"(d[OFF + 1]), "+f"(d[OFF + 2]), "+f"(d[OFF + 3]), "+f"(d[OFF + 4]), "+f"(d[OFF + 5]), "+f"(d[OFF + 6]), "+f"(d[OFF + 7]), "+f"(d[OFF + 8]), "+f"(d[OFF + 9]), "+f"(d[OFF + 10]), "+f"(d[OFF + 11]), "+f"(d[OFF + 12]), "+f"(d[OFF + 13]), "+f"(d[OFF + 14]), "+f"(d[OFF + 15]), "+f"(d[OFF + 16]), "+f"(d[OFF + 17]), "+f"(d[OFF + 18]), "+f"(d[OFF + 19]), "+f"(d[OFF + 20]), "+f"(d[OFF + 21]), "+f"(d[OFF + 22]), "+f"(d[OFF + 23]), "+f"(d[OFF + 24]), "+f"(d[OFF + 25]), "+f"(d[OFF + 26]), "+f"(d[OFF + 27]), "+f"(d[OFF + 28]), "+f"(d[OFF + 29]), "+f"(d[OFF + 30]), "+f"(d[OFF + 31]), "+f"(d[OFF + 32]), "+f"(d[OFF + 33]), "+f"(d[OFF + 34]), "+f"(d[OFF + 35]), "+f"(d[OFF + 36]), "+f"(d[OFF + 37]), "+f"(d[OFF + 38]), "+f"(d[OFF + 39]), "+f"(d[OFF + 40]), "+f"(d[OFF + 41]), "+f"(d[OFF + 42]), "+f"(d[OFF + 43]), "+f"(d[OFF + 44]), "+f"(d[OFF + 45]), "+f"(d[OFF + 46]), "+f"(d[OFF + 47]), "+f"(d[OFF + 48]), "+f"(d[OFF + 49]), "+f"(d[OFF + 50]), "+f"(d[OFF + 51]), "+f"(d[OFF + 52]), "+f"(d[OFF + 53]), "+f"(d[OFF + 54]), "+f"(d[OFF + 55]), "+f"(d[OFF + 56]), "+f"(d[OFF + 57]), "+f"(d[OFF + 58]), "+f"(d[OFF + 59]), "+f"(d[OFF + 60]), "+f"(d[OFF + 61]), "+f"(d[OFF + 62]), "+f"(d[OFF + 63]), "+f"(d[OFF + 64]), "+f"(d[OFF + 65]), "+f"(d[OFF + 66]), "+f"(d[OFF + 67]), "+f"(d[OFF + 68]), "+f"(d[OFF + 69]), "+f"(d[OFF + 70]), "+f"(d[OFF + 71]), "+f"(d[OFF + 72]), "+f"(d[OFF + 73]), "+f"(d[OFF + 74]), "+f"(d[OFF + 75]), "+f"(d[OFF + 76]), "+f"(d[OFF + 77]), "+f"(d[OFF + 78]), "+f"(d[OFF + 79]), "+f"(d[OFF + 80]), "+f"(d[OFF + 81]), "+f"(d[OFF + 82]), "+f"(d[OFF + 83]), "+f"(d[OFF + 84]), "+f"(d[OFF + 85]), "+f"(d[OFF + 86]), "+f"(d[OFF + 87]), "+f"(d[OFF + 88]), "+f"(d[OFF + 89]), "+f"(d[OFF + 90]), "+f"(d[OFF + 91]), "+f"(d[OFF + 92]), "+f"(d[OFF + 93]), "+f"(d[OFF + 94]), "+f"(d[OFF + 95])
        : "l"(da), "l"(db));
}
template <int OFF>
__device__ __forceinline__ void wgmma_n128_tB(float (&d)[160], uint64_t da, uint64_t db) {
    asm volatile("wgmma.mma_async.sync.aligned.m64n128k16.f32.bf16.bf16 {%0,%1,%2,%3,%4,%5,%6,%7,%8,%9,%10,%11,%12,%13,%14,%15,%16,%17,%18,%19,%20,%21,%22,%23,%24,%25,%26,%27,%28,%29,%30,%31,%32,%33,%34,%35,%36,%37,%38,%39,%40,%41,%42,%43,%44,%45,%46,%47,%48,%49,%50,%51,%52,%53,%54,%55,%56,%57,%58,%59,%60,%61,%62,%63}, %64, %65, 1, 1, 1, 0, 1;\n"
        : "+f"(d[OFF + 0]), "+f"(d[OFF + 1]), "+f"(d[OFF + 2]), "+f"(d[OFF + 3]), "+f"(d[OFF + 4]), "+f"(d[OFF + 5]), "+f"(d[OFF + 6]), "+f"(d[OFF + 7]), "+f"(d[OFF + 8]), "+f"(d[OFF + 9]), "+f"(d[OFF + 10]), "+f"(d[OFF + 11]), "+f"(d[OFF + 12]), "+f"(d[OFF + 13]), "+f"(d[OFF + 14]), "+f"(d[OFF + 15]), "+f"(d[OFF + 16]), "+f"(d[OFF + 17]), "+f"(d[OFF + 18]), "+f"(d[OFF + 19]), "+f"(d[OFF + 20]), "+f"(d[OFF + 21]), "+f"(d[OFF + 22]), "+f"(d[OFF + 23]), "+f"(d[OFF + 24]), "+f"(d[OFF + 25]), "+f"(d[OFF + 26]), "+f"(d[OFF + 27]), "+f"(d[OFF + 28]), "+f"(d[OFF + 29]), "+f"(d[OFF + 30]), "+f"(d[OFF + 31]), "+f"(d[OFF + 32]), "+f"(d[OFF + 33]), "+f"(d[OFF + 34]), "+f"(d[OFF + 35]), "+f"(d[OFF + 36]), "+f"(d[OFF + 37]), "+f"(d[OFF + 38]), "+f"(d[OFF + 39]), "+f"(d[OFF + 40]), "+f"(d[OFF + 41]), "+f"(d[OFF + 42]), "+f"(d[OFF + 43]), "+f"(d[OFF + 44]), "+f"(d[OFF + 45]), "+f"(d[OFF + 46]), "+f"(d[OFF + 47]), "+f"(d[OFF + 48]), "+f"(d[OFF + 49]), "+f"(d[OFF + 50]), "+f"(d[OFF + 51]), "+f"(d[OFF + 52]), "+f"(d[OFF + 53]), "+f"(d[OFF + 54]), "+f"(d[OFF + 55]), "+f"(d[OFF + 56]), "+f"(d[OFF + 57]), "+f"(d[OFF + 58]), "+f"(d[OFF + 59]), "+f"(d[OFF + 60]), "+f"(d[OFF + 61]), "+f"(d[OFF + 62]), "+f"(d[OFF + 63])
        : "l"(da), "l"(db));
}
__device__ __forceinline__ void stsm4(uint32_t addr, uint32_t r0, uint32_t r1, uint32_t r2, uint32_t r3) {
    asm volatile("stmatrix.sync.aligned.m8n8.x4.shared.b16 [%0], {%1,%2,%3,%4};" :: "r"(addr), "r"(r0), "r"(r1), "r"(r2), "r"(r3) : "memory");
}

#define AX_BAR   0
#define NST_G 4
#define AX_EMPTY (AX_BAR + 16 + 8 * NST_G)
#define AX_DATA  1024
#define AX_UNIT  28672
#define AX_STAGE 57344
#define AX_TOTAL (AX_DATA + 8 * AX_UNIT)

__device__ __forceinline__ void attn_compute(unsigned char* smem, uint32_t sb, uint32_t buf, int warp, int lane);
__device__ __forceinline__ void attn_producer(unsigned char* smem, int hg, unsigned epoch) {
    const uint32_t sb = smem_u32(smem);
    const int lane = threadIdx.x & 31;
    {
        for (int s = 0; s < NSEG; s++) {
            const uint32_t buf = AX_DATA + (s & 1) * (4 * AX_UNIT), bar = sb + AX_BAR + 8 * (s & 1);
            if (lane < 4) wait_counter(&g_flag[s][4 * hg + lane], (epoch + 1) * 3u);
            if (lane == 4) mbar_wait_sleep(sb + AX_EMPTY + 8 * (s & 1), ((s >> 1) & 1) ^ 1);
            __syncwarp();
            if (lane == 0) mbar_expect_tx(bar, 4 * AX_UNIT);
            __syncwarp();
            if (lane < 24) {
                fence_async_all();
                const int u = lane / 6, r = lane % 6, hf = r & 1, kind = r >> 1;
                const uint32_t ub = sb + buf + u * AX_UNIT;
                const size_t img = ((size_t)(s * NH + 4 * hg + u) * 2) + hf;
                if (kind == 0) bulk_g2s(ub + hf * 4096, g_Qimg + img * 2048, 4096, bar);
                else if (kind == 1) bulk_g2s(ub + 8192 + hf * 5120, g_Kimg + img * 2560, 5120, bar);
                else bulk_g2s(ub + 18432 + hf * 5120, g_Vimg + img * 2560, 5120, bar);
            }
            __syncwarp();
        }
    }
}
__device__ __forceinline__ void attn_loop(unsigned char* smem, int hg, unsigned epoch) {
    const uint32_t sb = smem_u32(smem);
    const int tid = threadIdx.x, warp = tid >> 5, lane = tid & 31;
    for (int s = 0; s < NSEG; s++) {
        const uint32_t buf = AX_DATA + (s & 1) * (4 * AX_UNIT), bar = sb + AX_BAR + 8 * (s & 1);
        mbar_wait_sleep(bar, (s >> 1) & 1);
        if (s >= 36) ATR(2 + 2 * (s - 36));
        attn_compute(smem, sb, buf, warp, lane);
        if (s >= 36) ATR(3 + 2 * (s - 36));
        fence_async();
        __syncwarp();
        if (lane == 0) mbar_arrive(sb + AX_EMPTY + 16 + 8 * (s & 1));
    }
}
__device__ __forceinline__ void attn_storer(unsigned char* smem, int hg) {
    const uint32_t sb = smem_u32(smem);
    const int lane = threadIdx.x & 31;
    for (int s = 0; s < NSEG; s++) {
        const uint32_t buf = AX_DATA + (s & 1) * (4 * AX_UNIT);
        mbar_wait_sleep(sb + AX_EMPTY + 16 + 8 * (s & 1), (s >> 1) & 1);
        if (lane < 8) {
            const int uu = lane >> 1, hf = lane & 1, hh = 4 * hg + uu;
            bulk_s2g(g_Oimg + (((size_t)(s >> 2) * 64 + hh * 2 + hf) * 128 + (s & 3) * 32) * 64, sb + buf + uu * AX_UNIT + hf * 4096, 4096);
            bulk_commit();
            bulk_wait_read0();
            mbar_arrive(sb + AX_EMPTY + 8 * (s & 1));
            bulk_wait0();
            fence_async_all();
            __threadfence();
            atomicAdd(&g_ocnt[s >> 1], 1u);
        }
        __syncwarp();
    }
}
__device__ __forceinline__ void attn_compute(unsigned char* smem, uint32_t sb, uint32_t buf, int warp, int lane) {
    const int g = lane >> 2, t = lane & 3;
    const int u = warp >> 1, qh = warp & 1;
    const uint32_t ub = sb + buf + u * AX_UNIT;
    float sc[5][4];
    #pragma unroll
    for (int j = 0; j < 5; j++) { sc[j][0] = sc[j][1] = sc[j][2] = sc[j][3] = 0.f; }
    #pragma unroll
    for (int ks = 0; ks < 8; ks++) {
        const int hf = ks >> 2, c0 = (ks & 3) * 2;
        uint32_t a[4];
        { int mi = lane >> 3, row = 16 * qh + (mi & 1) * 8 + (lane & 7), chunk = c0 + (mi >> 1);
          ldsm4(a, ub + hf * 4096 + row * 128 + ((chunk ^ (row & 7)) << 4)); }
        #pragma unroll
        for (int jp = 0; jp < 3; jp++) {
            uint32_t b[4];
            int mi = lane >> 3, nt = 2 * jp + (mi >> 1); if (nt > 4) nt = 4;
            int row = 8 * nt + (lane & 7), chunk = c0 + (mi & 1);
            ldsm4(b, ub + 8192 + hf * 5120 + row * 128 + ((chunk ^ (row & 7)) << 4));
            mma_bf16(sc[2 * jp], a[0], a[1], a[2], a[3], b[0], b[1]);
            if (jp < 2) mma_bf16(sc[2 * jp + 1], a[0], a[1], a[2], a[3], b[2], b[3]);
        }
    }
    uint32_t pa[3][4];
    {
        const float sc2 = 0.08838834764831845f * 1.4426950408889634f;
        float mx0 = -3.0e38f, mx1 = -3.0e38f;
        const int q0 = 16 * qh + g, q1 = q0 + 8;
        #pragma unroll
        for (int j = 0; j < 5; j++)
            #pragma unroll
            for (int e = 0; e < 2; e++) {
                int key = 8 * j + 2 * t + e - 8;
                sc[j][e] = (key <= q0) ? sc[j][e] * sc2 : -3.0e38f;
                sc[j][2 + e] = (key <= q1) ? sc[j][2 + e] * sc2 : -3.0e38f;
                mx0 = fmaxf(mx0, sc[j][e]); mx1 = fmaxf(mx1, sc[j][2 + e]);
            }
        mx0 = fmaxf(mx0, __shfl_xor_sync(~0u, mx0, 1)); mx0 = fmaxf(mx0, __shfl_xor_sync(~0u, mx0, 2));
        mx1 = fmaxf(mx1, __shfl_xor_sync(~0u, mx1, 1)); mx1 = fmaxf(mx1, __shfl_xor_sync(~0u, mx1, 2));
        float s0 = 0.f, s1 = 0.f;
        #pragma unroll
        for (int j = 0; j < 5; j++)
            #pragma unroll
            for (int e = 0; e < 2; e++) {
                sc[j][e] = ex2_approx(sc[j][e] - mx0); sc[j][2 + e] = ex2_approx(sc[j][2 + e] - mx1);
                s0 += sc[j][e]; s1 += sc[j][2 + e];
            }
        s0 += __shfl_xor_sync(~0u, s0, 1); s0 += __shfl_xor_sync(~0u, s0, 2);
        s1 += __shfl_xor_sync(~0u, s1, 1); s1 += __shfl_xor_sync(~0u, s1, 2);
        const float i0 = __frcp_rn(s0), i1 = __frcp_rn(s1);
        #pragma unroll
        for (int k = 0; k < 3; k++) {
            pa[k][0] = pack_bf16(sc[2 * k][0] * i0, sc[2 * k][1] * i0);
            pa[k][1] = pack_bf16(sc[2 * k][2] * i1, sc[2 * k][3] * i1);
            if (k < 2) { pa[k][2] = pack_bf16(sc[2 * k + 1][0] * i0, sc[2 * k + 1][1] * i0); pa[k][3] = pack_bf16(sc[2 * k + 1][2] * i1, sc[2 * k + 1][3] * i1); }
            else { pa[k][2] = 0u; pa[k][3] = 0u; }
        }
    }
    __syncwarp();
    nbar_sync(5 + u, 64);
    #pragma unroll
    for (int np = 0; np < 8; np++) {
        const int hf = np >> 2, c0 = (np & 3) * 2;
        float o0[4] = {0, 0, 0, 0}, o1[4] = {0, 0, 0, 0};
        #pragma unroll
        for (int k = 0; k < 3; k++) {
            uint32_t b[4];
            int mi = lane >> 3;
            int row = 16 * k + (mi & 1) * 8 + (lane & 7); if (row > 39) row = 39 - 7 + (lane & 7);
            int chunk = c0 + (mi >> 1);
            ldsm4t(b, ub + 18432 + hf * 5120 + row * 128 + ((chunk ^ (row & 7)) << 4));
            mma_bf16(o0, pa[k][0], pa[k][1], pa[k][2], pa[k][3], b[0], k < 2 ? b[1] : 0u);
            mma_bf16(o1, pa[k][0], pa[k][1], pa[k][2], pa[k][3], b[2], k < 2 ? b[3] : 0u);
        }
        int mi = lane >> 3, row = 16 * qh + (mi & 1) * 8 + (lane & 7), chunk = c0 + (mi >> 1);
        stsm4(ub + hf * 4096 + row * 128 + ((chunk ^ (row & 7)) << 4), pack_bf16(o0[0], o0[1]), pack_bf16(o0[2], o0[3]), pack_bf16(o1[0], o1[1]), pack_bf16(o1[2], o1[3]));
    }
}

template <int V> struct IntC { static constexpr int value = V; };
struct Task { int type, rb, c, k0, nch, plane; };
#define NFINE 30
#define NGEMM (8 + 144 + 8 * 2 + 4 + 8 * 6 + 26 * 2 + 16 * 2)
__device__ __forceinline__ Task decode_task(int j) {
    Task t; t.type = 0; t.rb = 0; t.c = 0; t.k0 = 0; t.nch = 16; t.plane = 0;
    auto H = [&](int rb, int i) { t.type = 1; t.rb = rb; t.c = i & 1; t.plane = i >> 1; t.k0 = t.plane * 16; };
    auto CF = [&](int rb, int i) { t.type = 2; t.rb = rb; t.c = i & 1; t.k0 = rb * 64 + (i >> 1) * 16; t.nch = 16; };
    auto H13 = [&](int rb, int i) { t.type = 1; t.rb = rb; t.c = i & 1; t.plane = i >> 1; t.k0 = t.plane * 5; t.nch = (t.plane == 12) ? 4 : 5; };
    auto C13 = [&](int rb, int i) { t.type = 2; t.rb = rb; t.c = i & 1; t.k0 = rb * 64 + (i >> 1) * 8; t.nch = 8; };
    if (j >= NGEMM) { t.type = 3; return t; }
    if (j < 8) { t.c = j & 1; t.plane = j >> 1; t.k0 = t.plane * 16; return t; }
    j -= 8;
    if (j < 144) {
        const int q = j / 12, r = j % 12;
        if (r < 8) { t.rb = 2 * (q + 1); t.c = r & 1; t.plane = r >> 1; t.k0 = t.plane * 16; }
        else { t.type = 2; t.rb = 2 * q + ((r - 8) >> 1); t.c = r & 1; t.k0 = t.rb * 64; t.nch = 64; }
        return t;
    }
    j -= 144;
    if (j < 8) { H(26, j); return t; }
    j -= 8;
    if (j < 8) { H(27, j); return t; }
    j -= 8;
    if (j < 4) { t.type = 2; t.rb = 24 + (j >> 1); t.c = j & 1; t.k0 = t.rb * 64; t.nch = 64; return t; }
    j -= 4;
    if (j < 8) { H(28, j); return t; }
    j -= 8;
    if (j < 8) { CF(26, j); return t; }
    j -= 8;
    if (j < 8) { H(29, j); return t; }
    j -= 8;
    if (j < 8) { CF(27, j); return t; }
    j -= 8;
    if (j < 26) { H13(30, j); return t; }
    j -= 26;
    if (j < 8) { CF(28, j); return t; }
    j -= 8;
    if (j < 8) { CF(29, j); return t; }
    j -= 8;
    if (j < 26) { H13(31, j); return t; }
    j -= 26;
    if (j < 16) { C13(30, j); return t; }
    j -= 16;
    C13(31, j);
    return t;
}
__device__ __forceinline__ void gemm_producer(unsigned char* smem, const CUtensorMap* womap, unsigned epoch, volatile int* s_tasks) {
    const uint32_t sb = smem_u32(smem);
    uint32_t st = 0, ph = 1;
    for (int n = 0;; n++) {
        const int j = (int)(atomicAdd(&g_gemmctr, 1u) - epoch * (unsigned)(NGEMM + NAUX - NATT));
        const Task t = decode_task(j);
        if (t.type <= 1) {
            wait_counter(&g_ocnt[t.rb], (epoch + 1) * 128u);
            if (t.type == 0) wait_counter(&g_ocnt[t.rb + 1], (epoch + 1) * 128u);
            fence_async_all();
        } else if (t.type == 2) {
            wait_counter(&g_gcnt[t.rb][t.c], (epoch + 1) * (t.rb >= NFINE ? 13u : 4u));
            wait_counter(&g_ssmcnt, (epoch + 1) * 80u);
        }
        const int nch = (t.type <= 1) ? t.nch : 1;
        for (int kc = 0; kc < nch; kc++) {
            mbar_wait_sleep(sb + AX_EMPTY + 8 * st, ph);
            const uint32_t a = sb + AX_DATA + st * AX_STAGE, bar = sb + AX_BAR + 16 + 8 * st;
            if (kc == 0) s_tasks[n & 7] = j;
            if (t.type > 1) mbar_arrive(bar);
            else {
                const bf16* asrc = g_Oimg + ((size_t)(t.rb >> 1) * 64 + t.k0 + kc) * 8192 + (t.rb & 1) * 4096;
                if (t.type == 0) { mbar_expect_tx(bar, AX_STAGE); bulk_g2s(a, asrc, 8192, bar); bulk_g2s(a + 8192, asrc + 4096, 8192, bar); }
                else { mbar_expect_tx(bar, AX_STAGE - 8192); bulk_g2s(a, asrc, 8192, bar); }
                #pragma unroll
                for (int b = 0; b < 5; b++) tma_load_2d(a + 16384 + b * 8192, womap, t.c * 320 + b * 64, (t.k0 + kc) * 64, bar);
            }
            if (++st == NST_G) { st = 0; ph ^= 1; }
        }
        if (t.type == 3) break;
    }
}
__device__ __forceinline__ void gemm_signaller(volatile int* s_done) {
    for (int n = 0;; n++) {
        nbar_sync(2, 288);
        const int j = s_done[n & 7];
        if (j < 0) break;
        if ((threadIdx.x & 31) == 0) {
            const Task t = decode_task(j);
            __threadfence();
            atomicAdd(&g_gcnt[t.rb][t.c], 1u);
            if (t.type == 0) atomicAdd(&g_gcnt[t.rb + 1][t.c], 1u);
        }
        __syncwarp();
    }
}
__device__ __forceinline__ void gemm_consumer(unsigned char* smem, bf16* __restrict__ out, volatile int* s_tasks, volatile int* s_done) {
    const uint32_t sb = smem_u32(smem);
    const int tid = threadIdx.x, lane = tid & 31;
    const int wg = __shfl_sync(~0u, tid >> 7, 0), warp = __shfl_sync(~0u, (tid >> 5) & 3, 0);
    uint32_t st = 0, ph = 0;
    int ndone = 0;
    for (int n = 0;; n++) {
        mbar_wait_sleep(sb + AX_BAR + 16 + 8 * st, ph);
        const Task t = decode_task(__shfl_sync(~0u, s_tasks[n & 7], 0));
        if (t.type > 1) {
            nbar_sync(1, 256);
            if ((tid & 127) == 0) mbar_arrive(sb + AX_EMPTY + 8 * st);
            if (++st == NST_G) { st = 0; ph ^= 1; }
            if (t.type == 3) break;
            const int np = (t.rb >= NFINE) ? 13 : 4;
            const float* pbase = (t.rb >= NFINE) ? g_part31 + (size_t)(t.rb - NFINE) * 13 * 64 * DM - (size_t)t.rb * 64 * DM : g_part;
            const size_t pstride = (t.rb >= NFINE) ? (size_t)64 * DM : (size_t)SEQ * DM;
            auto combine = [&](int i, auto NP) {
                const int r = t.k0 + i / 80, cc = t.c * 320 + (i % 80) * 4;
                float4 v[NP.value];
                #pragma unroll
                for (int q = 0; q < NP.value; q++) v[q] = __ldcg(reinterpret_cast<const float4*>(pbase + q * pstride + (size_t)r * DM + cc));
                const float gt = __ldcg(g_g + r);
                const uint2 bb = __ldcg(reinterpret_cast<const uint2*>(g_b + (size_t)r * DM + cc));
                float4 a = v[0];
                #pragma unroll
                for (int q = 1; q < NP.value; q++) { a.x += v[q].x; a.y += v[q].y; a.z += v[q].z; a.w += v[q].w; }
                const float b0 = __uint_as_float(bb.x << 16), b1 = __uint_as_float(bb.x & 0xffff0000u), b2 = __uint_as_float(bb.y << 16), b3 = __uint_as_float(bb.y & 0xffff0000u);
                uint2 o; o.x = pack_bf16(gt * a.x + (1.f - gt) * b0, gt * a.y + (1.f - gt) * b1); o.y = pack_bf16(gt * a.z + (1.f - gt) * b2, gt * a.w + (1.f - gt) * b3);
                *reinterpret_cast<uint2*>(out + (size_t)r * DM + cc) = o;
            };
            if (np == 4) {
                const int nit = t.nch * 80 / 256;
                for (int it0 = 0; it0 < nit; it0 += 5) {
                    #pragma unroll
                    for (int it = 0; it < 5; it++) combine(tid + 256 * (it0 + it), IntC<4>());
                }
            } else {
                #pragma unroll
                for (int it = 0; it < 3; it++) { const int i = tid + 256 * it; if (i < 640) combine(i, IntC<13>()); }
            }
            if (n < 56) ATRID(6 + n, s_tasks[n & 7]);
            continue;
        }
        const int g = lane >> 2, tq = lane & 3;
        if (t.type == 0) {
            float acc[160];
            #pragma unroll
            for (int i = 0; i < 160; i++) acc[i] = 0.f;
            uint32_t prev = 0;
            for (int kc = 0; kc < 16; kc++) {
                mbar_wait(sb + AX_BAR + 16 + 8 * st, ph);
                const uint32_t a = sb + AX_DATA + st * AX_STAGE;
                const uint64_t da = make_desc(a + wg * 8192, 16, 1024), db = make_desc(a + 16384, 8192, 1024);
                wg_fence();
                #pragma unroll
                for (int ks = 0; ks < 4; ks++) {
                    wgmma_n192_tB<0>(acc, da + ks * 2, db + ks * 128);
                    wgmma_n128_tB<96>(acc, da + ks * 2, db + ks * 128 + 3 * 512);
                }
                wg_commit();
                asm volatile("wgmma.wait_group.sync.aligned 1;" ::: "memory");
                if (kc > 0 && (tid & 127) == 0) mbar_arrive(sb + AX_EMPTY + 8 * prev);
                prev = st;
                if (++st == NST_G) { st = 0; ph ^= 1; }
            }
            wg_wait0();
            if ((tid & 127) == 0) mbar_arrive(sb + AX_EMPTY + 8 * prev);
            float* base = g_part + ((size_t)t.plane * SEQ + t.rb * 64 + wg * 64 + warp * 16 + g) * DM + t.c * 320 + 2 * tq;
            #pragma unroll
            for (int q = 0; q < 40; q++) {
                *reinterpret_cast<float2*>(base + q * 8) = make_float2(acc[4 * q], acc[4 * q + 1]);
                *reinterpret_cast<float2*>(base + 8 * DM + q * 8) = make_float2(acc[4 * q + 2], acc[4 * q + 3]);
            }
        } else {
            float* base = (t.rb >= NFINE ? g_part31 + (size_t)((t.rb - NFINE) * 13 + t.plane) * 64 * DM : g_part + ((size_t)t.plane * SEQ + t.rb * 64) * DM) + (size_t)(warp * 16 + g) * DM + t.c * 320 + 2 * tq;
            if (wg == 0) {
                float acc[160];
                #pragma unroll
                for (int i = 0; i < 96; i++) acc[i] = 0.f;
                uint32_t prev = 0;
                for (int kc = 0; kc < t.nch; kc++) {
                    mbar_wait(sb + AX_BAR + 16 + 8 * st, ph);
                    const uint32_t a = sb + AX_DATA + st * AX_STAGE;
                    const uint64_t da = make_desc(a, 16, 1024), db = make_desc(a + 16384, 8192, 1024);
                    wg_fence();
                    #pragma unroll
                    for (int ks = 0; ks < 4; ks++) wgmma_n192_tB<0>(acc, da + ks * 2, db + ks * 128);
                    wg_commit();
                    asm volatile("wgmma.wait_group.sync.aligned 1;" ::: "memory");
                    if (kc > 0 && (tid & 127) == 0) mbar_arrive(sb + AX_EMPTY + 8 * prev);
                    prev = st;
                    if (++st == NST_G) { st = 0; ph ^= 1; }
                }
                wg_wait0();
                if ((tid & 127) == 0) mbar_arrive(sb + AX_EMPTY + 8 * prev);
                #pragma unroll
                for (int q = 0; q < 24; q++) {
                    *reinterpret_cast<float2*>(base + q * 8) = make_float2(acc[4 * q], acc[4 * q + 1]);
                    *reinterpret_cast<float2*>(base + 8 * DM + q * 8) = make_float2(acc[4 * q + 2], acc[4 * q + 3]);
                }
            } else {
                float acc[160];
                #pragma unroll
                for (int i = 96; i < 160; i++) acc[i] = 0.f;
                uint32_t prev = 0;
                for (int kc = 0; kc < t.nch; kc++) {
                    mbar_wait(sb + AX_BAR + 16 + 8 * st, ph);
                    const uint32_t a = sb + AX_DATA + st * AX_STAGE;
                    const uint64_t da = make_desc(a, 16, 1024), db = make_desc(a + 16384, 8192, 1024);
                    wg_fence();
                    #pragma unroll
                    for (int ks = 0; ks < 4; ks++) wgmma_n128_tB<96>(acc, da + ks * 2, db + ks * 128 + 3 * 512);
                    wg_commit();
                    asm volatile("wgmma.wait_group.sync.aligned 1;" ::: "memory");
                    if (kc > 0 && (tid & 127) == 0) mbar_arrive(sb + AX_EMPTY + 8 * prev);
                    prev = st;
                    if (++st == NST_G) { st = 0; ph ^= 1; }
                }
                wg_wait0();
                if ((tid & 127) == 0) mbar_arrive(sb + AX_EMPTY + 8 * prev);
                #pragma unroll
                for (int q = 24; q < 40; q++) {
                    *reinterpret_cast<float2*>(base + q * 8) = make_float2(acc[4 * q], acc[4 * q + 1]);
                    *reinterpret_cast<float2*>(base + 8 * DM + q * 8) = make_float2(acc[4 * q + 2], acc[4 * q + 3]);
                }
            }
        }
        if (tid == 0) s_done[ndone & 7] = s_tasks[n & 7];
        ndone++;
        nbar_arrive(2, 288);
        if (n < 56) ATRID(6 + n, s_tasks[n & 7]);
    }
    if (tid == 0) s_done[ndone & 7] = -1;
    nbar_arrive(2, 288);
}

__global__ void __launch_bounds__(384, 1)
k_aux(const __grid_constant__ CUtensorMap womap, const bf16* __restrict__ x, const bf16* __restrict__ A_re, const bf16* __restrict__ A_im,
      const bf16* __restrict__ B_re, const bf16* __restrict__ B_im, const bf16* __restrict__ C_re, const bf16* __restrict__ C_im,
      const bf16* __restrict__ log_dt, const bf16* __restrict__ Dskip, const bf16* __restrict__ gw, bf16* __restrict__ out) {
    extern __shared__ __align__(1024) unsigned char smem[];
    const uint32_t sb = smem_u32(smem);
    const int tid = threadIdx.x, warp = tid >> 5, lane = tid & 31;
    __shared__ unsigned s_epoch;
    __shared__ int s_task, s_tasks[8], s_done[8];
    if (tid == 0) {
        for (int i = 0; i < 2 + NST_G; i++) mbar_init(sb + AX_BAR + 8 * i, 1);
        for (int i = 0; i < NST_G; i++) mbar_init(sb + AX_EMPTY + 8 * i, blockIdx.x < NATT ? 8 : 2);
        asm volatile("fence.mbarrier_init.release.cluster;" ::: "memory");
        s_epoch = *reinterpret_cast<volatile unsigned*>(&g_epoch);
    }
    __syncthreads();
    const unsigned epoch = s_epoch;
    ATR(0);
    const int wg = __shfl_sync(~0u, tid >> 7, 0);
    if (wg == 2) {
        asm volatile("setmaxnreg.dec.sync.aligned.u32 40;");
        if (blockIdx.x < NATT) { if (warp == 8) attn_producer(smem, blockIdx.x, epoch); else if (warp == 9) attn_storer(smem, blockIdx.x); }
        else {
            nbar_sync(3, 384);
            if (warp == 8) { if (lane == 0) gemm_producer(smem, &womap, epoch, s_tasks); }
            else if (warp == 9) gemm_signaller(s_done);
        }
        __syncwarp();
        nbar_sync(4, 384);
    } else {
        asm volatile("setmaxnreg.inc.sync.aligned.u32 232;");
        if (blockIdx.x < NATT) attn_loop(smem, blockIdx.x, epoch);
        else {
            int ntask = 0;
            for (;;) {
                nbar_sync(1, 256);
                if (tid == 0) s_task = (int)(atomicAdd(&g_taskctr, 1u) - epoch * (unsigned)(80 + NAUX - NATT));
                nbar_sync(1, 256);
                const int task = s_task;
                if (task >= 80) break;
                for (int r = task * 26 + warp; r < min(SEQ, task * 26 + 26); r += 8) {
                    float sum = 0.f;
                    for (int i = lane * 2; i < DM; i += 64) {
                        __nv_bfloat162 xv = *reinterpret_cast<const __nv_bfloat162*>(x + (size_t)r * DM + i), wv = *reinterpret_cast<const __nv_bfloat162*>(gw + i);
                        sum += bf2f(xv.x) * bf2f(wv.x) + bf2f(xv.y) * bf2f(wv.y);
                    }
                    #pragma unroll
                    for (int o = 16; o; o >>= 1) sum += __shfl_xor_sync(~0u, sum, o);
                    if (lane == 0) g_g[r] = 1.f / (1.f + expf(-sum));
                }
                ssm_group(smem + AX_DATA, task, x, A_re, A_im, B_re, B_im, C_re, C_im, log_dt, Dskip);
                nbar_sync(1, 256);
                if (tid == 0) { __threadfence(); atomicAdd(&g_ssmcnt, 1u); }
                if (ntask < 4) ATR(2 + ntask);
                ntask++;
            }
            fence_async();
            nbar_sync(3, 384);
            gemm_consumer(smem, out, s_tasks, s_done);
        }
        nbar_sync(4, 384);
        if (tid == 0) {
            __threadfence();
            unsigned old = atomicAdd(&g_auxdone, 1u);
            if (old == NAUX - 1) { g_auxdone = 0; __threadfence(); atomicAdd(&g_epoch, 1u); }
        }
    }
    asm volatile("griddepcontrol.wait;" ::: "memory");
}

extern "C" void kernel_launch(void* const* d_in, const int* in_sizes, int n_in, void* d_out, int out_size) {
    const bf16* x = (const bf16*)d_in[0];
    const bf16* mem0 = (const bf16*)d_in[1];
    const bf16* Wq = (const bf16*)d_in[2];
    const bf16* Wk = (const bf16*)d_in[3];
    const bf16* Wv = (const bf16*)d_in[4];
    const bf16* Wo = (const bf16*)d_in[5];
    const bf16 *A_re = (const bf16*)d_in[8], *A_im = (const bf16*)d_in[9], *B_re = (const bf16*)d_in[10], *B_im = (const bf16*)d_in[11];
    const bf16 *C_re = (const bf16*)d_in[12], *C_im = (const bf16*)d_in[13], *log_dt = (const bf16*)d_in[14], *Dskip = (const bf16*)d_in[15];
    const bf16* gw = (const bf16*)d_in[16];
    bf16* out = (bf16*)d_out;
    cudaStream_t st = cudaStreamPerThread;
    static bool init = false;
    static CUtensorMap xmap, womap, wqmap, wkmap, wvmap;
    static const void* xmap_ptr = nullptr; static const void* womap_ptr = nullptr; static const void* w_ptr[3] = {nullptr, nullptr, nullptr};
    if (!init) {
        cudaFuncSetAttribute(k_chain, cudaFuncAttributeMaxDynamicSharedMemorySize, SM_TOTAL);
        cudaFuncSetAttribute(k_aux, cudaFuncAttributeMaxDynamicSharedMemorySize, AX_TOTAL);
        init = true;
    }
    if (xmap_ptr != (const void*)x || womap_ptr != (const void*)Wo || w_ptr[0] != Wq || w_ptr[1] != Wk || w_ptr[2] != Wv) {
        void* fn = nullptr; cudaDriverEntryPointQueryResult qres;
        cudaGetDriverEntryPoint("cuTensorMapEncodeTiled", &fn, cudaEnableDefault, &qres);
        typedef CUresult (*EncFn)(CUtensorMap*, CUtensorMapDataType, cuuint32_t, void*, const cuuint64_t*, const cuuint64_t*, const cuuint32_t*, const cuuint32_t*,
                                  CUtensorMapInterleave, CUtensorMapSwizzle, CUtensorMapL2promotion, CUtensorMapFloatOOBfill);
        cuuint32_t es[2] = {1, 1};
        {
          cuuint64_t dims[3] = {64, SEQ, 10}; cuuint64_t strides[2] = {DM * 2, 128}; cuuint32_t box[3] = {64, 32, 10}; cuuint32_t es3[3] = {1, 1, 1};
          ((EncFn)fn)(&xmap, CU_TENSOR_MAP_DATA_TYPE_BFLOAT16, 3, (void*)x, dims, strides, box, es3, CU_TENSOR_MAP_INTERLEAVE_NONE, CU_TENSOR_MAP_SWIZZLE_128B,
                      CU_TENSOR_MAP_L2_PROMOTION_L2_128B, CU_TENSOR_MAP_FLOAT_OOB_FILL_NONE); }
        { cuuint64_t dims[2] = {DM, HD}; cuuint64_t strides[1] = {DM * 2}; cuuint32_t box[2] = {64, 64};
          ((EncFn)fn)(&womap, CU_TENSOR_MAP_DATA_TYPE_BFLOAT16, 2, (void*)Wo, dims, strides, box, es, CU_TENSOR_MAP_INTERLEAVE_NONE, CU_TENSOR_MAP_SWIZZLE_128B,
                      CU_TENSOR_MAP_L2_PROMOTION_L2_128B, CU_TENSOR_MAP_FLOAT_OOB_FILL_NONE); }
        { cuuint64_t dims[2] = {HD, DM}; cuuint64_t strides[1] = {HD * 2}; cuuint32_t box[2] = {64, 128};
          const bf16* ws[3] = {Wq, Wk, Wv}; CUtensorMap* ms[3] = {&wqmap, &wkmap, &wvmap};
          for (int i = 0; i < 3; i++)
              ((EncFn)fn)(ms[i], CU_TENSOR_MAP_DATA_TYPE_BFLOAT16, 2, (void*)ws[i], dims, strides, box, es, CU_TENSOR_MAP_INTERLEAVE_NONE, CU_TENSOR_MAP_SWIZZLE_128B,
                          CU_TENSOR_MAP_L2_PROMOTION_L2_128B, CU_TENSOR_MAP_FLOAT_OOB_FILL_NONE); }
        xmap_ptr = (const void*)x; womap_ptr = (const void*)Wo; w_ptr[0] = Wq; w_ptr[1] = Wk; w_ptr[2] = Wv;
    }
    k_chain<<<96, 384, SM_TOTAL, st>>>(xmap, wqmap, wkmap, wvmap, womap, x, mem0);
    {
        cudaLaunchConfig_t cfg = {};
        cfg.gridDim = dim3(NAUX); cfg.blockDim = dim3(384); cfg.dynamicSmemBytes = AX_TOTAL; cfg.stream = st;
        cudaLaunchAttribute at[1];
        at[0].id = cudaLaunchAttributeProgrammaticStreamSerialization; at[0].val.programmaticStreamSerializationAllowed = 1;
        cfg.attrs = at; cfg.numAttrs = 1;
        cudaLaunchKernelEx(&cfg, k_aux, womap, x, A_re, A_im, B_re, B_im, C_re, C_im, log_dt, Dskip, gw, out);
    }
}
```

```cpp
#include <cuda_runtime.h>
#include <cuda_bf16.h>
#include <stdint.h>
#include <cuda.h>

typedef __nv_bfloat16 bf16;

#define SEQ 2048
#define DM 640
#define NH 32
#define DH 128
#define NM 8
#define SEG 32
#define NSEG 64
#define NST 128
#define HD 4096

__device__ bf16  g_b[SEQ * DM];
__device__ float g_g[SEQ];

__device__ __forceinline__ float bf2f(bf16 v) { return __bfloat162float(v); }
__device__ __forceinline__ uint32_t pack_bf16(float lo, float hi) {
    uint32_t r; asm("cvt.rn.bf16x2.f32 %0, %1, %2;" : "=r"(r) : "f"(hi), "f"(lo)); return r;
}
__device__ __forceinline__ uint32_t f2tf32(float x) { uint32_t r; asm("cvt.rna.tf32.f32 %0, %1;" : "=r"(r) : "f"(x)); return r; }
__device__ __forceinline__ void mma_tf32(float (&d)[4], uint32_t a0, uint32_t a1, uint32_t a2, uint32_t a3, uint32_t b0, uint32_t b1) {
    asm volatile("mma.sync.aligned.m16n8k8.row.col.f32.tf32.tf32.f32 {%0,%1,%2,%3}, {%4,%5,%6,%7}, {%8,%9}, {%0,%1,%2,%3};\n"
        : "+f"(d[0]), "+f"(d[1]), "+f"(d[2]), "+f"(d[3]) : "r"(a0), "r"(a1), "r"(a2), "r"(a3), "r"(b0), "r"(b1));
}
__device__ __forceinline__ void mma_bf16(float (&d)[4], uint32_t a0, uint32_t a1, uint32_t a2, uint32_t a3, uint32_t b0, uint32_t b1) {
    asm volatile("mma.sync.aligned.m16n8k16.row.col.f32.bf16.bf16.f32 {%0,%1,%2,%3}, {%4,%5,%6,%7}, {%8,%9}, {%0,%1,%2,%3};\n"
        : "+f"(d[0]), "+f"(d[1]), "+f"(d[2]), "+f"(d[3]) : "r"(a0), "r"(a1), "r"(a2), "r"(a3), "r"(b0), "r"(b1));
}
struct cf { float re, im; };
__device__ __forceinline__ cf cmul(cf a, cf b) { cf r; r.re = a.re * b.re - a.im * b.im; r.im = a.re * b.im + a.im * b.re; return r; }
__device__ __forceinline__ cf csq(cf a) { cf r; r.re = a.re * a.re - a.im * a.im; r.im = 2.f * a.re * a.im; return r; }
__device__ __forceinline__ cf cexpL(float zr, float zi, float L) {
    float e = __expf(zr * L);
    float ang = zi * L;
    float k = rintf(ang * 0.15915494309189535f);
    ang = fmaf(-k, 6.2831854820251465f, ang);
    ang = fmaf(-k, -1.7484555314695172e-07f, ang);
    cf r; r.re = e * __cosf(ang); r.im = e * __sinf(ang); return r;
}

#define SSM_CH 8
#define KC_PITCH 648
#define XS_PAD 128
#define XS_PITCH (XS_PAD + 2048 + 8)
#define YS_PITCH (2048 + 8)
#define KT_LEN (2048 + 48)
struct SsmSmem {
    float Kc[SSM_CH][KC_PITCH];
    bf16  xs[SSM_CH][XS_PITCH];
    union {
        bf16  KT[SSM_CH][2][KT_LEN];
        float st[SSM_CH][NST][8];
    } u;
    bf16  ys[SSM_CH][YS_PITCH];
    uint16_t kidx[2048];
};

__device__ __forceinline__ int kc_index(int l) {
    return l < 256 ? l : (l < 512 ? 256 + ((l - 256) >> 1) : (l < 1024 ? 384 + ((l - 512) >> 2) : 512 + ((l - 1024) >> 3)));
}

__device__ __forceinline__ void ssm_group(unsigned char* smem_raw, int grp, const bf16* __restrict__ x, const bf16* __restrict__ A_re, const bf16* __restrict__ A_im,
        const bf16* __restrict__ B_re, const bf16* __restrict__ B_im, const bf16* __restrict__ C_re, const bf16* __restrict__ C_im,
        const bf16* __restrict__ log_dt, const bf16* __restrict__ Dskip) {
    SsmSmem& S = *reinterpret_cast<SsmSmem*>(smem_raw);
    const int tid = threadIdx.x, w = tid >> 5, lane = tid & 31, g = lane >> 2, t = lane & 3;
    const int d0 = grp * SSM_CH;
    asm volatile("bar.sync 1, 256;" ::: "memory");
    #pragma unroll
    for (int it = 0; it < 8; it++) {
        const int l = tid + 256 * it;
        uint4 v = *reinterpret_cast<const uint4*>(x + (size_t)l * DM + d0);
        const bf16* p = reinterpret_cast<const bf16*>(&v);
        const int lr = (l & ~15) | (15 - (l & 15));
        #pragma unroll
        for (int c = 0; c < 8; c++) S.xs[c][XS_PAD + lr] = p[c];
        S.kidx[l] = (uint16_t)((int)bf2f(__float2bfloat16_rn((float)l)) == 2048 ? 640 : kc_index((int)bf2f(__float2bfloat16_rn((float)l))));
    }
    for (int i = tid; i < SSM_CH * XS_PAD / 2; i += 256) reinterpret_cast<uint32_t*>(&S.xs[i / (XS_PAD / 2)][0])[i % (XS_PAD / 2)] = 0u;
    {
        const int d = d0 + w;
        const float dt = bf2f(__float2bfloat16_rn(expf(bf2f(log_dt[d]))));
        #pragma unroll
        for (int i = 0; i < 4; i++) {
            const int n = lane + 32 * i;
            float zr = dt * bf2f(A_re[d * NST + n]), zi = dt * bf2f(A_im[d * NST + n]);
            cf dB; dB.re = dt * bf2f(B_re[d * NST + n]); dB.im = dt * bf2f(B_im[d * NST + n]);
            cf C; C.re = bf2f(C_re[d * NST + n]); C.im = bf2f(C_im[d * NST + n]);
            cf wv = cmul(C, dB);
            cf u8 = cexpL(zr, zi, 8.f), u128 = cexpL(zr, zi, 128.f);
            float* st = S.u.st[w][n];
            *reinterpret_cast<float4*>(st) = make_float4(zr, zi, wv.re, wv.im);
            *reinterpret_cast<float4*>(st + 4) = make_float4(u8.re, u8.im, u128.re, u128.im);
        }
        __syncwarp();
        float a0a[4] = {0, 0, 0, 0}, a0b[4] = {0, 0, 0, 0}, a1[4] = {0, 0, 0, 0}, a2a[4] = {0, 0, 0, 0}, a2b[4] = {0, 0, 0, 0};
        float k2048 = 0.f;
        const float Lg = (g < 4) ? (512.f + 4.f * g) : (g < 6 ? 1024.f + 8.f * (g - 4) : 1536.f + 8.f * (g - 6));
        #pragma unroll 4
        for (int kk = 0; kk < 32; kk++) {
            const float* st = S.u.st[w][4 * kk + t];
            float4 s0 = *reinterpret_cast<const float4*>(st), s1 = *reinterpret_cast<const float4*>(st + 4);
            cf wv; wv.re = s0.z; wv.im = s0.w;
            cf u8; u8.re = s1.x; u8.im = s1.y;
            cf u128; u128.re = s1.z; u128.im = s1.w;
            cf e1 = cexpL(s0.x, s0.y, (float)g);
            cf e23 = cexpL(s0.x, s0.y, Lg);
            cf e1b = cmul(e1, u8);
            cf e2 = csq(e1);
            cf p = csq(csq(csq(e2)));
            cf f0 = cmul(wv, p), f1 = cmul(f0, u128), f2 = cmul(f1, u128), f3 = cmul(f2, u128);
            uint32_t A00 = f2tf32(f0.re), A01 = f2tf32(f1.re), A02 = f2tf32(-f0.im), A03 = f2tf32(-f1.im);
            uint32_t A10 = f2tf32(f2.re), A11 = f2tf32(f3.re), A12 = f2tf32(-f2.im), A13 = f2tf32(-f3.im);
            mma_tf32(a0a, A00, A01, A02, A03, f2tf32(e1.re), f2tf32(e1.im));
            mma_tf32(a0b, A00, A01, A02, A03, f2tf32(e1b.re), f2tf32(e1b.im));
            mma_tf32(a1, A10, A11, A12, A13, f2tf32(e2.re), f2tf32(e2.im));
            uint32_t E0 = f2tf32(e23.re), E1 = f2tf32(e23.im);
            mma_tf32(a2a, A00, A01, A02, A03, E0, E1);
            mma_tf32(a2b, A10, A11, A12, A13, E0, E1);
            cf e2048 = csq(e23);
            k2048 += wv.re * e2048.re - wv.im * e2048.im;
        }
        k2048 += __shfl_xor_sync(~0u, k2048, 1);
        k2048 += __shfl_xor_sync(~0u, k2048, 2);
        float* Kc = S.Kc[w];
        Kc[16 * g + 2 * t] = a0a[0]; Kc[16 * g + 2 * t + 1] = a0a[1]; Kc[16 * (g + 8) + 2 * t] = a0a[2]; Kc[16 * (g + 8) + 2 * t + 1] = a0a[3];
        Kc[16 * g + 8 + 2 * t] = a0b[0]; Kc[16 * g + 8 + 2 * t + 1] = a0b[1]; Kc[16 * (g + 8) + 8 + 2 * t] = a0b[2]; Kc[16 * (g + 8) + 8 + 2 * t + 1] = a0b[3];
        Kc[256 + 8 * g + 2 * t] = a1[0]; Kc[256 + 8 * g + 2 * t + 1] = a1[1]; Kc[256 + 8 * (g + 8) + 2 * t] = a1[2]; Kc[256 + 8 * (g + 8) + 2 * t + 1] = a1[3];
        #pragma unroll
        for (int mt = 0; mt < 2; mt++) {
            #pragma unroll
            for (int e = 0; e < 4; e++) {
                int A = mt * 16 + g + (e >> 1) * 8, j = 2 * t + (e & 1);
                int Lj = (j < 4) ? 512 + 4 * j : (j < 6 ? 1024 + 8 * (j - 4) : 1536 + 8 * (j - 6));
                Kc[kc_index(Lj + 16 * A)] = mt ? a2b[e] : a2a[e];
            }
        }
        if (lane == 16) Kc[640] = k2048;
    }
    __syncwarp();
    {
        asm volatile("bar.sync 1, 256;" ::: "memory");
        bf16* k0 = S.u.KT[w][0];
        bf16* k1 = S.u.KT[w][1];
        const float* Kc = S.Kc[w];
        #pragma unroll 8
        for (int j = lane; j < 2048; j += 32) {
            const bf16 v = __float2bfloat16_rn(Kc[S.kidx[j]]);
            k0[16 + j] = v;
            k1[15 + j] = v;
        }
        if (lane < 16) { k0[lane] = __float2bfloat16_rn(0.f); if (lane < 15) k1[lane] = __float2bfloat16_rn(0.f); }
        k0[2064 + lane] = __float2bfloat16_rn(0.f); k1[2063 + lane] = __float2bfloat16_rn(0.f);
        __syncwarp();
    }
    {
        float acc[16][4];
        #pragma unroll
        for (int v = 0; v < 16; v++) { acc[v][0] = acc[v][1] = acc[v][2] = acc[v][3] = 0.f; }
        const bf16* kt = (g & 1) ? &S.u.KT[w][0][0] : &S.u.KT[w][1][0];
        const int ibase0 = g + 1 + 2 * t - ((g & 1) ? 0 : 1);
        #pragma unroll 1
        for (int r = 0; r < 8; r++) {
            uint32_t B[16][2];
            #pragma unroll
            for (int v = 0; v < 16; v++) {
                const bf16* p = &S.xs[w][XS_PAD + 16 * (8 * v + g - r) + 2 * t];
                B[v][0] = *reinterpret_cast<const uint32_t*>(p);
                B[v][1] = *reinterpret_cast<const uint32_t*>(p + 8);
            }
            #pragma unroll
            for (int q = 0; q < 16; q++) {
                const int i0 = ibase0 + 16 * r + 128 * q;
                const uint32_t A0 = *reinterpret_cast<const uint32_t*>(kt + i0);
                const uint32_t A1 = *reinterpret_cast<const uint32_t*>(kt + i0 + 8);
                const uint32_t A3 = *reinterpret_cast<const uint32_t*>(kt + i0 + 16);
                #pragma unroll
                for (int v = q; v < 16; v++) mma_bf16(acc[v], A0, A1, A1, A3, B[v - q][0], B[v - q][1]);
            }
        }
        bf16* ys = S.ys[w];
        #pragma unroll
        for (int v = 0; v < 16; v++) {
            const int a = 8 * v + 2 * t;
            ys[16 * a + g] = __float2bfloat16_rn(acc[v][0]); ys[16 * (a + 1) + g] = __float2bfloat16_rn(acc[v][1]);
            ys[16 * a + g + 8] = __float2bfloat16_rn(acc[v][2]); ys[16 * (a + 1) + g + 8] = __float2bfloat16_rn(acc[v][3]);
        }
    }
    asm volatile("bar.sync 1, 256;" ::: "memory");
    {
        float dsk[8];
        #pragma unroll
        for (int c = 0; c < 8; c++) dsk[c] = bf2f(Dskip[d0 + c]);
        #pragma unroll 2
        for (int it = 0; it < 8; it++) {
            const int l = tid + 256 * it;
            const int lr = XS_PAD + ((l & ~15) | (15 - (l & 15)));
            float o[8];
            #pragma unroll
            for (int c = 0; c < 8; c++) o[c] = bf2f(S.ys[c][l]) + bf2f(__float2bfloat16_rn(bf2f(S.xs[c][lr]) * dsk[c]));
            *reinterpret_cast<uint4*>(g_b + (size_t)l * DM + d0) = make_uint4(pack_bf16(o[0], o[1]), pack_bf16(o[2], o[3]), pack_bf16(o[4], o[5]), pack_bf16(o[6], o[7]));
        }
    }
}

__device__ __forceinline__ uint32_t smem_u32(const void* p) { return (uint32_t)__cvta_generic_to_shared(p); }
__device__ __forceinline__ void mbar_init(uint32_t bar, uint32_t cnt) { asm volatile("mbarrier.init.shared::cta.b64 [%0], %1;" :: "r"(bar), "r"(cnt) : "memory"); }
__device__ __forceinline__ void mbar_expect_tx(uint32_t bar, uint32_t bytes) { asm volatile("mbarrier.arrive.expect_tx.shared::cta.b64 _, [%0], %1;" :: "r"(bar), "r"(bytes) : "memory"); }
__device__ __forceinline__ void mbar_arrive(uint32_t bar) { asm volatile("mbarrier.arrive.shared::cta.b64 _, [%0];" :: "r"(bar) : "memory"); }
__device__ __forceinline__ void mbar_wait(uint32_t bar, uint32_t parity) {
    uint32_t ok; int guard = 0;
    do {
        asm volatile("{\n.reg .pred P1;\nmbarrier.test_wait.parity.shared::cta.b64 P1, [%1], %2;\nselp.u32 %0,1,0,P1;\n}" : "=r"(ok) : "r"(bar), "r"(parity) : "memory");
    } while (!ok && ++guard < (1 << 26));
}
__device__ __forceinline__ void mbar_wait_sleep(uint32_t bar, uint32_t parity) {
    uint32_t ok; int guard = 0;
    do {
        asm volatile("{\n.reg .pred P1;\nmbarrier.try_wait.parity.shared::cta.b64 P1, [%1], %2;\nselp.u32 %0,1,0,P1;\n}" : "=r"(ok) : "r"(bar), "r"(parity) : "memory");
    } while (!ok && ++guard < (1 << 22));
}
__device__ __forceinline__ uint32_t mapa(uint32_t addr, uint32_t rank) { uint32_t r; asm volatile("mapa.shared::cluster.u32 %0, %1, %2;" : "=r"(r) : "r"(addr), "r"(rank)); return r; }
__device__ __forceinline__ void st_async4(uint32_t addr, float a, float b, float c, float d, uint32_t bar) {
    asm volatile("st.async.weak.shared::cluster.mbarrier::complete_tx::bytes.v4.f32 [%0], {%1,%2,%3,%4}, [%5];" :: "r"(addr), "f"(a), "f"(b), "f"(c), "f"(d), "r"(bar) : "memory");
}
__device__ __forceinline__ void bulk_s2c(uint32_t dst, uint32_t src, uint32_t bytes, uint32_t bar) {
    asm volatile("cp.async.bulk.shared::cluster.shared::cta.mbarrier::complete_tx::bytes [%0], [%1], %2, [%3];" :: "r"(dst), "r"(src), "r"(bytes), "r"(bar) : "memory");
}
__device__ __forceinline__ void bulk_g2s(uint32_t dst, const void* src, uint32_t bytes, uint32_t bar) {
    asm volatile("cp.async.bulk.shared::cluster.global.mbarrier::complete_tx::bytes [%0], [%1], %2, [%3];" :: "r"(dst), "l"(src), "r"(bytes), "r"(bar) : "memory");
}
__device__ __forceinline__ void bulk_s2g(void* dst, uint32_t src, uint32_t bytes) {
    asm volatile("cp.async.bulk.global.shared::cta.bulk_group [%0], [%1], %2;" :: "l"(dst), "r"(src), "r"(bytes) : "memory");
}
__device__ __forceinline__ void bulk_commit() { asm volatile("cp.async.bulk.commit_group;" ::: "memory"); }
__device__ __forceinline__ void bulk_wait_read0() { asm volatile("cp.async.bulk.wait_group.read 0;" ::: "memory"); }
__device__ __forceinline__ void bulk_wait0() { asm volatile("cp.async.bulk.wait_group 0;" ::: "memory"); }
__device__ __forceinline__ void fence_async() { asm volatile("fence.proxy.async.shared::cta;" ::: "memory"); }
__device__ __forceinline__ void nbar_sync(int id, int n) { asm volatile("bar.sync %0, %1;" :: "r"(id), "r"(n) : "memory"); }
__device__ __forceinline__ void nbar_arrive(int id, int n) { asm volatile("bar.arrive %0, %1;" :: "r"(id), "r"(n) : "memory"); }
__device__ __forceinline__ void cp_async16(uint32_t dst, const void* src) { asm volatile("cp.async.cg.shared.global [%0], [%1], 16;" :: "r"(dst), "l"(src) : "memory"); }
__device__ __forceinline__ void cp_async_wait_all() { asm volatile("cp.async.wait_all;" ::: "memory"); }
__device__ __forceinline__ void ldsm4(uint32_t (&r)[4], uint32_t addr) {
    asm volatile("ldmatrix.sync.aligned.m8n8.x4.shared.b16 {%0,%1,%2,%3}, [%4];" : "=r"(r[0]), "=r"(r[1]), "=r"(r[2]), "=r"(r[3]) : "r"(addr) : "memory");
}
__device__ __forceinline__ void ldsm4t(uint32_t (&r)[4], uint32_t addr) {
    asm volatile("ldmatrix.sync.aligned.m8n8.x4.trans.shared.b16 {%0,%1,%2,%3}, [%4];" : "=r"(r[0]), "=r"(r[1]), "=r"(r[2]), "=r"(r[3]) : "r"(addr) : "memory");
}
__device__ __forceinline__ void stsm2t(uint32_t addr, uint32_t r0, uint32_t r1) {
    asm volatile("stmatrix.sync.aligned.m8n8.x2.trans.shared.b16 [%0], {%1,%2};" :: "r"(addr), "r"(r0), "r"(r1) : "memory");
}
__device__ __forceinline__ uint4 ld_relaxed4(const void* p) { uint4 v; asm volatile("ld.relaxed.gpu.global.v4.u32 {%0,%1,%2,%3}, [%4];" : "=r"(v.x), "=r"(v.y), "=r"(v.z), "=r"(v.w) : "l"(p) : "memory"); return v; }
__device__ __forceinline__ void st_relaxed2(void* p, uint32_t a, uint32_t b) { asm volatile("st.relaxed.gpu.global.v2.u32 [%0], {%1,%2};" :: "l"(p), "r"(a), "r"(b) : "memory"); }
__device__ __forceinline__ void st_relaxed1(void* p, uint32_t a) { asm volatile("st.relaxed.gpu.global.u32 [%0], %1;" :: "l"(p), "r"(a) : "memory"); }
__device__ __forceinline__ unsigned ld_acquire(const unsigned* p) { unsigned v; asm volatile("ld.acquire.gpu.global.u32 %0, [%1];" : "=r"(v) : "l"(p) : "memory"); return v; }
__device__ __forceinline__ float ex2_approx(float x) { float r; asm("ex2.approx.ftz.f32 %0, %1;" : "=f"(r) : "f"(x)); return r; }
__device__ __forceinline__ uint64_t make_desc(uint32_t saddr, uint32_t lbo, uint32_t sbo) {
    return (uint64_t)((saddr & 0x3FFFF) >> 4) | ((uint64_t)((lbo & 0x3FFFF) >> 4) << 16) | ((uint64_t)((sbo & 0x3FFFF) >> 4) << 32) | (1ull << 62);
}
__device__ __forceinline__ void wg_fence() { asm volatile("wgmma.fence.sync.aligned;" ::: "memory"); }
__device__ __forceinline__ void wg_commit() { asm volatile("wgmma.commit_group.sync.aligned;" ::: "memory"); }
__device__ __forceinline__ void wg_wait0() { asm volatile("wgmma.wait_group.sync.aligned 0;" ::: "memory"); }
__device__ __forceinline__ void wgmma_n40_tA(float (&d)[20], uint64_t da, uint64_t db, int scale_d) {
    asm volatile("{\n.reg .pred p;\nsetp.ne.b32 p, %22, 0;\n"
        "wgmma.mma_async.sync.aligned.m64n40k16.f32.bf16.bf16 {%0,%1,%2,%3,%4,%5,%6,%7,%8,%9,%10,%11,%12,%13,%14,%15,%16,%17,%18,%19}, %20, %21, p, 1, 1, 1, 0;\n}\n"
        : "+f"(d[0]), "+f"(d[1]), "+f"(d[2]), "+f"(d[3]), "+f"(d[4]), "+f"(d[5]), "+f"(d[6]), "+f"(d[7]), "+f"(d[8]), "+f"(d[9]),
          "+f"(d[10]), "+f"(d[11]), "+f"(d[12]), "+f"(d[13]), "+f"(d[14]), "+f"(d[15]), "+f"(d[16]), "+f"(d[17]), "+f"(d[18]), "+f"(d[19])
        : "l"(da), "l"(db), "r"(scale_d));
}

#define NREP 8
#define NRED 80
#define CAL_THR 410u
#define COMM_REGS "40"
#define NPOOL 576
#define RPS 1
__device__ __align__(4096) uint32_t g_pool[(NPOOL + 1) * 1024];
__device__ unsigned g_cls[NPOOL];
__device__ unsigned g_side[96];
__device__ unsigned g_calcnt;
__device__ unsigned g_epoch;
__device__ unsigned g_flag[NSEG][NH];
__device__ __align__(1024) bf16 g_Qimg[NSEG * NH * 2 * 32 * 64];
__device__ __align__(1024) bf16 g_Kimg[NSEG * NH * 2 * 40 * 64];
__device__ __align__(1024) bf16 g_Vimg[NSEG * NH * 2 * 40 * 64];

#define SM_XB    0
#define SM_VT    81920
#define SM_KT    (SM_VT + 20480)
#define SM_QT    (SM_KT + 10240)
#define SM_QS    (SM_QT + 4096)
#define SM_MEMB  (SM_QS + 1024)
#define SM_RED   (SM_MEMB + 10240)
#define SM_SC    (SM_RED + 16384)
#define SM_CRED  (SM_SC + 5120)
#define SM_PB    (SM_CRED + 1024)
#define SM_TRACE (SM_PB + 1024)
#define SM_WO    163840
#define SM_BAR   (SM_WO + 65536)
#define SM_TPM   (SM_BAR + 256)
#define SM_TRD   (SM_TPM + 256)
#define SM_TPUB  (SM_TRD + 16)
#define SM_TGAT  (SM_TPUB + 128)
#define SM_CAL   (SM_TGAT + 64)
#define SM_TOTAL (SM_CAL + 128)
#define B_SC   (SM_BAR + 0)
#define B_V    (SM_BAR + 16)
#define B_MEM  (SM_BAR + 32)
#define B_P    (SM_BAR + 48)
#define B_X    (SM_BAR + 56)
#define B_EXP  (SM_BAR + 72)

#define TR(ev) do {} while (0)
__device__ __forceinline__ uint32_t tag_of(int s) { return (uint32_t)(((s >> 1) & 1) + 1); }
__device__ __forceinline__ unsigned probe_latency(uint32_t* p, uint32_t zero) {
    uint32_t v, best = 0xffffffffu;
    asm volatile("atom.relaxed.gpu.global.add.u32 %0, [%1], 0;" : "=r"(v) : "l"(p) : "memory");
    #pragma unroll 1
    for (int r = 0; r < 4; r++) {
        uint32_t c0, c1;
        asm volatile("mov.u32 %0, %%clock;" : "=r"(c0) : "r"(v) : "memory");
        asm volatile("atom.relaxed.gpu.global.add.u32 %0, [%1], 0;" : "=r"(v) : "l"(p + ((v + c0) & zero)) : "memory");
        asm volatile("{\n.reg .u32 t;\nand.b32 t, %1, %2;\nmov.u32 %0, %%clock;\nadd.u32 %0, %0, t;\n}" : "=r"(c1) : "r"(v), "r"(zero) : "memory");
        best = min(best, c1 - c0);
    }
    return best;
}
__device__ __forceinline__ void cluster_sync_all() { asm volatile("barrier.cluster.arrive.release.aligned;\nbarrier.cluster.wait.acquire.aligned;" ::: "memory"); }
__device__ __forceinline__ void tma_load_2d(uint32_t dst, const void* map, int c0, int c1, uint32_t bar) {
    asm volatile("cp.async.bulk.tensor.2d.shared::cluster.global.mbarrier::complete_tx::bytes [%0], [%1, {%3, %4}], [%2];"
        :: "r"(dst), "l"(map), "r"(bar), "r"(c0), "r"(c1) : "memory");
}
__device__ __forceinline__ void tma_load_3d(uint32_t dst, const void* map, int c0, int c1, int c2, uint32_t bar) {
    asm volatile("cp.async.bulk.tensor.3d.shared::cluster.global.mbarrier::complete_tx::bytes [%0], [%1, {%3, %4, %5}], [%2];"
        :: "r"(dst), "l"(map), "r"(bar), "r"(c0), "r"(c1), "r"(c2) : "memory");
}
__device__ __forceinline__ void stsm4t(uint32_t addr, uint32_t r0, uint32_t r1, uint32_t r2, uint32_t r3) {
    asm volatile("stmatrix.sync.aligned.m8n8.x4.trans.shared.b16 [%0], {%1,%2,%3,%4};" :: "r"(addr), "r"(r0), "r"(r1), "r"(r2), "r"(r3) : "memory");
}
__device__ __forceinline__ void wgmma_n32_rs(float (&d)[16], const uint32_t (&a)[4], uint64_t db, int scale_d) {
    asm volatile("{\n.reg .pred p;\nsetp.ne.b32 p, %21, 0;\n"
        "wgmma.mma_async.sync.aligned.m64n32k16.f32.bf16.bf16 {%0,%1,%2,%3,%4,%5,%6,%7,%8,%9,%10,%11,%12,%13,%14,%15}, {%16,%17,%18,%19}, %20, p, 1, 1, 0;\n}\n"
        : "+f"(d[0]), "+f"(d[1]), "+f"(d[2]), "+f"(d[3]), "+f"(d[4]), "+f"(d[5]), "+f"(d[6]), "+f"(d[7]),
          "+f"(d[8]), "+f"(d[9]), "+f"(d[10]), "+f"(d[11]), "+f"(d[12]), "+f"(d[13]), "+f"(d[14]), "+f"(d[15])
        : "r"(a[0]), "r"(a[1]), "r"(a[2]), "r"(a[3]), "l"(db), "r"(scale_d));
}

__device__ __forceinline__ void st_async4u(uint32_t addr, uint4 v, uint32_t bar) {
    asm volatile("st.async.weak.shared::cluster.mbarrier::complete_tx::bytes.v4.u32 [%0], {%1,%2,%3,%4}, [%5];" :: "r"(addr), "r"(v.x), "r"(v.y), "r"(v.z), "r"(v.w), "r"(bar) : "memory");
}
__device__ __forceinline__ void export_issue(uint32_t sb, int s, int h, uint32_t rank) {
    const size_t img = (size_t)(s * NH + h) * 2;
    const int sl = s & 1;
    if (rank == 2) {
        bulk_s2g(g_Vimg + img * 2560, sb + SM_VT + sl * 10240, 5120);
        bulk_s2g(g_Vimg + (img + 1) * 2560, sb + SM_VT + sl * 10240 + 5120, 5120);
    } else {
        bulk_s2g(g_Qimg + (img + rank) * 2048, sb + SM_QT, 4096);
        bulk_s2g(g_Kimg + (img + rank) * 2560, sb + SM_KT + sl * 5120, 5120);
    }
    bulk_commit();
    bulk_wait_read0();
    mbar_arrive(sb + B_EXP);
}
__device__ __forceinline__ void export_signal(int s, int h) {
    bulk_wait0();
    asm volatile("fence.proxy.async;" ::: "memory");
    __threadfence();
    atomicAdd(&g_flag[s][h], 1u);
}

__device__ __forceinline__ void score_tile(uint32_t sb, int sl, int nt, int lane, uint32_t rank) {
    float sc[4] = {0, 0, 0, 0}, sd[4] = {0, 0, 0, 0};
    const int r = lane & 7;
    uint32_t qa[2][4], kb[2][4];
    #pragma unroll
    for (int j = 0; j < 2; j++) {
        const int chunk = (lane >> 3) + 4 * j;
        ldsm4(kb[j], sb + SM_KT + sl * 5120 + (8 * nt + r) * 128 + ((chunk ^ r) << 4));
        ldsm4(qa[j], sb + SM_QS + r * 128 + ((chunk ^ r) << 4));
    }
    mma_bf16(sc, qa[0][0], 0u, qa[0][1], 0u, kb[0][0], kb[0][1]);
    mma_bf16(sd, qa[1][0], 0u, qa[1][1], 0u, kb[1][0], kb[1][1]);
    mma_bf16(sc, qa[0][2], 0u, qa[0][3], 0u, kb[0][2], kb[0][3]);
    mma_bf16(sd, qa[1][2], 0u, qa[1][3], 0u, kb[1][2], kb[1][3]);
    sc[0] += sd[0]; sc[1] += sd[1];
    const float o0 = __shfl_down_sync(~0u, sc[0], 1), o1 = __shfl_down_sync(~0u, sc[1], 1);
    if ((lane & 1) == 0) {
        const uint32_t a = SM_SC + sl * 2560 + rank * 1280 + ((lane >> 2) * 40 + 8 * nt + 2 * (lane & 3)) * 4;
        const uint32_t bo = B_SC + 8 * sl;
        { const uint32_t rb = mapa(sb, 2); st_async4(rb + a, sc[0], sc[1], o0, o1, rb + bo); }
        { const uint32_t rb = mapa(sb, rank ^ 1); st_async4(rb + a, sc[0], sc[1], o0, o1, rb + bo); }
        asm volatile("st.shared.v4.f32 [%0], {%1,%2,%3,%4};" :: "r"(sb + a), "f"(sc[0]), "f"(sc[1]), "f"(o0), "f"(o1) : "memory");
    }
    __syncwarp();
    if (lane == 0) mbar_arrive(sb + B_SC + 8 * sl);
}
__device__ __forceinline__ void wgmma_n40_rs(float (&d)[20], const uint32_t (&a)[4], uint64_t db, int scale_d) {
    asm volatile("{\n.reg .pred p;\nsetp.ne.b32 p, %25, 0;\n"
        "wgmma.mma_async.sync.aligned.m64n40k16.f32.bf16.bf16 {%0,%1,%2,%3,%4,%5,%6,%7,%8,%9,%10,%11,%12,%13,%14,%15,%16,%17,%18,%19}, {%20,%21,%22,%23}, %24, p, 1, 1, 0;\n}\n"
        : "+f"(d[0]), "+f"(d[1]), "+f"(d[2]), "+f"(d[3]), "+f"(d[4]), "+f"(d[5]), "+f"(d[6]), "+f"(d[7]), "+f"(d[8]), "+f"(d[9]),
          "+f"(d[10]), "+f"(d[11]), "+f"(d[12]), "+f"(d[13]), "+f"(d[14]), "+f"(d[15]), "+f"(d[16]), "+f"(d[17]), "+f"(d[18]), "+f"(d[19])
        : "r"(a[0]), "r"(a[1]), "r"(a[2]), "r"(a[3]), "l"(db), "r"(scale_d));
}
__device__ __forceinline__ void pu_store(const float (&u)[20], const uint32_t (&pb)[5], float2 inv, unsigned char* smem, int sl, int lt, int warp, int lane, uint32_t tg) {
    float o[4] = {0, 0, 0, 0}, o2[4] = {0, 0, 0, 0};
    mma_bf16(o, pack_bf16(u[0], u[1]), pack_bf16(u[2], u[3]), pack_bf16(u[4], u[5]), pack_bf16(u[6], u[7]), pb[0], pb[1]);
    mma_bf16(o2, pack_bf16(u[8], u[9]), pack_bf16(u[10], u[11]), pack_bf16(u[12], u[13]), pack_bf16(u[14], u[15]), pb[2], pb[3]);
    mma_bf16(o, pack_bf16(u[16], u[17]), pack_bf16(u[18], u[19]), 0u, 0u, pb[4], 0u);
    const uint2 off = *reinterpret_cast<const uint2*>(smem + SM_TPM + (((sl * 4 + lt) * 4 + warp) * 2) * 4);
    unsigned char* pool = reinterpret_cast<unsigned char*>(g_pool) + lane * 8;
    st_relaxed2(pool + off.x, (__float_as_uint((o[0] + o2[0]) * inv.x) & ~3u) | tg, (__float_as_uint((o[1] + o2[1]) * inv.y) & ~3u) | tg);
    st_relaxed2(pool + off.y, (__float_as_uint((o[2] + o2[2]) * inv.x) & ~3u) | tg, (__float_as_uint((o[3] + o2[3]) * inv.y) & ~3u) | tg);
}
template <int NT>
__device__ __forceinline__ void u_pass(unsigned char* smem, uint32_t sb, int s, uint32_t rank, int wg, int warp, int lane) {
    const int sl = s & 1;
    constexpr int NRS = 6;
    uint32_t wa[NRS][4];
    {
        const int mi = lane >> 3, chunk = 2 * warp + (mi & 1);
        #pragma unroll
        for (int ks = 0; ks < NRS; ks++) {
            const int row = 16 * ks + (mi >> 1) * 8 + (lane & 7);
            ldsm4t(wa[ks], sb + SM_WO + (2 * wg) * 16384 + row * 128 + ((chunk ^ (row & 7)) << 4));
        }
    }
    if (rank < 2) { mbar_wait(sb + B_V + 8 * sl, (s >> 1) & 1); fence_async(); }
    if (wg == 0 && warp == 0) TR(4);
    float U0[20];
    wg_fence();
    #pragma unroll
    for (int ks = 0; ks < NRS; ks++)
        wgmma_n40_rs(U0, wa[ks], make_desc(sb + SM_VT + sl * 10240 + (ks >> 2) * 5120 + (ks & 3) * 32, 16, 1024), ks > 0);
    #pragma unroll
    for (int ks = NRS; ks < 8; ks++)
        wgmma_n40_tA(U0, make_desc(sb + SM_WO + (2 * wg) * 16384 + ks * 2048, 1024, 1024),
                     make_desc(sb + SM_VT + sl * 10240 + (ks >> 2) * 5120 + (ks & 3) * 32, 16, 1024), 1);
    wg_commit();
    const uint32_t tg = tag_of(s);
    uint32_t pb[5];
    float2 inv;
    auto get_p = [&]() {
        nbar_sync(9, 288);
        const uint32_t* pbs = reinterpret_cast<const uint32_t*>(smem + SM_PB);
        #pragma unroll
        for (int q = 0; q < 5; q++) pb[q] = pbs[q * 32 + lane];
        float sm[4] = {0, 0, 0, 0}, sm2[4] = {0, 0, 0, 0};
        const uint32_t one = 0x3f803f80u;
        mma_bf16(sm, one, one, one, one, pb[0], pb[1]);
        mma_bf16(sm2, one, one, one, one, pb[2], pb[3]);
        mma_bf16(sm, one, one, 0u, 0u, pb[4], 0u);
        inv.x = __frcp_rn(sm[0] + sm2[0]); inv.y = __frcp_rn(sm[1] + sm2[1]);
    };
    if (NT == 2) {
        wg_wait0();
        float U1[20];
        wg_fence();
        #pragma unroll
        for (int ks = 0; ks < 8; ks++)
            wgmma_n40_tA(U1, make_desc(sb + SM_WO + (2 * wg + 1) * 16384 + ks * 2048, 1024, 1024),
                         make_desc(sb + SM_VT + sl * 10240 + (ks >> 2) * 5120 + (ks & 3) * 32, 16, 1024), ks > 0);
        wg_commit();
        get_p();
        if (wg == 0 && warp == 0) TR(8);
        pu_store(U0, pb, inv, smem, sl, 2 * wg, warp, lane, tg);
        wg_wait0();
        if (wg == 0 && warp == 0) TR(6);
        pu_store(U1, pb, inv, smem, sl, 2 * wg + 1, warp, lane, tg);
    } else {
        wg_wait0();
        get_p();
        pu_store(U0, pb, inv, smem, sl, 2 * wg, warp, lane, tg);
    }
}

__global__ void __cluster_dims__(3, 1, 1) __launch_bounds__(384, 1)
k_chain(const __grid_constant__ CUtensorMap xmap, const __grid_constant__ CUtensorMap wqmap, const __grid_constant__ CUtensorMap wkmap,
        const __grid_constant__ CUtensorMap wvmap, const __grid_constant__ CUtensorMap womap, const bf16* __restrict__ xptr, const bf16* __restrict__ mem0) {
    extern __shared__ __align__(1024) unsigned char smem[];
    const uint32_t sb = smem_u32(smem);
    const int tid = threadIdx.x, lane = tid & 31;
    const int wg = __shfl_sync(~0u, tid >> 7, 0), warp = __shfl_sync(~0u, (tid >> 5) & 3, 0);
    uint32_t rank; asm volatile("mov.u32 %0, %%cluster_ctarank;" : "=r"(rank));
    const int cta = blockIdx.x, h = cta / 3;
    asm volatile("griddepcontrol.launch_dependents;");
    if (tid == 0) {
        for (int i = 0; i < 2; i++) { mbar_init(sb + B_SC + 8 * i, rank < 2 ? 6 : 1); mbar_init(sb + B_V + 8 * i, 1); mbar_init(sb + B_MEM + 8 * i, 64); mbar_init(sb + B_X + 8 * i, 1); }
        mbar_init(sb + B_P, 1); mbar_init(sb + B_EXP, 1);
        asm volatile("fence.mbarrier_init.release.cluster;" ::: "memory");
    }
    if (tid < 80) asm volatile("prefetch.global.L2 [%0];" :: "l"(mem0 + tid * 64));
    if (h < 2) { for (int i = tid; i < 320; i += 384) asm volatile("prefetch.global.L2 [%0];" :: "l"(xptr + (size_t)h * 32 * DM + i * 64)); }
    {
        const int w12 = tid >> 5;
        if (lane == 0 && w12 < 7) {
            uint32_t* pp = (w12 < 6) ? g_pool + (size_t)(cta * 6 + w12) * 1024 + 512 : g_pool + (size_t)NPOOL * 1024 + (cta & 31) * 32 + (cta >> 5) * 8;
            const unsigned lat = probe_latency(pp, blockIdx.y);
            if (w12 < 6) g_cls[cta * 6 + w12] = lat > CAL_THR ? 1u : 0u; else g_side[cta] = lat > CAL_THR ? 1u : 0u;
        }
        __syncwarp();
        uint4* z = reinterpret_cast<uint4*>(g_pool + (size_t)cta * 6 * 1024);
        #pragma unroll
        for (int q = 0; q < 4; q++) z[tid + 384 * q] = make_uint4(0, 0, 0, 0);
        __threadfence();
        __syncwarp();
        if (lane == 0) atomicAdd(&g_calcnt, 1u);
    }
    __syncthreads();
    if (tid == 0) {
        const int ntile = (rank == 2) ? 4 : 3;
        const int tile0 = (rank == 2) ? 0 : (rank == 0 ? 4 : 7);
        mbar_expect_tx(sb + B_P, 163840 + ntile * 16384);
        const void* m0 = (rank == 2) ? &wvmap : &wqmap;
        const void* m1 = (rank == 2) ? &wvmap : &wkmap;
        const int c0 = h * DH + (rank == 1 ? 64 : 0), c1 = h * DH + (rank == 0 ? 0 : 64);
        for (int b = 0; b < 5; b++) {
            tma_load_2d(sb + b * 16384, m0, c0, b * 128, sb + B_P);
            tma_load_2d(sb + 81920 + b * 16384, m1, c1, b * 128, sb + B_P);
        }
        for (int lt = 0; lt < ntile; lt++) {
            tma_load_2d(sb + SM_WO + lt * 16384, &womap, (tile0 + lt) * 64, h * DH, sb + B_P);
            tma_load_2d(sb + SM_WO + lt * 16384 + 8192, &womap, (tile0 + lt) * 64, h * DH + 64, sb + B_P);
        }
    }
    {
        const int tile0 = (rank == 2) ? 0 : (rank == 0 ? 4 : 7);
        if (wg == 2) {
            const int ct = tid & 127;
            if (ct == 0) {
                const unsigned target = (*reinterpret_cast<volatile unsigned*>(&g_epoch) + 1u) * (96u * 12u);
                int guard = 0;
                while ((int)(ld_acquire(&g_calcnt) - target) < 0 && ++guard < (1 << 22)) {}
            }
            nbar_sync(4, 128);
            uint32_t* bm = reinterpret_cast<uint32_t*>(smem + SM_CAL);
            {
                unsigned v[5];
                #pragma unroll
                for (int q = 0; q < 5; q++) { const int b = ct + 128 * q; v[q] = (b < NPOOL) ? (__ldcg(&g_cls[b]) ^ __ldcg(&g_side[b / 6])) : 0u; }
                const unsigned sv = (ct < 96) ? __ldcg(&g_side[ct]) : 0u;
                #pragma unroll
                for (int q = 0; q < 5; q++) { const unsigned m = __ballot_sync(~0u, v[q] & 1u); if (lane == 0 && q * 4 + warp < 18) bm[q * 4 + warp] = m; }
                const unsigned m = __ballot_sync(~0u, sv & 1u);
                if (lane == 0 && warp < 3) bm[18 + warp] = m;
            }
            nbar_sync(4, 128);
            int nblk1 = 0;
            for (int i = 0; i < 18; i++) nblk1 += __popc(bm[i]);
            const unsigned red_last = (1u << (NRED - 64)) - 1u;
            const int nred1 = __popc(bm[18]) + __popc(bm[19]) + __popc(bm[20] & red_last);
            auto side_of = [&](int c) -> int { return (bm[18 + (c >> 5)] >> (c & 31)) & 1; };
            auto rank_of = [&](int c) -> int {
                int ones = 0;
                for (int i = 0; i < (c >> 5); i++) ones += __popc(bm[18 + i]);
                ones += __popc(bm[18 + (c >> 5)] & ((1u << (c & 31)) - 1u));
                return side_of(c) ? ones : c - ones;
            };
            auto nth = [&](int side, int idx) -> uint32_t {
                for (int i = 0; i < 18; i++) {
                    const unsigned m = side ? bm[i] : ~bm[i];
                    const int n = __popc(m);
                    if (idx < n) return (uint32_t)(i * 32 + __fns(m, 0, idx + 1));
                    idx -= n;
                }
                return 0u;
            };
            auto phys = [&](int side, int idx) -> uint32_t {
                const int c = side ? nblk1 : NPOOL - nblk1;
                return (idx < c) ? nth(side, idx) : nth(side ^ 1, (NPOOL - c) - 1 - (idx - c));
            };
            const int e = ct;
            if (e < 64) {
                const int slot = e >> 5, lt = (e >> 3) & 3, w = (e >> 1) & 3, hf = e & 1;
                const int tile = min(tile0 + lt, 9);
                const int r = 2 * (4 * tile + w) + hf;
                reinterpret_cast<uint32_t*>(smem + SM_TPM)[e] = phys(side_of(r), 4 * rank_of(r) + slot * 2 + (h >> 4)) * 4096u + (h & 15) * 256u;
            } else if (e < 68) {
                const int i = e - 64;
                reinterpret_cast<uint32_t*>(smem + SM_TRD)[i] = (cta < NRED) ? phys(side_of(cta), 4 * rank_of(cta) + i) * 4096u : 0u;
            } else if (e < 100) {
                const int i = e - 68, slot = i >> 3, rep = i & 7, side = (rep / RPS) & 1;
                reinterpret_cast<uint32_t*>(smem + SM_TPUB)[i] = phys(side, 4 * (side ? nred1 : NRED - nred1) + (slot * RPS + (rep % RPS)) * 3 + (cta >> 5)) * 4096u + (cta & 31) * 128u;
            } else if (e < 112) {
                const int i = e - 100, slot = i / 3, b = i % 3, side = side_of(cta);
                reinterpret_cast<uint32_t*>(smem + SM_TGAT)[slot * 4 + b] = phys(side, 4 * (side ? nred1 : NRED - nred1) + (slot * RPS + (h % RPS)) * 3 + b) * 4096u;
            }
        }
    }
    __syncthreads();
    mbar_wait_sleep(sb + B_P, 0);

    if (wg == 2) {
        asm volatile("setmaxnreg.dec.sync.aligned.u32 " COMM_REGS ";");
        const int ct = tid & 127;
        nbar_sync(5, 384);
        for (int c = ct; c < 640; c += 128) {
            int ks = c >> 4, hf = (c >> 3) & 1, r = c & 7;
            *reinterpret_cast<uint4*>(smem + SM_MEMB + c * 16) = *reinterpret_cast<const uint4*>(mem0 + r * DM + ks * 16 + hf * 8);
        }
        if (ct == 0) {
            for (int sg = 0; sg < 2; sg++) {
                mbar_expect_tx(sb + B_X + 8 * sg, 40960);
                tma_load_3d(sb + SM_XB + sg * 40960, &xmap, 0, sg * 32, 0, sb + B_X + 8 * sg);
            }
            mbar_expect_tx(sb + B_SC, rank < 2 ? 1280 : 2560);
            if (rank < 2) mbar_expect_tx(sb + B_V, 8192 + 2048);
        }
        nbar_sync(5, 384);
        cluster_sync_all();
        unsigned char* const pool = reinterpret_cast<unsigned char*>(g_pool);
        for (int s = 0; s < NSEG - 1; s++) {
            if (warp == 1) nbar_sync(12, 288);
            if (warp == 0) {
                const int g = lane >> 2, t = lane & 3;
                mbar_wait(sb + B_SC + 8 * (s & 1), (s >> 1) & 1);
                TR(5);
                const uint32_t sa = sb + SM_SC + (s & 1) * 2560 + (g * 40 + 2 * t) * 4;
                float v[5][2], u[5][2];
                #pragma unroll
                for (int q = 0; q < 5; q++) {
                    asm volatile("ld.shared.v2.f32 {%0,%1}, [%2];" : "=f"(v[q][0]), "=f"(v[q][1]) : "r"(sa + 32 * q) : "memory");
                    asm volatile("ld.shared.v2.f32 {%0,%1}, [%2];" : "=f"(u[q][0]), "=f"(u[q][1]) : "r"(sa + 1280 + 32 * q) : "memory");
                }
                float mx = -3.0e38f;
                #pragma unroll
                for (int q = 0; q < 5; q++) {
                    v[q][0] += u[q][0]; v[q][1] += u[q][1];
                    mx = fmaxf(mx, fmaxf(v[q][0], v[q][1]));
                }
                mx = fmaxf(mx, __shfl_xor_sync(~0u, mx, 1));
                mx = fmaxf(mx, __shfl_xor_sync(~0u, mx, 2));
                const float sc2 = 0.08838834764831845f * 1.4426950408889634f;
                const float mxs = mx * sc2;
                uint32_t* pbs = reinterpret_cast<uint32_t*>(smem + SM_PB);
                #pragma unroll
                for (int q = 0; q < 5; q++) {
                    const float e0 = ex2_approx(fmaf(v[q][0], sc2, -mxs)), e1 = ex2_approx(fmaf(v[q][1], sc2, -mxs));
                    pbs[q * 32 + lane] = pack_bf16(e0, e1);
                }
                __syncwarp();
                TR(0);
                nbar_arrive(9, 288);
            } else if (warp == 1 && lane == 0) {
                if (s + 1 < NSEG - 1) {
                    mbar_expect_tx(sb + B_SC + 8 * ((s + 1) & 1), rank < 2 ? 1280 : 2560);
                    if (rank < 2) mbar_expect_tx(sb + B_V + 8 * ((s + 1) & 1), 8192 + 2048);
                }
                if (s + 2 < NSEG) {
                    mbar_expect_tx(sb + B_X + 8 * (s & 1), 40960);
                    tma_load_3d(sb + SM_XB + (s & 1) * 40960, &xmap, 0, (s + 2) * 32, 0, sb + B_X + 8 * (s & 1));
                }
                export_issue(sb, s, h, rank);
                if (s >= NSEG - 4) export_signal(s, h);
            }
            __syncwarp();
            nbar_sync(3, 384);
            const uint32_t tg = tag_of(s);
            if (cta < NRED) {
                const unsigned char* base = pool + reinterpret_cast<const uint32_t*>(smem + SM_TRD)[(s & 1) * 2 + (warp >> 1)] + (warp & 1) * 2048 + lane * 16;
                uint4 v[4]; int guard = 0;
                #pragma unroll
                for (int j = 0; j < 4; j++) v[j] = make_uint4(0, 0, 0, 0);
                uint32_t pend = 0xF;
                do {
                    #pragma unroll
                    for (int j = 0; j < 4; j++) if (pend & (1u << j)) v[j] = ld_relaxed4(base + j * 512);
                    #pragma unroll
                    for (int j = 0; j < 4; j++)
                        if (((v[j].x & 3) == tg) && ((v[j].y & 3) == tg) && ((v[j].z & 3) == tg) && ((v[j].w & 3) == tg)) pend &= ~(1u << j);
                } while (__any_sync(~0u, pend != 0) && ++guard < (1 << 20));
                if (warp == 0) TR(9);
                float a0 = 0, a1 = 0, a2 = 0, a3 = 0;
                #pragma unroll
                for (int j = 0; j < 4; j++) { a0 += __uint_as_float(v[j].x); a1 += __uint_as_float(v[j].y); a2 += __uint_as_float(v[j].z); a3 += __uint_as_float(v[j].w); }
                a0 += __shfl_xor_sync(~0u, a0, 16); a1 += __shfl_xor_sync(~0u, a1, 16); a2 += __shfl_xor_sync(~0u, a2, 16); a3 += __shfl_xor_sync(~0u, a3, 16);
                float* cr = reinterpret_cast<float*>(smem + SM_CRED);
                if (lane < 16) *reinterpret_cast<float4*>(cr + warp * 64 + lane * 4) = make_float4(a0, a1, a2, a3);
                nbar_sync(4, 128);
                {
                    int rho = lane >> 2, pp = lane & 3;
                    int i0 = ((2 * pp) * 4 + (rho >> 1)) * 2 + (rho & 1), i1 = i0 + 8;
                    uint32_t wv = pack_bf16((cr[i0] + cr[64 + i0]) + (cr[128 + i0] + cr[192 + i0]), (cr[i1] + cr[64 + i1]) + (cr[128 + i1] + cr[192 + i1]));
                    if (wv == 0) wv = 0x8000u;
                    if (warp == 0) TR(10);
                    const uint32_t* tp = reinterpret_cast<const uint32_t*>(smem + SM_TPUB) + warp;
                    if (warp < 2 * RPS) st_relaxed1(pool + tp[((s + 1) & 3) * 8] + lane * 4, wv);
                    if (RPS == 4) st_relaxed1(pool + tp[((s + 1) & 3) * 8 + 4] + lane * 4, wv);
                    if (warp < 2 * RPS) st_relaxed1(pool + tp[(s & 3) * 8] + lane * 4, 0u);
                    if (RPS == 4) st_relaxed1(pool + tp[(s & 3) * 8 + 4] + lane * 4, 0u);
                }
            }
            {
                const int c0 = warp * 160 + lane;
                const uint32_t* tg3 = reinterpret_cast<const uint32_t*>(smem + SM_TGAT) + ((s + 1) & 3) * 4;
                const uint32_t g0 = tg3[0], g1 = tg3[1], g2 = tg3[2];
                uint4 v[5]; int guard = 0;
                #pragma unroll
                for (int j = 0; j < 5; j++) v[j] = make_uint4(0, 0, 0, 0);
                uint32_t pend = 0x1F;
                do {
                    #pragma unroll
                    for (int j = 0; j < 5; j++) {
                        const int c = c0 + 32 * j;
                        if (pend & (1u << j)) v[j] = ld_relaxed4(pool + ((c >> 8) == 0 ? g0 : ((c >> 8) == 1 ? g1 : g2)) + (c & 255) * 16);
                    }
                    #pragma unroll
                    for (int j = 0; j < 5; j++) if (v[j].x && v[j].y && v[j].z && v[j].w) pend &= ~(1u << j);
                } while (__any_sync(~0u, pend != 0) && ++guard < (1 << 20));
                #pragma unroll
                for (int j = 0; j < 5; j++) *reinterpret_cast<uint4*>(smem + SM_MEMB + (c0 + 32 * j) * 16) = v[j];
                if (warp == 0) TR(11);
                if (warp == 3) TR(12);
                nbar_arrive(warp < 2 ? 7 + warp : 8 + warp, 160);
            }
            if (warp == 1 && lane == 0 && s < NSEG - 4) export_signal(s, h);
            __syncwarp();
        }
        if (warp == 1) { nbar_sync(12, 288); if (lane == 0) { export_issue(sb, NSEG - 1, h, rank); export_signal(NSEG - 1, h); } }
        __syncwarp();
        nbar_sync(3, 384);
        __syncwarp();
        cluster_sync_all();
    } else {
        asm volatile("setmaxnreg.inc.sync.aligned.u32 232;");
        const int wtid = tid & 127;
        const int cw = wg * 4 + warp;
        uint32_t areg[2][20][4];
        #pragma unroll
        for (int mt = 0; mt < 2; mt++)
            #pragma unroll
            for (int kk = 0; kk < 20; kk++) {
                int mi = lane >> 3;
                int row = 16 * (20 * wg + kk) + (mi >> 1) * 8 + (lane & 7);
                int chunk = 2 * warp + (mi & 1);
                ldsm4t(areg[mt][kk], sb + mt * 81920 + row * 128 + ((chunk ^ (row & 7)) << 4));
            }
        nbar_sync(5, 384);
        nbar_sync(5, 384);
        cluster_sync_all();

        for (int s = -1; s < NSEG; s++) {
            const int sl = s & 1;
            if (s >= 0) {
            if (s > 0) nbar_sync(7 + 3 * wg, 160);
            float fin[4];
            {
                float acc[2][2][4];
                #pragma unroll
                for (int i = 0; i < 2; i++)
                    #pragma unroll
                    for (int j = 0; j < 2; j++) { acc[i][j][0] = acc[i][j][1] = acc[i][j][2] = acc[i][j][3] = 0.f; }
                uint32_t b[3][4];
                const uint32_t mb = sb + SM_MEMB + (20 * wg) * 256 + lane * 16;
                ldsm4(b[0], mb); ldsm4(b[1], mb + 512);
                #pragma unroll
                for (int kp = 0; kp < 10; kp++) {
                    if (kp == 3 && s > 0) nbar_sync(8 + 3 * wg, 160);
                    if (kp + 2 < 10) ldsm4(b[(kp + 2) % 3], mb + (kp + 2) * 512);
                    const uint32_t (&bb)[4] = b[kp % 3];
                    mma_bf16(acc[0][0], areg[0][2 * kp][0], areg[0][2 * kp][1], areg[0][2 * kp][2], areg[0][2 * kp][3], bb[0], bb[1]);
                    mma_bf16(acc[1][0], areg[1][2 * kp][0], areg[1][2 * kp][1], areg[1][2 * kp][2], areg[1][2 * kp][3], bb[0], bb[1]);
                    mma_bf16(acc[0][1], areg[0][2 * kp + 1][0], areg[0][2 * kp + 1][1], areg[0][2 * kp + 1][2], areg[0][2 * kp + 1][3], bb[2], bb[3]);
                    mma_bf16(acc[1][1], areg[1][2 * kp + 1][0], areg[1][2 * kp + 1][1], areg[1][2 * kp + 1][2], areg[1][2 * kp + 1][3], bb[2], bb[3]);
                }
                float4* red = reinterpret_cast<float4*>(smem + SM_RED);
                float m0[4], m1[4];
                #pragma unroll
                for (int i = 0; i < 4; i++) { m0[i] = acc[0][0][i] + acc[0][1][i]; m1[i] = acc[1][0][i] + acc[1][1][i]; }
                red[(wg ^ 1) * 128 + wtid] = wg == 0 ? make_float4(m1[0], m1[1], m1[2], m1[3]) : make_float4(m0[0], m0[1], m0[2], m0[3]);
                nbar_sync(1, 256);
                float4 r = red[wg * 128 + wtid];
                fin[0] = (wg == 0 ? m0[0] : m1[0]) + r.x; fin[1] = (wg == 0 ? m0[1] : m1[1]) + r.y;
                fin[2] = (wg == 0 ? m0[2] : m1[2]) + r.z; fin[3] = (wg == 0 ? m0[3] : m1[3]) + r.w;
            }
            if (cw == 0) TR(1);
            {
                uint32_t p0 = pack_bf16(fin[0], fin[1]), p1 = pack_bf16(fin[2], fin[3]);
                const uint32_t doff = (rank == 2) ? SM_VT + sl * 10240 + wg * 5120 : (wg == 0 ? SM_QS : SM_KT + sl * 5120);
                const int r = lane & 7, chunk = 2 * warp + ((lane >> 3) & 1);
                const uint32_t coff = doff + r * 128 + ((chunk ^ r) << 4);
                stsm2t(sb + coff, p0, p1);
                if (rank == 2 && s < NSEG - 1) {
                    __syncwarp();
                    const uint4 v = *reinterpret_cast<const uint4*>(smem + coff);
                    const uint32_t rb = mapa(sb, lane >> 4);
                    st_async4u(rb + coff, v, rb + B_V + 8 * sl);
                }
            }
            fence_async();
            nbar_sync(1, 256);
            nbar_arrive(12, 288);
            if (cw == 0) TR(2);
            if (rank < 2 && s < NSEG - 1) {
                if (wg == 1) score_tile(sb, sl, 1 + warp, lane, rank);
                else if (warp == 0) score_tile(sb, sl, 0, lane, rank);
            }
            if (s == NSEG - 1) break;
            if (cw == 0) TR(3);
            if (wg == 0 || rank == 2) u_pass<2>(smem, sb, s, rank, wg, warp, lane);
            else                      u_pass<1>(smem, sb, s, rank, wg, warp, lane);
            if (cw == 0) TR(7);
            nbar_arrive(3, 384);
            }
            {
                const int sn = s + 1, sln = sn & 1;
                mbar_wait(sb + B_X + 8 * sln, (sn >> 1) & 1);
                float acc[2][16];
                wg_fence();
                #pragma unroll
                for (int mt = 0; mt < 2; mt++)
                    #pragma unroll
                    for (int kk = 0; kk < 20; kk++) {
                        uint64_t db = make_desc(sb + SM_XB + sln * 40960 + (5 * wg + (kk >> 2)) * 4096 + (kk & 3) * 32, 16, 1024);
                        wgmma_n32_rs(acc[mt], areg[mt][kk], db, kk > 0);
                    }
                wg_commit();
                if (cw == 0 && s >= 0) TR(14);
                wg_wait0();
                if (cw == 0 && s >= 0) TR(15);
                float4* red = reinterpret_cast<float4*>(smem + SM_RED);
                #pragma unroll
                for (int j = 0; j < 4; j++) {
                    red[((wg ^ 1) * 4 + j) * 128 + wtid] = make_float4(wg == 0 ? acc[1][4 * j] : acc[0][4 * j], wg == 0 ? acc[1][4 * j + 1] : acc[0][4 * j + 1],
                                                                       wg == 0 ? acc[1][4 * j + 2] : acc[0][4 * j + 2], wg == 0 ? acc[1][4 * j + 3] : acc[0][4 * j + 3]);
                }
                if (s >= 0) mbar_wait(sb + B_EXP, s & 1);
                nbar_sync(1, 256);
                uint32_t pk[8];
                #pragma unroll
                for (int j = 0; j < 4; j++) {
                    float4 r = red[(wg * 4 + j) * 128 + wtid];
                    pk[2 * j] = pack_bf16((wg == 0 ? acc[0][4 * j] : acc[1][4 * j]) + r.x, (wg == 0 ? acc[0][4 * j + 1] : acc[1][4 * j + 1]) + r.y);
                    pk[2 * j + 1] = pack_bf16((wg == 0 ? acc[0][4 * j + 2] : acc[1][4 * j + 2]) + r.z, (wg == 0 ? acc[0][4 * j + 3] : acc[1][4 * j + 3]) + r.w);
                }
                const uint32_t dst = (rank == 2) ? sb + SM_VT + sln * 10240 + wg * 5120 + 1024 : (wg == 0 ? sb + SM_QT : sb + SM_KT + sln * 5120 + 1024);
                #pragma unroll
                for (int jj = 0; jj < 2; jj++) {
                    int mi = lane >> 3, tok = 8 * (2 * jj + (mi >> 1)) + (lane & 7), chunk = 2 * warp + (mi & 1);
                    stsm4t(dst + tok * 128 + ((chunk ^ (tok & 7)) << 4), pk[4 * jj], pk[4 * jj + 1], pk[4 * jj + 2], pk[4 * jj + 3]);
                }
                fence_async();
                nbar_sync(1, 256);
                if (rank == 2 && lane == 0 && cw < 4 && sn < NSEG - 1) {
                    const uint32_t off = SM_VT + sln * 10240 + (cw & 1) * 5120 + 1024;
                    const uint32_t rb = mapa(sb, cw >> 1);
                    bulk_s2c(rb + off, sb + off, 4096, rb + B_V + 8 * sln);
                }
                if (cw == 0 && s >= 0) TR(13);
            }
        }
        nbar_arrive(3, 384);
        __syncwarp();
        cluster_sync_all();
    }
}

#define NAUX 36
__device__ __align__(1024) bf16 g_Oimg[16 * 64 * 128 * 64];
__device__ float    g_part[4 * SEQ * DM];
__device__ float    g_part31[3 * 13 * 64 * DM];
__device__ unsigned g_ocnt[32];
__device__ unsigned g_gcnt[32][2];
__device__ unsigned g_ssmcnt, g_auxdone, g_taskctr, g_gemmctr;
#define NATT 8
#define ATR(i) do {} while (0)
#define ATRID(i, id) do {} while (0)

__device__ __forceinline__ void wait_counter(const unsigned* p, unsigned target) {
    int guard = 0;
    while ((int)(ld_acquire(p) - target) < 0 && ++guard < (1 << 22)) __nanosleep(64);
}
__device__ __forceinline__ void fence_async_all() { asm volatile("fence.proxy.async;" ::: "memory"); }
template <int OFF>
__device__ __forceinline__ void wgmma_n192_tB(float (&d)[160], uint64_t da, uint64_t db) {
    asm volatile("wgmma.mma_async.sync.aligned.m64n192k16.f32.bf16.bf16 {%0,%1,%2,%3,%4,%5,%6,%7,%8,%9,%10,%11,%12,%13,%14,%15,%16,%17,%18,%19,%20,%21,%22,%23,%24,%25,%26,%27,%28,%29,%30,%31,%32,%33,%34,%35,%36,%37,%38,%39,%40,%41,%42,%43,%44,%45,%46,%47,%48,%49,%50,%51,%52,%53,%54,%55,%56,%57,%58,%59,%60,%61,%62,%63,%64,%65,%66,%67,%68,%69,%70,%71,%72,%73,%74,%75,%76,%77,%78,%79,%80,%81,%82,%83,%84,%85,%86,%87,%88,%89,%90,%91,%92,%93,%94,%95}, %96, %97, 1, 1, 1, 0, 1;\n"
        : "+f"(d[OFF + 0]), "+f"(d[OFF + 1]), "+f"(d[OFF + 2]), "+f"(d[OFF + 3]), "+f"(d[OFF + 4]), "+f"(d[OFF + 5]), "+f"(d[OFF + 6]), "+f"(d[OFF + 7]), "+f"(d[OFF + 8]), "+f"(d[OFF + 9]), "+f"(d[OFF + 10]), "+f"(d[OFF + 11]), "+f"(d[OFF + 12]), "+f"(d[OFF + 13]), "+f"(d[OFF + 14]), "+f"(d[OFF + 15]), "+f"(d[OFF + 16]), "+f"(d[OFF + 17]), "+f"(d[OFF + 18]), "+f"(d[OFF + 19]), "+f"(d[OFF + 20]), "+f"(d[OFF + 21]), "+f"(d[OFF + 22]), "+f"(d[OFF + 23]), "+f"(d[OFF + 24]), "+f"(d[OFF + 25]), "+f"(d[OFF + 26]), "+f"(d[OFF + 27]), "+f"(d[OFF + 28]), "+f"(d[OFF + 29]), "+f"(d[OFF + 30]), "+f"(d[OFF + 31]), "+f"(d[OFF + 32]), "+f"(d[OFF + 33]), "+f"(d[OFF + 34]), "+f"(d[OFF + 35]), "+f"(d[OFF + 36]), "+f"(d[OFF + 37]), "+f"(d[OFF + 38]), "+f"(d[OFF + 39]), "+f"(d[OFF + 40]), "+f"(d[OFF + 41]), "+f"(d[OFF + 42]), "+f"(d[OFF + 43]), "+f"(d[OFF + 44]), "+f"(d[OFF + 45]), "+f"(d[OFF + 46]), "+f"(d[OFF + 47]), "+f"(d[OFF + 48]), "+f"(d[OFF + 49]), "+f"(d[OFF + 50]), "+f"(d[OFF + 51]), "+f"(d[OFF + 52]), "+f"(d[OFF + 53]), "+f"(d[OFF + 54]), "+f"(d[OFF + 55]), "+f"(d[OFF + 56]), "+f"(d[OFF + 57]), "+f"(d[OFF + 58]), "+f"(d[OFF + 59]), "+f"(d[OFF + 60]), "+f"(d[OFF + 61]), "+f"(d[OFF + 62]), "+f"(d[OFF + 63]), "+f"(d[OFF + 64]), "+f"(d[OFF + 65]), "+f"(d[OFF + 66]), "+f"(d[OFF + 67]), "+f"(d[OFF + 68]), "+f"(d[OFF + 69]), "+f"(d[OFF + 70]), "+f"(d[OFF + 71]), "+f"(d[OFF + 72]), "+f"(d[OFF + 73]), "+f"(d[OFF + 74]), "+f"(d[OFF + 75]), "+f"(d[OFF + 76]), "+f"(d[OFF + 77]), "+f"(d[OFF + 78]), "+f"(d[OFF + 79]), "+f"(d[OFF + 80]), "+f"(d[OFF + 81]), "+f"(d[OFF + 82]), "+f"(d[OFF + 83]), "+f"(d[OFF + 84]), "+f"(d[OFF + 85]), "+f"(d[OFF + 86]), "+f"(d[OFF + 87]), "+f"(d[OFF + 88]), "+f"(d[OFF + 89]), "+f"(d[OFF + 90]), "+f"(d[OFF + 91]), "+f"(d[OFF + 92]), "+f"(d[OFF + 93]), "+f"(d[OFF + 94]), "+f"(d[OFF + 95])
        : "l"(da), "l"(db));
}
template <int OFF>
__device__ __forceinline__ void wgmma_n128_tB(float (&d)[160], uint64_t da, uint64_t db) {
    asm volatile("wgmma.mma_async.sync.aligned.m64n128k16.f32.bf16.bf16 {%0,%1,%2,%3,%4,%5,%6,%7,%8,%9,%10,%11,%12,%13,%14,%15,%16,%17,%18,%19,%20,%21,%22,%23,%24,%25,%26,%27,%28,%29,%30,%31,%32,%33,%34,%35,%36,%37,%38,%39,%40,%41,%42,%43,%44,%45,%46,%47,%48,%49,%50,%51,%52,%53,%54,%55,%56,%57,%58,%59,%60,%61,%62,%63}, %64, %65, 1, 1, 1, 0, 1;\n"
        : "+f"(d[OFF + 0]), "+f"(d[OFF + 1]), "+f"(d[OFF + 2]), "+f"(d[OFF + 3]), "+f"(d[OFF + 4]), "+f"(d[OFF + 5]), "+f"(d[OFF + 6]), "+f"(d[OFF + 7]), "+f"(d[OFF + 8]), "+f"(d[OFF + 9]), "+f"(d[OFF + 10]), "+f"(d[OFF + 11]), "+f"(d[OFF + 12]), "+f"(d[OFF + 13]), "+f"(d[OFF + 14]), "+f"(d[OFF + 15]), "+f"(d[OFF + 16]), "+f"(d[OFF + 17]), "+f"(d[OFF + 18]), "+f"(d[OFF + 19]), "+f"(d[OFF + 20]), "+f"(d[OFF + 21]), "+f"(d[OFF + 22]), "+f"(d[OFF + 23]), "+f"(d[OFF + 24]), "+f"(d[OFF + 25]), "+f"(d[OFF + 26]), "+f"(d[OFF + 27]), "+f"(d[OFF + 28]), "+f"(d[OFF + 29]), "+f"(d[OFF + 30]), "+f"(d[OFF + 31]), "+f"(d[OFF + 32]), "+f"(d[OFF + 33]), "+f"(d[OFF + 34]), "+f"(d[OFF + 35]), "+f"(d[OFF + 36]), "+f"(d[OFF + 37]), "+f"(d[OFF + 38]), "+f"(d[OFF + 39]), "+f"(d[OFF + 40]), "+f"(d[OFF + 41]), "+f"(d[OFF + 42]), "+f"(d[OFF + 43]), "+f"(d[OFF + 44]), "+f"(d[OFF + 45]), "+f"(d[OFF + 46]), "+f"(d[OFF + 47]), "+f"(d[OFF + 48]), "+f"(d[OFF + 49]), "+f"(d[OFF + 50]), "+f"(d[OFF + 51]), "+f"(d[OFF + 52]), "+f"(d[OFF + 53]), "+f"(d[OFF + 54]), "+f"(d[OFF + 55]), "+f"(d[OFF + 56]), "+f"(d[OFF + 57]), "+f"(d[OFF + 58]), "+f"(d[OFF + 59]), "+f"(d[OFF + 60]), "+f"(d[OFF + 61]), "+f"(d[OFF + 62]), "+f"(d[OFF + 63])
        : "l"(da), "l"(db));
}
__device__ __forceinline__ void stsm4(uint32_t addr, uint32_t r0, uint32_t r1, uint32_t r2, uint32_t r3) {
    asm volatile("stmatrix.sync.aligned.m8n8.x4.shared.b16 [%0], {%1,%2,%3,%4};" :: "r"(addr), "r"(r0), "r"(r1), "r"(r2), "r"(r3) : "memory");
}

#define AX_BAR   0
#define NST_G 4
#define AX_EMPTY (AX_BAR + 16 + 8 * NST_G)
#define AX_DATA  1024
#define AX_UNIT  28672
#define AX_STAGE 57344
#define AX_TOTAL (AX_DATA + 8 * AX_UNIT)

__device__ __forceinline__ void attn_compute(unsigned char* smem, uint32_t sb, uint32_t buf, int warp, int lane);
__device__ __forceinline__ void attn_producer(unsigned char* smem, int hg, unsigned epoch) {
    const uint32_t sb = smem_u32(smem);
    const int lane = threadIdx.x & 31;
    {
        for (int s = 0; s < NSEG; s++) {
            const uint32_t buf = AX_DATA + (s & 1) * (4 * AX_UNIT), bar = sb + AX_BAR + 8 * (s & 1);
            if (lane < 4) wait_counter(&g_flag[s][4 * hg + lane], (epoch + 1) * 3u);
            if (lane == 4) mbar_wait_sleep(sb + AX_EMPTY + 8 * (s & 1), ((s >> 1) & 1) ^ 1);
            __syncwarp();
            if (lane == 0) mbar_expect_tx(bar, 4 * AX_UNIT);
            __syncwarp();
            if (lane < 24) {
                fence_async_all();
                const int u = lane / 6, r = lane % 6, hf = r & 1, kind = r >> 1;
                const uint32_t ub = sb + buf + u * AX_UNIT;
                const size_t img = ((size_t)(s * NH + 4 * hg + u) * 2) + hf;
                if (kind == 0) bulk_g2s(ub + hf * 4096, g_Qimg + img * 2048, 4096, bar);
                else if (kind == 1) bulk_g2s(ub + 8192 + hf * 5120, g_Kimg + img * 2560, 5120, bar);
                else bulk_g2s(ub + 18432 + hf * 5120, g_Vimg + img * 2560, 5120, bar);
            }
            __syncwarp();
        }
    }
}
__device__ __forceinline__ void attn_loop(unsigned char* smem, int hg, unsigned epoch) {
    const uint32_t sb = smem_u32(smem);
    const int tid = threadIdx.x, warp = tid >> 5, lane = tid & 31;
    for (int s = 0; s < NSEG; s++) {
        const uint32_t buf = AX_DATA + (s & 1) * (4 * AX_UNIT), bar = sb + AX_BAR + 8 * (s & 1);
        mbar_wait_sleep(bar, (s >> 1) & 1);
        if (s >= 36) ATR(2 + 2 * (s - 36));
        attn_compute(smem, sb, buf, warp, lane);
        if (s >= 36) ATR(3 + 2 * (s - 36));
        fence_async();
        __syncwarp();
        if (lane == 0) mbar_arrive(sb + AX_EMPTY + 16 + 8 * (s & 1));
    }
}
__device__ __forceinline__ void attn_storer(unsigned char* smem, int hg) {
    const uint32_t sb = smem_u32(smem);
    const int lane = threadIdx.x & 31;
    for (int s = 0; s < NSEG; s++) {
        const uint32_t buf = AX_DATA + (s & 1) * (4 * AX_UNIT);
        mbar_wait_sleep(sb + AX_EMPTY + 16 + 8 * (s & 1), (s >> 1) & 1);
        if (lane < 8) {
            const int uu = lane >> 1, hf = lane & 1, hh = 4 * hg + uu;
            bulk_s2g(g_Oimg + (((size_t)(s >> 2) * 64 + hh * 2 + hf) * 128 + (s & 3) * 32) * 64, sb + buf + uu * AX_UNIT + hf * 4096, 4096);
            bulk_commit();
            bulk_wait_read0();
            mbar_arrive(sb + AX_EMPTY + 8 * (s & 1));
            bulk_wait0();
            fence_async_all();
            __threadfence();
            atomicAdd(&g_ocnt[s >> 1], 1u);
        }
        __syncwarp();
    }
}
__device__ __forceinline__ void attn_compute(unsigned char* smem, uint32_t sb, uint32_t buf, int warp, int lane) {
    const int g = lane >> 2, t = lane & 3;
    const int u = warp >> 1, qh = warp & 1;
    const uint32_t ub = sb + buf + u * AX_UNIT;
    float sc[5][4];
    #pragma unroll
    for (int j = 0; j < 5; j++) { sc[j][0] = sc[j][1] = sc[j][2] = sc[j][3] = 0.f; }
    #pragma unroll
    for (int ks = 0; ks < 8; ks++) {
        const int hf = ks >> 2, c0 = (ks & 3) * 2;
        uint32_t a[4];
        { int mi = lane >> 3, row = 16 * qh + (mi & 1) * 8 + (lane & 7), chunk = c0 + (mi >> 1);
          ldsm4(a, ub + hf * 4096 + row * 128 + ((chunk ^ (row & 7)) << 4)); }
        #pragma unroll
        for (int jp = 0; jp < 3; jp++) {
            uint32_t b[4];
            int mi = lane >> 3, nt = 2 * jp + (mi >> 1); if (nt > 4) nt = 4;
            int row = 8 * nt + (lane & 7), chunk = c0 + (mi & 1);
            ldsm4(b, ub + 8192 + hf * 5120 + row * 128 + ((chunk ^ (row & 7)) << 4));
            mma_bf16(sc[2 * jp], a[0], a[1], a[2], a[3], b[0], b[1]);
            if (jp < 2) mma_bf16(sc[2 * jp + 1], a[0], a[1], a[2], a[3], b[2], b[3]);
        }
    }
    uint32_t pa[3][4];
    {
        const float sc2 = 0.08838834764831845f * 1.4426950408889634f;
        float mx0 = -3.0e38f, mx1 = -3.0e38f;
        const int q0 = 16 * qh + g, q1 = q0 + 8;
        #pragma unroll
        for (int j = 0; j < 5; j++)
            #pragma unroll
            for (int e = 0; e < 2; e++) {
                int key = 8 * j + 2 * t + e - 8;
                sc[j][e] = (key <= q0) ? sc[j][e] * sc2 : -3.0e38f;
                sc[j][2 + e] = (key <= q1) ? sc[j][2 + e] * sc2 : -3.0e38f;
                mx0 = fmaxf(mx0, sc[j][e]); mx1 = fmaxf(mx1, sc[j][2 + e]);
            }
        mx0 = fmaxf(mx0, __shfl_xor_sync(~0u, mx0, 1)); mx0 = fmaxf(mx0, __shfl_xor_sync(~0u, mx0, 2));
        mx1 = fmaxf(mx1, __shfl_xor_sync(~0u, mx1, 1)); mx1 = fmaxf(mx1, __shfl_xor_sync(~0u, mx1, 2));
        float s0 = 0.f, s1 = 0.f;
        #pragma unroll
        for (int j = 0; j < 5; j++)
            #pragma unroll
            for (int e = 0; e < 2; e++) {
                sc[j][e] = ex2_approx(sc[j][e] - mx0); sc[j][2 + e] = ex2_approx(sc[j][2 + e] - mx1);
                s0 += sc[j][e]; s1 += sc[j][2 + e];
            }
        s0 += __shfl_xor_sync(~0u, s0, 1); s0 += __shfl_xor_sync(~0u, s0, 2);
        s1 += __shfl_xor_sync(~0u, s1, 1); s1 += __shfl_xor_sync(~0u, s1, 2);
        const float i0 = __frcp_rn(s0), i1 = __frcp_rn(s1);
        #pragma unroll
        for (int k = 0; k < 3; k++) {
            pa[k][0] = pack_bf16(sc[2 * k][0] * i0, sc[2 * k][1] * i0);
            pa[k][1] = pack_bf16(sc[2 * k][2] * i1, sc[2 * k][3] * i1);
            if (k < 2) { pa[k][2] = pack_bf16(sc[2 * k + 1][0] * i0, sc[2 * k + 1][1] * i0); pa[k][3] = pack_bf16(sc[2 * k + 1][2] * i1, sc[2 * k + 1][3] * i1); }
            else { pa[k][2] = 0u; pa[k][3] = 0u; }
        }
    }
    __syncwarp();
    nbar_sync(5 + u, 64);
    #pragma unroll
    for (int np = 0; np < 8; np++) {
        const int hf = np >> 2, c0 = (np & 3) * 2;
        float o0[4] = {0, 0, 0, 0}, o1[4] = {0, 0, 0, 0};
        #pragma unroll
        for (int k = 0; k < 3; k++) {
            uint32_t b[4];
            int mi = lane >> 3;
            int row = 16 * k + (mi & 1) * 8 + (lane & 7); if (row > 39) row = 39 - 7 + (lane & 7);
            int chunk = c0 + (mi >> 1);
            ldsm4t(b, ub + 18432 + hf * 5120 + row * 128 + ((chunk ^ (row & 7)) << 4));
            mma_bf16(o0, pa[k][0], pa[k][1], pa[k][2], pa[k][3], b[0], k < 2 ? b[1] : 0u);
            mma_bf16(o1, pa[k][0], pa[k][1], pa[k][2], pa[k][3], b[2], k < 2 ? b[3] : 0u);
        }
        int mi = lane >> 3, row = 16 * qh + (mi & 1) * 8 + (lane & 7), chunk = c0 + (mi >> 1);
        stsm4(ub + hf * 4096 + row * 128 + ((chunk ^ (row & 7)) << 4), pack_bf16(o0[0], o0[1]), pack_bf16(o0[2], o0[3]), pack_bf16(o1[0], o1[1]), pack_bf16(o1[2], o1[3]));
    }
}

template <int V> struct IntC { static constexpr int value = V; };
struct Task { int type, rb, c, k0, nch, plane; };
#define NFINE 29
#define NGEMM (8 + 144 + 8 * 2 + 4 + 8 * 4 + 26 * 3 + 16 * 3)
__device__ __forceinline__ Task decode_task(int j) {
    Task t; t.type = 0; t.rb = 0; t.c = 0; t.k0 = 0; t.nch = 16; t.plane = 0;
    auto H = [&](int rb, int i) { t.type = 1; t.rb = rb; t.c = i & 1; t.plane = i >> 1; t.k0 = t.plane * 16; };
    auto CF = [&](int rb, int i) { t.type = 2; t.rb = rb; t.c = i & 1; t.k0 = rb * 64 + (i >> 1) * 16; t.nch = 16; };
    auto H13 = [&](int rb, int i) { t.type = 1; t.rb = rb; t.c = i & 1; t.plane = i >> 1; t.k0 = t.plane * 5; t.nch = (t.plane == 12) ? 4 : 5; };
    auto C13 = [&](int rb, int i) { t.type = 2; t.rb = rb; t.c = i & 1; t.k0 = rb * 64 + (i >> 1) * 8; t.nch = 8; };
    if (j >= NGEMM) { t.type = 3; return t; }
    if (j < 8) { t.c = j & 1; t.plane = j >> 1; t.k0 = t.plane * 16; return t; }
    j -= 8;
    if (j < 144) {
        const int q = j / 12, r = j % 12;
        if (r < 8) { t.rb = 2 * (q + 1); t.c = r & 1; t.plane = r >> 1; t.k0 = t.plane * 16; }
        else { t.type = 2; t.rb = 2 * q + ((r - 8) >> 1); t.c = r & 1; t.k0 = t.rb * 64; t.nch = 64; }
        return t;
    }
    j -= 144;
    if (j < 8) { H(26, j); return t; }
    j -= 8;
    if (j < 8) { H(27, j); return t; }
    j -= 8;
    if (j < 4) { t.type = 2; t.rb = 24 + (j >> 1); t.c = j & 1; t.k0 = t.rb * 64; t.nch = 64; return t; }
    j -= 4;
    if (j < 8) { H(28, j); return t; }
    j -= 8;
    if (j < 8) { CF(26, j); return t; }
    j -= 8;
    if (j < 8) { CF(27, j); return t; }
    j -= 8;
    if (j < 26) { H13(29, j); return t; }
    j -= 26;
    if (j < 8) { CF(28, j); return t; }
    j -= 8;
    if (j < 26) { H13(30, j); return t; }
    j -= 26;
    if (j < 16) { C13(29, j); return t; }
    j -= 16;
    if (j < 26) { H13(31, j); return t; }
    j -= 26;
    if (j < 16) { C13(30, j); return t; }
    j -= 16;
    C13(31, j);
    return t;
}
__device__ __forceinline__ void gemm_producer(unsigned char* smem, const CUtensorMap* womap, unsigned epoch, volatile int* s_tasks) {
    const uint32_t sb = smem_u32(smem);
    uint32_t st = 0, ph = 1;
    for (int n = 0;; n++) {
        const int j = (int)(atomicAdd(&g_gemmctr, 1u) - epoch * (unsigned)(NGEMM + NAUX - NATT));
        const Task t = decode_task(j);
        if (t.type <= 1) {
            wait_counter(&g_ocnt[t.rb], (epoch + 1) * 128u);
            if (t.type == 0) wait_counter(&g_ocnt[t.rb + 1], (epoch + 1) * 128u);
            fence_async_all();
        } else if (t.type == 2) {
            wait_counter(&g_gcnt[t.rb][t.c], (epoch + 1) * (t.rb >= NFINE ? 13u : 4u));
            wait_counter(&g_ssmcnt, (epoch + 1) * 80u);
        }
        const int nch = (t.type <= 1) ? t.nch : 1;
        for (int kc = 0; kc < nch; kc++) {
            mbar_wait_sleep(sb + AX_EMPTY + 8 * st, ph);
            const uint32_t a = sb + AX_DATA + st * AX_STAGE, bar = sb + AX_BAR + 16 + 8 * st;
            if (kc == 0) s_tasks[n & 7] = j;
            if (t.type > 1) mbar_arrive(bar);
            else {
                const bf16* asrc = g_Oimg + ((size_t)(t.rb >> 1) * 64 + t.k0 + kc) * 8192 + (t.rb & 1) * 4096;
                if (t.type == 0) { mbar_expect_tx(bar, AX_STAGE); bulk_g2s(a, asrc, 8192, bar); bulk_g2s(a + 8192, asrc + 4096, 8192, bar); }
                else { mbar_expect_tx(bar, AX_STAGE - 8192); bulk_g2s(a, asrc, 8192, bar); }
                #pragma unroll
                for (int b = 0; b < 5; b++) tma_load_2d(a + 16384 + b * 8192, womap, t.c * 320 + b * 64, (t.k0 + kc) * 64, bar);
            }
            if (++st == NST_G) { st = 0; ph ^= 1; }
        }
        if (t.type == 3) break;
    }
}
__device__ __forceinline__ void gemm_signaller(volatile int* s_done) {
    for (int n = 0;; n++) {
        nbar_sync(2, 288);
        const int j = s_done[n & 7];
        if (j < 0) break;
        if ((threadIdx.x & 31) == 0) {
            const Task t = decode_task(j);
            __threadfence();
            atomicAdd(&g_gcnt[t.rb][t.c], 1u);
            if (t.type == 0) atomicAdd(&g_gcnt[t.rb + 1][t.c], 1u);
        }
        __syncwarp();
    }
}
__device__ __forceinline__ void gemm_consumer(unsigned char* smem, bf16* __restrict__ out, volatile int* s_tasks, volatile int* s_done) {
    const uint32_t sb = smem_u32(smem);
    const int tid = threadIdx.x, lane = tid & 31;
    const int wg = __shfl_sync(~0u, tid >> 7, 0), warp = __shfl_sync(~0u, (tid >> 5) & 3, 0);
    uint32_t st = 0, ph = 0;
    int ndone = 0;
    for (int n = 0;; n++) {
        mbar_wait_sleep(sb + AX_BAR + 16 + 8 * st, ph);
        const Task t = decode_task(__shfl_sync(~0u, s_tasks[n & 7], 0));
        if (t.type > 1) {
            nbar_sync(1, 256);
            if ((tid & 127) == 0) mbar_arrive(sb + AX_EMPTY + 8 * st);
            if (++st == NST_G) { st = 0; ph ^= 1; }
            if (t.type == 3) break;
            const int np = (t.rb >= NFINE) ? 13 : 4;
            const float* pbase = (t.rb >= NFINE) ? g_part31 + (size_t)(t.rb - NFINE) * 13 * 64 * DM - (size_t)t.rb * 64 * DM : g_part;
            const size_t pstride = (t.rb >= NFINE) ? (size_t)64 * DM : (size_t)SEQ * DM;
            auto combine = [&](int i, auto NP) {
                const int r = t.k0 + i / 80, cc = t.c * 320 + (i % 80) * 4;
                float4 v[NP.value];
                #pragma unroll
                for (int q = 0; q < NP.value; q++) v[q] = __ldcg(reinterpret_cast<const float4*>(pbase + q * pstride + (size_t)r * DM + cc));
                const float gt = __ldcg(g_g + r);
                const uint2 bb = __ldcg(reinterpret_cast<const uint2*>(g_b + (size_t)r * DM + cc));
                float4 a = v[0];
                #pragma unroll
                for (int q = 1; q < NP.value; q++) { a.x += v[q].x; a.y += v[q].y; a.z += v[q].z; a.w += v[q].w; }
                const float b0 = __uint_as_float(bb.x << 16), b1 = __uint_as_float(bb.x & 0xffff0000u), b2 = __uint_as_float(bb.y << 16), b3 = __uint_as_float(bb.y & 0xffff0000u);
                uint2 o; o.x = pack_bf16(gt * a.x + (1.f - gt) * b0, gt * a.y + (1.f - gt) * b1); o.y = pack_bf16(gt * a.z + (1.f - gt) * b2, gt * a.w + (1.f - gt) * b3);
                *reinterpret_cast<uint2*>(out + (size_t)r * DM + cc) = o;
            };
            if (np == 4) {
                const int nit = t.nch * 80 / 256;
                for (int it0 = 0; it0 < nit; it0 += 5) {
                    #pragma unroll
                    for (int it = 0; it < 5; it++) combine(tid + 256 * (it0 + it), IntC<4>());
                }
            } else {
                #pragma unroll
                for (int it = 0; it < 3; it++) { const int i = tid + 256 * it; if (i < 640) combine(i, IntC<13>()); }
            }
            if (n < 56) ATRID(6 + n, s_tasks[n & 7]);
            continue;
        }
        const int g = lane >> 2, tq = lane & 3;
        if (t.type == 0) {
            float acc[160];
            #pragma unroll
            for (int i = 0; i < 160; i++) acc[i] = 0.f;
            uint32_t prev = 0;
            for (int kc = 0; kc < 16; kc++) {
                mbar_wait(sb + AX_BAR + 16 + 8 * st, ph);
                const uint32_t a = sb + AX_DATA + st * AX_STAGE;
                const uint64_t da = make_desc(a + wg * 8192, 16, 1024), db = make_desc(a + 16384, 8192, 1024);
                wg_fence();
                #pragma unroll
                for (int ks = 0; ks < 4; ks++) {
                    wgmma_n192_tB<0>(acc, da + ks * 2, db + ks * 128);
                    wgmma_n128_tB<96>(acc, da + ks * 2, db + ks * 128 + 3 * 512);
                }
                wg_commit();
                asm volatile("wgmma.wait_group.sync.aligned 1;" ::: "memory");
                if (kc > 0 && (tid & 127) == 0) mbar_arrive(sb + AX_EMPTY + 8 * prev);
                prev = st;
                if (++st == NST_G) { st = 0; ph ^= 1; }
            }
            wg_wait0();
            if ((tid & 127) == 0) mbar_arrive(sb + AX_EMPTY + 8 * prev);
            float* base = g_part + ((size_t)t.plane * SEQ + t.rb * 64 + wg * 64 + warp * 16 + g) * DM + t.c * 320 + 2 * tq;
            #pragma unroll
            for (int q = 0; q < 40; q++) {
                *reinterpret_cast<float2*>(base + q * 8) = make_float2(acc[4 * q], acc[4 * q + 1]);
                *reinterpret_cast<float2*>(base + 8 * DM + q * 8) = make_float2(acc[4 * q + 2], acc[4 * q + 3]);
            }
        } else {
            float* base = (t.rb >= NFINE ? g_part31 + (size_t)((t.rb - NFINE) * 13 + t.plane) * 64 * DM : g_part + ((size_t)t.plane * SEQ + t.rb * 64) * DM) + (size_t)(warp * 16 + g) * DM + t.c * 320 + 2 * tq;
            if (wg == 0) {
                float acc[160];
                #pragma unroll
                for (int i = 0; i < 96; i++) acc[i] = 0.f;
                uint32_t prev = 0;
                for (int kc = 0; kc < t.nch; kc++) {
                    mbar_wait(sb + AX_BAR + 16 + 8 * st, ph);
                    const uint32_t a = sb + AX_DATA + st * AX_STAGE;
                    const uint64_t da = make_desc(a, 16, 1024), db = make_desc(a + 16384, 8192, 1024);
                    wg_fence();
                    #pragma unroll
                    for (int ks = 0; ks < 4; ks++) wgmma_n192_tB<0>(acc, da + ks * 2, db + ks * 128);
                    wg_commit();
                    asm volatile("wgmma.wait_group.sync.aligned 1;" ::: "memory");
                    if (kc > 0 && (tid & 127) == 0) mbar_arrive(sb + AX_EMPTY + 8 * prev);
                    prev = st;
                    if (++st == NST_G) { st = 0; ph ^= 1; }
                }
                wg_wait0();
                if ((tid & 127) == 0) mbar_arrive(sb + AX_EMPTY + 8 * prev);
                #pragma unroll
                for (int q = 0; q < 24; q++) {
                    *reinterpret_cast<float2*>(base + q * 8) = make_float2(acc[4 * q], acc[4 * q + 1]);
                    *reinterpret_cast<float2*>(base + 8 * DM + q * 8) = make_float2(acc[4 * q + 2], acc[4 * q + 3]);
                }
            } else {
                float acc[160];
                #pragma unroll
                for (int i = 96; i < 160; i++) acc[i] = 0.f;
                uint32_t prev = 0;
                for (int kc = 0; kc < t.nch; kc++) {
                    mbar_wait(sb + AX_BAR + 16 + 8 * st, ph);
                    const uint32_t a = sb + AX_DATA + st * AX_STAGE;
                    const uint64_t da = make_desc(a, 16, 1024), db = make_desc(a + 16384, 8192, 1024);
                    wg_fence();
                    #pragma unroll
                    for (int ks = 0; ks < 4; ks++) wgmma_n128_tB<96>(acc, da + ks * 2, db + ks * 128 + 3 * 512);
                    wg_commit();
                    asm volatile("wgmma.wait_group.sync.aligned 1;" ::: "memory");
                    if (kc > 0 && (tid & 127) == 0) mbar_arrive(sb + AX_EMPTY + 8 * prev);
                    prev = st;
                    if (++st == NST_G) { st = 0; ph ^= 1; }
                }
                wg_wait0();
                if ((tid & 127) == 0) mbar_arrive(sb + AX_EMPTY + 8 * prev);
                #pragma unroll
                for (int q = 24; q < 40; q++) {
                    *reinterpret_cast<float2*>(base + q * 8) = make_float2(acc[4 * q], acc[4 * q + 1]);
                    *reinterpret_cast<float2*>(base + 8 * DM + q * 8) = make_float2(acc[4 * q + 2], acc[4 * q + 3]);
                }
            }
        }
        if (tid == 0) s_done[ndone & 7] = s_tasks[n & 7];
        ndone++;
        nbar_arrive(2, 288);
        if (n < 56) ATRID(6 + n, s_tasks[n & 7]);
    }
    if (tid == 0) s_done[ndone & 7] = -1;
    nbar_arrive(2, 288);
}

__global__ void __launch_bounds__(384, 1)
k_aux(const __grid_constant__ CUtensorMap womap, const bf16* __restrict__ x, const bf16* __restrict__ A_re, const bf16* __restrict__ A_im,
      const bf16* __restrict__ B_re, const bf16* __restrict__ B_im, const bf16* __restrict__ C_re, const bf16* __restrict__ C_im,
      const bf16* __restrict__ log_dt, const bf16* __restrict__ Dskip, const bf16* __restrict__ gw, bf16* __restrict__ out) {
    extern __shared__ __align__(1024) unsigned char smem[];
    const uint32_t sb = smem_u32(smem);
    const int tid = threadIdx.x, warp = tid >> 5, lane = tid & 31;
    __shared__ unsigned s_epoch;
    __shared__ int s_task, s_tasks[8], s_done[8];
    if (tid == 0) {
        for (int i = 0; i < 2 + NST_G; i++) mbar_init(sb + AX_BAR + 8 * i, 1);
        for (int i = 0; i < NST_G; i++) mbar_init(sb + AX_EMPTY + 8 * i, blockIdx.x < NATT ? 8 : 2);
        asm volatile("fence.mbarrier_init.release.cluster;" ::: "memory");
        s_epoch = *reinterpret_cast<volatile unsigned*>(&g_epoch);
    }
    __syncthreads();
    const unsigned epoch = s_epoch;
    ATR(0);
    const int wg = __shfl_sync(~0u, tid >> 7, 0);
    if (wg == 2) {
        asm volatile("setmaxnreg.dec.sync.aligned.u32 40;");
        if (blockIdx.x < NATT) { if (warp == 8) attn_producer(smem, blockIdx.x, epoch); else if (warp == 9) attn_storer(smem, blockIdx.x); }
        else {
            nbar_sync(3, 384);
            if (warp == 8) { if (lane == 0) gemm_producer(smem, &womap, epoch, s_tasks); }
            else if (warp == 9) gemm_signaller(s_done);
        }
        __syncwarp();
        nbar_sync(4, 384);
    } else {
        asm volatile("setmaxnreg.inc.sync.aligned.u32 232;");
        if (blockIdx.x < NATT) attn_loop(smem, blockIdx.x, epoch);
        else {
            int ntask = 0;
            for (;;) {
                nbar_sync(1, 256);
                if (tid == 0) s_task = (int)(atomicAdd(&g_taskctr, 1u) - epoch * (unsigned)(80 + NAUX - NATT));
                nbar_sync(1, 256);
                const int task = s_task;
                if (task >= 80) break;
                for (int r = task * 26 + warp; r < min(SEQ, task * 26 + 26); r += 8) {
                    float sum = 0.f;
                    for (int i = lane * 2; i < DM; i += 64) {
                        __nv_bfloat162 xv = *reinterpret_cast<const __nv_bfloat162*>(x + (size_t)r * DM + i), wv = *reinterpret_cast<const __nv_bfloat162*>(gw + i);
                        sum += bf2f(xv.x) * bf2f(wv.x) + bf2f(xv.y) * bf2f(wv.y);
                    }
                    #pragma unroll
                    for (int o = 16; o; o >>= 1) sum += __shfl_xor_sync(~0u, sum, o);
                    if (lane == 0) g_g[r] = 1.f / (1.f + expf(-sum));
                }
                ssm_group(smem + AX_DATA, task, x, A_re, A_im, B_re, B_im, C_re, C_im, log_dt, Dskip);
                nbar_sync(1, 256);
                if (tid == 0) { __threadfence(); atomicAdd(&g_ssmcnt, 1u); }
                if (ntask < 4) ATR(2 + ntask);
                ntask++;
            }
            fence_async();
            nbar_sync(3, 384);
            gemm_consumer(smem, out, s_tasks, s_done);
        }
        nbar_sync(4, 384);
        if (tid == 0) {
            __threadfence();
            unsigned old = atomicAdd(&g_auxdone, 1u);
            if (old == NAUX - 1) { g_auxdone = 0; __threadfence(); atomicAdd(&g_epoch, 1u); }
        }
    }
    asm volatile("griddepcontrol.wait;" ::: "memory");
}

extern "C" void kernel_launch(void* const* d_in, const int* in_sizes, int n_in, void* d_out, int out_size) {
    const bf16* x = (const bf16*)d_in[0];
    const bf16* mem0 = (const bf16*)d_in[1];
    const bf16* Wq = (const bf16*)d_in[2];
    const bf16* Wk = (const bf16*)d_in[3];
    const bf16* Wv = (const bf16*)d_in[4];
    const bf16* Wo = (const bf16*)d_in[5];
    const bf16 *A_re = (const bf16*)d_in[8], *A_im = (const bf16*)d_in[9], *B_re = (const bf16*)d_in[10], *B_im = (const bf16*)d_in[11];
    const bf16 *C_re = (const bf16*)d_in[12], *C_im = (const bf16*)d_in[13], *log_dt = (const bf16*)d_in[14], *Dskip = (const bf16*)d_in[15];
    const bf16* gw = (const bf16*)d_in[16];
    bf16* out = (bf16*)d_out;
    cudaStream_t st = cudaStreamPerThread;
    static bool init = false;
    static CUtensorMap xmap, womap, wqmap, wkmap, wvmap;
    static const void* xmap_ptr = nullptr; static const void* womap_ptr = nullptr; static const void* w_ptr[3] = {nullptr, nullptr, nullptr};
    if (!init) {
        cudaFuncSetAttribute(k_chain, cudaFuncAttributeMaxDynamicSharedMemorySize, SM_TOTAL);
        cudaFuncSetAttribute(k_aux, cudaFuncAttributeMaxDynamicSharedMemorySize, AX_TOTAL);
        init = true;
    }
    if (xmap_ptr != (const void*)x || womap_ptr != (const void*)Wo || w_ptr[0] != Wq || w_ptr[1] != Wk || w_ptr[2] != Wv) {
        void* fn = nullptr; cudaDriverEntryPointQueryResult qres;
        cudaGetDriverEntryPoint("cuTensorMapEncodeTiled", &fn, cudaEnableDefault, &qres);
        typedef CUresult (*EncFn)(CUtensorMap*, CUtensorMapDataType, cuuint32_t, void*, const cuuint64_t*, const cuuint64_t*, const cuuint32_t*, const cuuint32_t*,
                                  CUtensorMapInterleave, CUtensorMapSwizzle, CUtensorMapL2promotion, CUtensorMapFloatOOBfill);
        cuuint32_t es[2] = {1, 1};
        {
          cuuint64_t dims[3] = {64, SEQ, 10}; cuuint64_t strides[2] = {DM * 2, 128}; cuuint32_t box[3] = {64, 32, 10}; cuuint32_t es3[3] = {1, 1, 1};
          ((EncFn)fn)(&xmap, CU_TENSOR_MAP_DATA_TYPE_BFLOAT16, 3, (void*)x, dims, strides, box, es3, CU_TENSOR_MAP_INTERLEAVE_NONE, CU_TENSOR_MAP_SWIZZLE_128B,
                      CU_TENSOR_MAP_L2_PROMOTION_L2_128B, CU_TENSOR_MAP_FLOAT_OOB_FILL_NONE); }
        { cuuint64_t dims[2] = {DM, HD}; cuuint64_t strides[1] = {DM * 2}; cuuint32_t box[2] = {64, 64};
          ((EncFn)fn)(&womap, CU_TENSOR_MAP_DATA_TYPE_BFLOAT16, 2, (void*)Wo, dims, strides, box, es, CU_TENSOR_MAP_INTERLEAVE_NONE, CU_TENSOR_MAP_SWIZZLE_128B,
                      CU_TENSOR_MAP_L2_PROMOTION_L2_128B, CU_TENSOR_MAP_FLOAT_OOB_FILL_NONE); }
        { cuuint64_t dims[2] = {HD, DM}; cuuint64_t strides[1] = {HD * 2}; cuuint32_t box[2] = {64, 128};
          const bf16* ws[3] = {Wq, Wk, Wv}; CUtensorMap* ms[3] = {&wqmap, &wkmap, &wvmap};
          for (int i = 0; i < 3; i++)
              ((EncFn)fn)(ms[i], CU_TENSOR_MAP_DATA_TYPE_BFLOAT16, 2, (void*)ws[i], dims, strides, box, es, CU_TENSOR_MAP_INTERLEAVE_NONE, CU_TENSOR_MAP_SWIZZLE_128B,
                          CU_TENSOR_MAP_L2_PROMOTION_L2_128B, CU_TENSOR_MAP_FLOAT_OOB_FILL_NONE); }
        xmap_ptr = (const void*)x; womap_ptr = (const void*)Wo; w_ptr[0] = Wq; w_ptr[1] = Wk; w_ptr[2] = Wv;
    }
    k_chain<<<96, 384, SM_TOTAL, st>>>(xmap, wqmap, wkmap, wvmap, womap, x, mem0);
    {
        cudaLaunchConfig_t cfg = {};
        cfg.gridDim = dim3(NAUX); cfg.blockDim = dim3(384); cfg.dynamicSmemBytes = AX_TOTAL; cfg.stream = st;
        cudaLaunchAttribute at[1];
        at[0].id = cudaLaunchAttributeProgrammaticStreamSerialization; at[0].val.programmaticStreamSerializationAllowed = 1;
        cfg.attrs = at; cfg.numAttrs = 1;
        cudaLaunchKernelEx(&cfg, k_aux, womap, x, A_re, A_im, B_re, B_im, C_re, C_im, log_dt, Dskip, gw, out);
    }
}
```

```cpp
#include <cuda_runtime.h>
#include <cuda_bf16.h>
#include <stdint.h>
#include <cuda.h>

typedef __nv_bfloat16 bf16;

#define SEQ 2048
#define DM 640
#define NH 32
#define DH 128
#define NM 8
#define SEG 32
#define NSEG 64
#define NST 128
#define HD 4096

__device__ bf16  g_b[SEQ * DM];
__device__ float g_g[SEQ];

__device__ __forceinline__ float bf2f(bf16 v) { return __bfloat162float(v); }
__device__ __forceinline__ uint32_t pack_bf16(float lo, float hi) {
    uint32_t r; asm("cvt.rn.bf16x2.f32 %0, %1, %2;" : "=r"(r) : "f"(hi), "f"(lo)); return r;
}
__device__ __forceinline__ uint32_t f2tf32(float x) { uint32_t r; asm("cvt.rna.tf32.f32 %0, %1;" : "=r"(r) : "f"(x)); return r; }
__device__ __forceinline__ void mma_tf32(float (&d)[4], uint32_t a0, uint32_t a1, uint32_t a2, uint32_t a3, uint32_t b0, uint32_t b1) {
    asm volatile("mma.sync.aligned.m16n8k8.row.col.f32.tf32.tf32.f32 {%0,%1,%2,%3}, {%4,%5,%6,%7}, {%8,%9}, {%0,%1,%2,%3};\n"
        : "+f"(d[0]), "+f"(d[1]), "+f"(d[2]), "+f"(d[3]) : "r"(a0), "r"(a1), "r"(a2), "r"(a3), "r"(b0), "r"(b1));
}
__device__ __forceinline__ void mma_bf16(float (&d)[4], uint32_t a0, uint32_t a1, uint32_t a2, uint32_t a3, uint32_t b0, uint32_t b1) {
    asm volatile("mma.sync.aligned.m16n8k16.row.col.f32.bf16.bf16.f32 {%0,%1,%2,%3}, {%4,%5,%6,%7}, {%8,%9}, {%0,%1,%2,%3};\n"
        : "+f"(d[0]), "+f"(d[1]), "+f"(d[2]), "+f"(d[3]) : "r"(a0), "r"(a1), "r"(a2), "r"(a3), "r"(b0), "r"(b1));
}
struct cf { float re, im; };
__device__ __forceinline__ cf cmul(cf a, cf b) { cf r; r.re = a.re * b.re - a.im * b.im; r.im = a.re * b.im + a.im * b.re; return r; }
__device__ __forceinline__ cf csq(cf a) { cf r; r.re = a.re * a.re - a.im * a.im; r.im = 2.f * a.re * a.im; return r; }
__device__ __forceinline__ cf cexpL(float zr, float zi, float L) {
    float e = __expf(zr * L);
    float ang = zi * L;
    float k = rintf(ang * 0.15915494309189535f);
    ang = fmaf(-k, 6.2831854820251465f, ang);
    ang = fmaf(-k, -1.7484555314695172e-07f, ang);
    cf r; r.re = e * __cosf(ang); r.im = e * __sinf(ang); return r;
}

#define SSM_CH 8
#define KC_PITCH 648
#define XS_PAD 128
#define XS_PITCH (XS_PAD + 2048 + 8)
#define YS_PITCH (2048 + 8)
#define KT_LEN (2048 + 48)
struct SsmSmem {
    float Kc[SSM_CH][KC_PITCH];
    bf16  xs[SSM_CH][XS_PITCH];
    union {
        bf16  KT[SSM_CH][2][KT_LEN];
        float st[SSM_CH][NST][8];
    } u;
    bf16  ys[SSM_CH][YS_PITCH];
    uint16_t kidx[2048];
};

__device__ __forceinline__ int kc_index(int l) {
    return l < 256 ? l : (l < 512 ? 256 + ((l - 256) >> 1) : (l < 1024 ? 384 + ((l - 512) >> 2) : 512 + ((l - 1024) >> 3)));
}

__device__ __forceinline__ void ssm_group(unsigned char* smem_raw, int grp, const bf16* __restrict__ x, const bf16* __restrict__ A_re, const bf16* __restrict__ A_im,
        const bf16* __restrict__ B_re, const bf16* __restrict__ B_im, const bf16* __restrict__ C_re, const bf16* __restrict__ C_im,
        const bf16* __restrict__ log_dt, const bf16* __restrict__ Dskip) {
    SsmSmem& S = *reinterpret_cast<SsmSmem*>(smem_raw);
    const int tid = threadIdx.x, w = tid >> 5, lane = tid & 31, g = lane >> 2, t = lane & 3;
    const int d0 = grp * SSM_CH;
    asm volatile("bar.sync 1, 256;" ::: "memory");
    #pragma unroll
    for (int it = 0; it < 8; it++) {
        const int l = tid + 256 * it;
        uint4 v = *reinterpret_cast<const uint4*>(x + (size_t)l * DM + d0);
        const bf16* p = reinterpret_cast<const bf16*>(&v);
        const int lr = (l & ~15) | (15 - (l & 15));
        #pragma unroll
        for (int c = 0; c < 8; c++) S.xs[c][XS_PAD + lr] = p[c];
        S.kidx[l] = (uint16_t)((int)bf2f(__float2bfloat16_rn((float)l)) == 2048 ? 640 : kc_index((int)bf2f(__float2bfloat16_rn((float)l))));
    }
    for (int i = tid; i < SSM_CH * XS_PAD / 2; i += 256) reinterpret_cast<uint32_t*>(&S.xs[i / (XS_PAD / 2)][0])[i % (XS_PAD / 2)] = 0u;
    {
        const int d = d0 + w;
        const float dt = bf2f(__float2bfloat16_rn(expf(bf2f(log_dt[d]))));
        #pragma unroll
        for (int i = 0; i < 4; i++) {
            const int n = lane + 32 * i;
            float zr = dt * bf2f(A_re[d * NST + n]), zi = dt * bf2f(A_im[d * NST + n]);
            cf dB; dB.re = dt * bf2f(B_re[d * NST + n]); dB.im = dt * bf2f(B_im[d * NST + n]);
            cf C; C.re = bf2f(C_re[d * NST + n]); C.im = bf2f(C_im[d * NST + n]);
            cf wv = cmul(C, dB);
            cf u8 = cexpL(zr, zi, 8.f), u128 = cexpL(zr, zi, 128.f);
            float* st = S.u.st[w][n];
            *reinterpret_cast<float4*>(st) = make_float4(zr, zi, wv.re, wv.im);
            *reinterpret_cast<float4*>(st + 4) = make_float4(u8.re, u8.im, u128.re, u128.im);
        }
        __syncwarp();
        float a0a[4] = {0, 0, 0, 0}, a0b[4] = {0, 0, 0, 0}, a1[4] = {0, 0, 0, 0}, a2a[4] = {0, 0, 0, 0}, a2b[4] = {0, 0, 0, 0};
        float k2048 = 0.f;
        const float Lg = (g < 4) ? (512.f + 4.f * g) : (g < 6 ? 1024.f + 8.f * (g - 4) : 1536.f + 8.f * (g - 6));
        #pragma unroll 4
        for (int kk = 0; kk < 32; kk++) {
            const float* st = S.u.st[w][4 * kk + t];
            float4 s0 = *reinterpret_cast<const float4*>(st), s1 = *reinterpret_cast<const float4*>(st + 4);
            cf wv; wv.re = s0.z; wv.im = s0.w;
            cf u8; u8.re = s1.x; u8.im = s1.y;
            cf u128; u128.re = s1.z; u128.im = s1.w;
            cf e1 = cexpL(s0.x, s0.y, (float)g);
            cf e23 = cexpL(s0.x, s0.y, Lg);
            cf e1b = cmul(e1, u8);
            cf e2 = csq(e1);
            cf p = csq(csq(csq(e2)));
            cf f0 = cmul(wv, p), f1 = cmul(f0, u128), f2 = cmul(f1, u128), f3 = cmul(f2, u128);
            uint32_t A00 = f2tf32(f0.re), A01 = f2tf32(f1.re), A02 = f2tf32(-f0.im), A03 = f2tf32(-f1.im);
            uint32_t A10 = f2tf32(f2.re), A11 = f2tf32(f3.re), A12 = f2tf32(-f2.im), A13 = f2tf32(-f3.im);
            mma_tf32(a0a, A00, A01, A02, A03, f2tf32(e1.re), f2tf32(e1.im));
            mma_tf32(a0b, A00, A01, A02, A03, f2tf32(e1b.re), f2tf32(e1b.im));
            mma_tf32(a1, A10, A11, A12, A13, f2tf32(e2.re), f2tf32(e2.im));
            uint32_t E0 = f2tf32(e23.re), E1 = f2tf32(e23.im);
            mma_tf32(a2a, A00, A01, A02, A03, E0, E1);
            mma_tf32(a2b, A10, A11, A12, A13, E0, E1);
            cf e2048 = csq(e23);
            k2048 += wv.re * e2048.re - wv.im * e2048.im;
        }
        k2048 += __shfl_xor_sync(~0u, k2048, 1);
        k2048 += __shfl_xor_sync(~0u, k2048, 2);
        float* Kc = S.Kc[w];
        Kc[16 * g + 2 * t] = a0a[0]; Kc[16 * g + 2 * t + 1] = a0a[1]; Kc[16 * (g + 8) + 2 * t] = a0a[2]; Kc[16 * (g + 8) + 2 * t + 1] = a0a[3];
        Kc[16 * g + 8 + 2 * t] = a0b[0]; Kc[16 * g + 8 + 2 * t + 1] = a0b[1]; Kc[16 * (g + 8) + 8 + 2 * t] = a0b[2]; Kc[16 * (g + 8) + 8 + 2 * t + 1] = a0b[3];
        Kc[256 + 8 * g + 2 * t] = a1[0]; Kc[256 + 8 * g + 2 * t + 1] = a1[1]; Kc[256 + 8 * (g + 8) + 2 * t] = a1[2]; Kc[256 + 8 * (g + 8) + 2 * t + 1] = a1[3];
        #pragma unroll
        for (int mt = 0; mt < 2; mt++) {
            #pragma unroll
            for (int e = 0; e < 4; e++) {
                int A = mt * 16 + g + (e >> 1) * 8, j = 2 * t + (e & 1);
                int Lj = (j < 4) ? 512 + 4 * j : (j < 6 ? 1024 + 8 * (j - 4) : 1536 + 8 * (j - 6));
                Kc[kc_index(Lj + 16 * A)] = mt ? a2b[e] : a2a[e];
            }
        }
        if (lane == 16) Kc[640] = k2048;
    }
    __syncwarp();
    {
        asm volatile("bar.sync 1, 256;" ::: "memory");
        bf16* k0 = S.u.KT[w][0];
        bf16* k1 = S.u.KT[w][1];
        const float* Kc = S.Kc[w];
        #pragma unroll 8
        for (int j = lane; j < 2048; j += 32) {
            const bf16 v = __float2bfloat16_rn(Kc[S.kidx[j]]);
            k0[16 + j] = v;
            k1[15 + j] = v;
        }
        if (lane < 16) { k0[lane] = __float2bfloat16_rn(0.f); if (lane < 15) k1[lane] = __float2bfloat16_rn(0.f); }
        k0[2064 + lane] = __float2bfloat16_rn(0.f); k1[2063 + lane] = __float2bfloat16_rn(0.f);
        __syncwarp();
    }
    {
        float acc[16][4];
        #pragma unroll
        for (int v = 0; v < 16; v++) { acc[v][0] = acc[v][1] = acc[v][2] = acc[v][3] = 0.f; }
        const bf16* kt = (g & 1) ? &S.u.KT[w][0][0] : &S.u.KT[w][1][0];
        const int ibase0 = g + 1 + 2 * t - ((g & 1) ? 0 : 1);
        #pragma unroll 1
        for (int r = 0; r < 8; r++) {
            uint32_t B[16][2];
            #pragma unroll
            for (int v = 0; v < 16; v++) {
                const bf16* p = &S.xs[w][XS_PAD + 16 * (8 * v + g - r) + 2 * t];
                B[v][0] = *reinterpret_cast<const uint32_t*>(p);
                B[v][1] = *reinterpret_cast<const uint32_t*>(p + 8);
            }
            #pragma unroll
            for (int q = 0; q < 16; q++) {
                const int i0 = ibase0 + 16 * r + 128 * q;
                const uint32_t A0 = *reinterpret_cast<const uint32_t*>(kt + i0);
                const uint32_t A1 = *reinterpret_cast<const uint32_t*>(kt + i0 + 8);
                const uint32_t A3 = *reinterpret_cast<const uint32_t*>(kt + i0 + 16);
                #pragma unroll
                for (int v = q; v < 16; v++) mma_bf16(acc[v], A0, A1, A1, A3, B[v - q][0], B[v - q][1]);
            }
        }
        bf16* ys = S.ys[w];
        #pragma unroll
        for (int v = 0; v < 16; v++) {
            const int a = 8 * v + 2 * t;
            ys[16 * a + g] = __float2bfloat16_rn(acc[v][0]); ys[16 * (a + 1) + g] = __float2bfloat16_rn(acc[v][1]);
            ys[16 * a + g + 8] = __float2bfloat16_rn(acc[v][2]); ys[16 * (a + 1) + g + 8] = __float2bfloat16_rn(acc[v][3]);
        }
    }
    asm volatile("bar.sync 1, 256;" ::: "memory");
    {
        float dsk[8];
        #pragma unroll
        for (int c = 0; c < 8; c++) dsk[c] = bf2f(Dskip[d0 + c]);
        #pragma unroll 2
        for (int it = 0; it < 8; it++) {
            const int l = tid + 256 * it;
            const int lr = XS_PAD + ((l & ~15) | (15 - (l & 15)));
            float o[8];
            #pragma unroll
            for (int c = 0; c < 8; c++) o[c] = bf2f(S.ys[c][l]) + bf2f(__float2bfloat16_rn(bf2f(S.xs[c][lr]) * dsk[c]));
            *reinterpret_cast<uint4*>(g_b + (size_t)l * DM + d0) = make_uint4(pack_bf16(o[0], o[1]), pack_bf16(o[2], o[3]), pack_bf16(o[4], o[5]), pack_bf16(o[6], o[7]));
        }
    }
}

__device__ __forceinline__ uint32_t smem_u32(const void* p) { return (uint32_t)__cvta_generic_to_shared(p); }
__device__ __forceinline__ void mbar_init(uint32_t bar, uint32_t cnt) { asm volatile("mbarrier.init.shared::cta.b64 [%0], %1;" :: "r"(bar), "r"(cnt) : "memory"); }
__device__ __forceinline__ void mbar_expect_tx(uint32_t bar, uint32_t bytes) { asm volatile("mbarrier.arrive.expect_tx.shared::cta.b64 _, [%0], %1;" :: "r"(bar), "r"(bytes) : "memory"); }
__device__ __forceinline__ void mbar_arrive(uint32_t bar) { asm volatile("mbarrier.arrive.shared::cta.b64 _, [%0];" :: "r"(bar) : "memory"); }
__device__ __forceinline__ void mbar_wait(uint32_t bar, uint32_t parity) {
    uint32_t ok; int guard = 0;
    do {
        asm volatile("{\n.reg .pred P1;\nmbarrier.test_wait.parity.shared::cta.b64 P1, [%1], %2;\nselp.u32 %0,1,0,P1;\n}" : "=r"(ok) : "r"(bar), "r"(parity) : "memory");
    } while (!ok && ++guard < (1 << 26));
}
__device__ __forceinline__ void mbar_wait_sleep(uint32_t bar, uint32_t parity) {
    uint32_t ok; int guard = 0;
    do {
        asm volatile("{\n.reg .pred P1;\nmbarrier.try_wait.parity.shared::cta.b64 P1, [%1], %2;\nselp.u32 %0,1,0,P1;\n}" : "=r"(ok) : "r"(bar), "r"(parity) : "memory");
    } while (!ok && ++guard < (1 << 22));
}
__device__ __forceinline__ uint32_t mapa(uint32_t addr, uint32_t rank) { uint32_t r; asm volatile("mapa.shared::cluster.u32 %0, %1, %2;" : "=r"(r) : "r"(addr), "r"(rank)); return r; }
__device__ __forceinline__ void st_async4(uint32_t addr, float a, float b, float c, float d, uint32_t bar) {
    asm volatile("st.async.weak.shared::cluster.mbarrier::complete_tx::bytes.v4.f32 [%0], {%1,%2,%3,%4}, [%5];" :: "r"(addr), "f"(a), "f"(b), "f"(c), "f"(d), "r"(bar) : "memory");
}
__device__ __forceinline__ void bulk_s2c(uint32_t dst, uint32_t src, uint32_t bytes, uint32_t bar) {
    asm volatile("cp.async.bulk.shared::cluster.shared::cta.mbarrier::complete_tx::bytes [%0], [%1], %2, [%3];" :: "r"(dst), "r"(src), "r"(bytes), "r"(bar) : "memory");
}
__device__ __forceinline__ void bulk_g2s(uint32_t dst, const void* src, uint32_t bytes, uint32_t bar) {
    asm volatile("cp.async.bulk.shared::cluster.global.mbarrier::complete_tx::bytes [%0], [%1], %2, [%3];" :: "r"(dst), "l"(src), "r"(bytes), "r"(bar) : "memory");
}
__device__ __forceinline__ void bulk_s2g(void* dst, uint32_t src, uint32_t bytes) {
    asm volatile("cp.async.bulk.global.shared::cta.bulk_group [%0], [%1], %2;" :: "l"(dst), "r"(src), "r"(bytes) : "memory");
}
__device__ __forceinline__ void bulk_commit() { asm volatile("cp.async.bulk.commit_group;" ::: "memory"); }
__device__ __forceinline__ void bulk_wait_read0() { asm volatile("cp.async.bulk.wait_group.read 0;" ::: "memory"); }
__device__ __forceinline__ void bulk_wait0() { asm volatile("cp.async.bulk.wait_group 0;" ::: "memory"); }
__device__ __forceinline__ void fence_async() { asm volatile("fence.proxy.async.shared::cta;" ::: "memory"); }
__device__ __forceinline__ void nbar_sync(int id, int n) { asm volatile("bar.sync %0, %1;" :: "r"(id), "r"(n) : "memory"); }
__device__ __forceinline__ void nbar_arrive(int id, int n) { asm volatile("bar.arrive %0, %1;" :: "r"(id), "r"(n) : "memory"); }
__device__ __forceinline__ void cp_async16(uint32_t dst, const void* src) { asm volatile("cp.async.cg.shared.global [%0], [%1], 16;" :: "r"(dst), "l"(src) : "memory"); }
__device__ __forceinline__ void cp_async_wait_all() { asm volatile("cp.async.wait_all;" ::: "memory"); }
__device__ __forceinline__ void ldsm4(uint32_t (&r)[4], uint32_t addr) {
    asm volatile("ldmatrix.sync.aligned.m8n8.x4.shared.b16 {%0,%1,%2,%3}, [%4];" : "=r"(r[0]), "=r"(r[1]), "=r"(r[2]), "=r"(r[3]) : "r"(addr) : "memory");
}
__device__ __forceinline__ void ldsm4t(uint32_t (&r)[4], uint32_t addr) {
    asm volatile("ldmatrix.sync.aligned.m8n8.x4.trans.shared.b16 {%0,%1,%2,%3}, [%4];" : "=r"(r[0]), "=r"(r[1]), "=r"(r[2]), "=r"(r[3]) : "r"(addr) : "memory");
}
__device__ __forceinline__ void stsm2t(uint32_t addr, uint32_t r0, uint32_t r1) {
    asm volatile("stmatrix.sync.aligned.m8n8.x2.trans.shared.b16 [%0], {%1,%2};" :: "r"(addr), "r"(r0), "r"(r1) : "memory");
}
__device__ __forceinline__ uint4 ld_relaxed4(const void* p) { uint4 v; asm volatile("ld.relaxed.gpu.global.v4.u32 {%0,%1,%2,%3}, [%4];" : "=r"(v.x), "=r"(v.y), "=r"(v.z), "=r"(v.w) : "l"(p) : "memory"); return v; }
__device__ __forceinline__ void st_relaxed2(void* p, uint32_t a, uint32_t b) { asm volatile("st.relaxed.gpu.global.v2.u32 [%0], {%1,%2};" :: "l"(p), "r"(a), "r"(b) : "memory"); }
__device__ __forceinline__ void st_relaxed1(void* p, uint32_t a) { asm volatile("st.relaxed.gpu.global.u32 [%0], %1;" :: "l"(p), "r"(a) : "memory"); }
__device__ __forceinline__ unsigned ld_acquire(const unsigned* p) { unsigned v; asm volatile("ld.acquire.gpu.global.u32 %0, [%1];" : "=r"(v) : "l"(p) : "memory"); return v; }
__device__ __forceinline__ float ex2_approx(float x) { float r; asm("ex2.approx.ftz.f32 %0, %1;" : "=f"(r) : "f"(x)); return r; }
__device__ __forceinline__ uint64_t make_desc(uint32_t saddr, uint32_t lbo, uint32_t sbo) {
    return (uint64_t)((saddr & 0x3FFFF) >> 4) | ((uint64_t)((lbo & 0x3FFFF) >> 4) << 16) | ((uint64_t)((sbo & 0x3FFFF) >> 4) << 32) | (1ull << 62);
}
__device__ __forceinline__ void wg_fence() { asm volatile("wgmma.fence.sync.aligned;" ::: "memory"); }
__device__ __forceinline__ void wg_commit() { asm volatile("wgmma.commit_group.sync.aligned;" ::: "memory"); }
__device__ __forceinline__ void wg_wait0() { asm volatile("wgmma.wait_group.sync.aligned 0;" ::: "memory"); }
__device__ __forceinline__ void wgmma_n40_tA(float (&d)[20], uint64_t da, uint64_t db, int scale_d) {
    asm volatile("{\n.reg .pred p;\nsetp.ne.b32 p, %22, 0;\n"
        "wgmma.mma_async.sync.aligned.m64n40k16.f32.bf16.bf16 {%0,%1,%2,%3,%4,%5,%6,%7,%8,%9,%10,%11,%12,%13,%14,%15,%16,%17,%18,%19}, %20, %21, p, 1, 1, 1, 0;\n}\n"
        : "+f"(d[0]), "+f"(d[1]), "+f"(d[2]), "+f"(d[3]), "+f"(d[4]), "+f"(d[5]), "+f"(d[6]), "+f"(d[7]), "+f"(d[8]), "+f"(d[9]),
          "+f"(d[10]), "+f"(d[11]), "+f"(d[12]), "+f"(d[13]), "+f"(d[14]), "+f"(d[15]), "+f"(d[16]), "+f"(d[17]), "+f"(d[18]), "+f"(d[19])
        : "l"(da), "l"(db), "r"(scale_d));
}

#define NREP 8
#define NRED 80
#define CAL_THR 410u
#define COMM_REGS "40"
#define NPOOL 576
#define RPS 1
__device__ __align__(4096) uint32_t g_pool[(NPOOL + 1) * 1024];
__device__ unsigned g_cls[NPOOL];
__device__ unsigned g_side[96];
__device__ unsigned g_calcnt;
__device__ unsigned g_epoch;
__device__ unsigned g_flag[NSEG][NH];
__device__ __align__(1024) bf16 g_Qimg[NSEG * NH * 2 * 32 * 64];
__device__ __align__(1024) bf16 g_Kimg[NSEG * NH * 2 * 40 * 64];
__device__ __align__(1024) bf16 g_Vimg[NSEG * NH * 2 * 40 * 64];

#define SM_XB    0
#define SM_VT    81920
#define SM_KT    (SM_VT + 20480)
#define SM_QT    (SM_KT + 10240)
#define SM_QS    (SM_QT + 4096)
#define SM_MEMB  (SM_QS + 1024)
#define SM_RED   (SM_MEMB + 10240)
#define SM_SC    (SM_RED + 16384)
#define SM_CRED  (SM_SC + 5120)
#define SM_PB    (SM_CRED + 1024)
#define SM_TRACE (SM_PB + 1024)
#define SM_WO    163840
#define SM_BAR   (SM_WO + 65536)
#define SM_TPM   (SM_BAR + 256)
#define SM_TRD   (SM_TPM + 256)
#define SM_TPUB  (SM_TRD + 16)
#define SM_TGAT  (SM_TPUB + 128)
#define SM_CAL   (SM_TGAT + 64)
#define SM_TOTAL (SM_CAL + 128)
#define B_SC   (SM_BAR + 0)
#define B_V    (SM_BAR + 16)
#define B_MEM  (SM_BAR + 32)
#define B_P    (SM_BAR + 48)
#define B_X    (SM_BAR + 56)
#define B_EXP  (SM_BAR + 72)

#define TR(ev) do {} while (0)
__device__ __forceinline__ uint32_t tag_of(int s) { return (uint32_t)(((s >> 1) & 1) + 1); }
__device__ __forceinline__ unsigned probe_latency(uint32_t* p, uint32_t zero) {
    uint32_t v, best = 0xffffffffu;
    asm volatile("atom.relaxed.gpu.global.add.u32 %0, [%1], 0;" : "=r"(v) : "l"(p) : "memory");
    #pragma unroll 1
    for (int r = 0; r < 4; r++) {
        uint32_t c0, c1;
        asm volatile("mov.u32 %0, %%clock;" : "=r"(c0) : "r"(v) : "memory");
        asm volatile("atom.relaxed.gpu.global.add.u32 %0, [%1], 0;" : "=r"(v) : "l"(p + ((v + c0) & zero)) : "memory");
        asm volatile("{\n.reg .u32 t;\nand.b32 t, %1, %2;\nmov.u32 %0, %%clock;\nadd.u32 %0, %0, t;\n}" : "=r"(c1) : "r"(v), "r"(zero) : "memory");
        best = min(best, c1 - c0);
    }
    return best;
}
__device__ __forceinline__ void cluster_sync_all() { asm volatile("barrier.cluster.arrive.release.aligned;\nbarrier.cluster.wait.acquire.aligned;" ::: "memory"); }
__device__ __forceinline__ void tma_load_2d(uint32_t dst, const void* map, int c0, int c1, uint32_t bar) {
    asm volatile("cp.async.bulk.tensor.2d.shared::cluster.global.mbarrier::complete_tx::bytes [%0], [%1, {%3, %4}], [%2];"
        :: "r"(dst), "l"(map), "r"(bar), "r"(c0), "r"(c1) : "memory");
}
__device__ __forceinline__ void tma_load_3d(uint32_t dst, const void* map, int c0, int c1, int c2, uint32_t bar) {
    asm volatile("cp.async.bulk.tensor.3d.shared::cluster.global.mbarrier::complete_tx::bytes [%0], [%1, {%3, %4, %5}], [%2];"
        :: "r"(dst), "l"(map), "r"(bar), "r"(c0), "r"(c1), "r"(c2) : "memory");
}
__device__ __forceinline__ void stsm4t(uint32_t addr, uint32_t r0, uint32_t r1, uint32_t r2, uint32_t r3) {
    asm volatile("stmatrix.sync.aligned.m8n8.x4.trans.shared.b16 [%0], {%1,%2,%3,%4};" :: "r"(addr), "r"(r0), "r"(r1), "r"(r2), "r"(r3) : "memory");
}
__device__ __forceinline__ void wgmma_n32_rs(float (&d)[16], const uint32_t (&a)[4], uint64_t db, int scale_d) {
    asm volatile("{\n.reg .pred p;\nsetp.ne.b32 p, %21, 0;\n"
        "wgmma.mma_async.sync.aligned.m64n32k16.f32.bf16.bf16 {%0,%1,%2,%3,%4,%5,%6,%7,%8,%9,%10,%11,%12,%13,%14,%15}, {%16,%17,%18,%19}, %20, p, 1, 1, 0;\n}\n"
        : "+f"(d[0]), "+f"(d[1]), "+f"(d[2]), "+f"(d[3]), "+f"(d[4]), "+f"(d[5]), "+f"(d[6]), "+f"(d[7]),
          "+f"(d[8]), "+f"(d[9]), "+f"(d[10]), "+f"(d[11]), "+f"(d[12]), "+f"(d[13]), "+f"(d[14]), "+f"(d[15])
        : "r"(a[0]), "r"(a[1]), "r"(a[2]), "r"(a[3]), "l"(db), "r"(scale_d));
}

__device__ __forceinline__ void st_async4u(uint32_t addr, uint4 v, uint32_t bar) {
    asm volatile("st.async.weak.shared::cluster.mbarrier::complete_tx::bytes.v4.u32 [%0], {%1,%2,%3,%4}, [%5];" :: "r"(addr), "r"(v.x), "r"(v.y), "r"(v.z), "r"(v.w), "r"(bar) : "memory");
}
__device__ __forceinline__ void export_issue(uint32_t sb, int s, int h, uint32_t rank) {
    const size_t img = (size_t)(s * NH + h) * 2;
    const int sl = s & 1;
    if (rank == 2) {
        bulk_s2g(g_Vimg + img * 2560, sb + SM_VT + sl * 10240, 5120);
        bulk_s2g(g_Vimg + (img + 1) * 2560, sb + SM_VT + sl * 10240 + 5120, 5120);
    } else {
        bulk_s2g(g_Qimg + (img + rank) * 2048, sb + SM_QT, 4096);
        bulk_s2g(g_Kimg + (img + rank) * 2560, sb + SM_KT + sl * 5120, 5120);
    }
    bulk_commit();
    bulk_wait_read0();
    mbar_arrive(sb + B_EXP);
}
__device__ __forceinline__ void export_signal(int s, int h) {
    bulk_wait0();
    asm volatile("fence.proxy.async;" ::: "memory");
    __threadfence();
    atomicAdd(&g_flag[s][h], 1u);
}

__device__ __forceinline__ void score_tile(uint32_t sb, int sl, int nt, int lane, uint32_t rank) {
    float sc[4] = {0, 0, 0, 0}, sd[4] = {0, 0, 0, 0};
    const int r = lane & 7;
    uint32_t qa[2][4], kb[2][4];
    #pragma unroll
    for (int j = 0; j < 2; j++) {
        const int chunk = (lane >> 3) + 4 * j;
        ldsm4(kb[j], sb + SM_KT + sl * 5120 + (8 * nt + r) * 128 + ((chunk ^ r) << 4));
        ldsm4(qa[j], sb + SM_QS + r * 128 + ((chunk ^ r) << 4));
    }
    mma_bf16(sc, qa[0][0], 0u, qa[0][1], 0u, kb[0][0], kb[0][1]);
    mma_bf16(sd, qa[1][0], 0u, qa[1][1], 0u, kb[1][0], kb[1][1]);
    mma_bf16(sc, qa[0][2], 0u, qa[0][3], 0u, kb[0][2], kb[0][3]);
    mma_bf16(sd, qa[1][2], 0u, qa[1][3], 0u, kb[1][2], kb[1][3]);
    sc[0] += sd[0]; sc[1] += sd[1];
    const float o0 = __shfl_down_sync(~0u, sc[0], 1), o1 = __shfl_down_sync(~0u, sc[1], 1);
    if ((lane & 1) == 0) {
        const uint32_t a = SM_SC + sl * 2560 + rank * 1280 + ((lane >> 2) * 40 + 8 * nt + 2 * (lane & 3)) * 4;
        const uint32_t bo = B_SC + 8 * sl;
        { const uint32_t rb = mapa(sb, 2); st_async4(rb + a, sc[0], sc[1], o0, o1, rb + bo); }
        { const uint32_t rb = mapa(sb, rank ^ 1); st_async4(rb + a, sc[0], sc[1], o0, o1, rb + bo); }
        asm volatile("st.shared.v4.f32 [%0], {%1,%2,%3,%4};" :: "r"(sb + a), "f"(sc[0]), "f"(sc[1]), "f"(o0), "f"(o1) : "memory");
    }
    __syncwarp();
    if (lane == 0) mbar_arrive(sb + B_SC + 8 * sl);
}
__device__ __forceinline__ void wgmma_n40_rs(float (&d)[20], const uint32_t (&a)[4], uint64_t db, int scale_d) {
    asm volatile("{\n.reg .pred p;\nsetp.ne.b32 p, %25, 0;\n"
        "wgmma.mma_async.sync.aligned.m64n40k16.f32.bf16.bf16 {%0,%1,%2,%3,%4,%5,%6,%7,%8,%9,%10,%11,%12,%13,%14,%15,%16,%17,%18,%19}, {%20,%21,%22,%23}, %24, p, 1, 1, 0;\n}\n"
        : "+f"(d[0]), "+f"(d[1]), "+f"(d[2]), "+f"(d[3]), "+f"(d[4]), "+f"(d[5]), "+f"(d[6]), "+f"(d[7]), "+f"(d[8]), "+f"(d[9]),
          "+f"(d[10]), "+f"(d[11]), "+f"(d[12]), "+f"(d[13]), "+f"(d[14]), "+f"(d[15]), "+f"(d[16]), "+f"(d[17]), "+f"(d[18]), "+f"(d[19])
        : "r"(a[0]), "r"(a[1]), "r"(a[2]), "r"(a[3]), "l"(db), "r"(scale_d));
}
__device__ __forceinline__ void pu_mma(float (&o)[4], const float (&u)[20], const uint32_t (&pb)[5]) {
    float o2[4] = {0, 0, 0, 0};
    o[0] = o[1] = o[2] = o[3] = 0.f;
    mma_bf16(o, pack_bf16(u[0], u[1]), pack_bf16(u[2], u[3]), pack_bf16(u[4], u[5]), pack_bf16(u[6], u[7]), pb[0], pb[1]);
    mma_bf16(o2, pack_bf16(u[8], u[9]), pack_bf16(u[10], u[11]), pack_bf16(u[12], u[13]), pack_bf16(u[14], u[15]), pb[2], pb[3]);
    mma_bf16(o, pack_bf16(u[16], u[17]), pack_bf16(u[18], u[19]), 0u, 0u, pb[4], 0u);
    o[0] += o2[0]; o[1] += o2[1]; o[2] += o2[2]; o[3] += o2[3];
}
__device__ __forceinline__ void pu_store(const float (&o)[4], float2 inv, uint2 off, int lane, uint32_t tg) {
    unsigned char* pool = reinterpret_cast<unsigned char*>(g_pool) + lane * 8;
    st_relaxed2(pool + off.x, (__float_as_uint(o[0] * inv.x) & ~3u) | tg, (__float_as_uint(o[1] * inv.y) & ~3u) | tg);
    st_relaxed2(pool + off.y, (__float_as_uint(o[2] * inv.x) & ~3u) | tg, (__float_as_uint(o[3] * inv.y) & ~3u) | tg);
}
__device__ __forceinline__ float rcp_approx(float x) { float r; asm("rcp.approx.ftz.f32 %0, %1;" : "=f"(r) : "f"(x)); return r; }
template <int NT>
__device__ __forceinline__ void u_pass(unsigned char* smem, uint32_t sb, int s, uint32_t rank, int wg, int warp, int lane) {
    const int sl = s & 1;
#define NRS_V 6
    constexpr int NRS = NRS_V;
    uint32_t wa[NRS][4];
    {
        const int mi = lane >> 3, chunk = 2 * warp + (mi & 1);
        #pragma unroll
        for (int ks = 0; ks < NRS; ks++) {
            const int row = 16 * ks + (mi >> 1) * 8 + (lane & 7);
            ldsm4t(wa[ks], sb + SM_WO + (2 * wg) * 16384 + row * 128 + ((chunk ^ (row & 7)) << 4));
        }
    }
    if (rank < 2) { mbar_wait(sb + B_V + 8 * sl, (s >> 1) & 1); fence_async(); }
    if (wg == 0 && warp == 0) TR(4);
    float U0[20];
    wg_fence();
    #pragma unroll
    for (int ks = 0; ks < NRS; ks++)
        wgmma_n40_rs(U0, wa[ks], make_desc(sb + SM_VT + sl * 10240 + (ks >> 2) * 5120 + (ks & 3) * 32, 16, 1024), ks > 0);
    #pragma unroll
    for (int ks = NRS; ks < 8; ks++)
        wgmma_n40_tA(U0, make_desc(sb + SM_WO + (2 * wg) * 16384 + ks * 2048, 1024, 1024),
                     make_desc(sb + SM_VT + sl * 10240 + (ks >> 2) * 5120 + (ks & 3) * 32, 16, 1024), 1);
    wg_commit();
    const uint32_t tg = tag_of(s);
    uint32_t pb[5];
    float sm[4], sm2[4];
    auto get_p = [&]() {
        nbar_sync(9, 288);
        const uint32_t* pbs = reinterpret_cast<const uint32_t*>(smem + SM_PB);
        #pragma unroll
        for (int q = 0; q < 5; q++) pb[q] = pbs[q * 32 + lane];
        sm[0] = sm[1] = sm[2] = sm[3] = 0.f; sm2[0] = sm2[1] = sm2[2] = sm2[3] = 0.f;
        const uint32_t one = 0x3f803f80u;
        mma_bf16(sm, one, one, one, one, pb[0], pb[1]);
        mma_bf16(sm2, one, one, one, one, pb[2], pb[3]);
        mma_bf16(sm, one, one, 0u, 0u, pb[4], 0u);
    };
    const uint2* tpm = reinterpret_cast<const uint2*>(smem + SM_TPM) + (sl * 4 + 2 * wg) * 4 + warp;
    if (NT == 2) {
        wg_wait0();
        float U1[20];
        wg_fence();
        #pragma unroll
        for (int ks = 0; ks < 8; ks++)
            wgmma_n40_tA(U1, make_desc(sb + SM_WO + (2 * wg + 1) * 16384 + ks * 2048, 1024, 1024),
                         make_desc(sb + SM_VT + sl * 10240 + (ks >> 2) * 5120 + (ks & 3) * 32, 16, 1024), ks > 0);
        wg_commit();
        const uint2 off0 = tpm[0], off1 = tpm[4];
        get_p();
        float o0[4], o1[4];
        pu_mma(o0, U0, pb);
        wg_wait0();
        pu_mma(o1, U1, pb);
        const float2 inv = make_float2(rcp_approx(sm[0] + sm2[0]), rcp_approx(sm[1] + sm2[1]));
        if (wg == 0 && warp == 0) TR(8);
        pu_store(o0, inv, off0, lane, tg);
        pu_store(o1, inv, off1, lane, tg);
        if (wg == 0 && warp == 0) TR(6);
    } else {
        const uint2 off0 = tpm[0];
        wg_wait0();
        get_p();
        float o0[4];
        pu_mma(o0, U0, pb);
        const float2 inv = make_float2(rcp_approx(sm[0] + sm2[0]), rcp_approx(sm[1] + sm2[1]));
        pu_store(o0, inv, off0, lane, tg);
    }
}

__global__ void __cluster_dims__(3, 1, 1) __launch_bounds__(384, 1)
k_chain(const __grid_constant__ CUtensorMap xmap, const __grid_constant__ CUtensorMap wqmap, const __grid_constant__ CUtensorMap wkmap,
        const __grid_constant__ CUtensorMap wvmap, const __grid_constant__ CUtensorMap womap, const bf16* __restrict__ xptr, const bf16* __restrict__ mem0) {
    extern __shared__ __align__(1024) unsigned char smem[];
    const uint32_t sb = smem_u32(smem);
    const int tid = threadIdx.x, lane = tid & 31;
    const int wg = __shfl_sync(~0u, tid >> 7, 0), warp = __shfl_sync(~0u, (tid >> 5) & 3, 0);
    uint32_t rank; asm volatile("mov.u32 %0, %%cluster_ctarank;" : "=r"(rank));
    const int cta = blockIdx.x, h = cta / 3;
    asm volatile("griddepcontrol.launch_dependents;");
    if (tid == 0) {
        for (int i = 0; i < 2; i++) { mbar_init(sb + B_SC + 8 * i, rank < 2 ? 6 : 1); mbar_init(sb + B_V + 8 * i, 1); mbar_init(sb + B_MEM + 8 * i, 64); mbar_init(sb + B_X + 8 * i, 1); }
        mbar_init(sb + B_P, 1); mbar_init(sb + B_EXP, 1);
        asm volatile("fence.mbarrier_init.release.cluster;" ::: "memory");
    }
    if (tid < 80) asm volatile("prefetch.global.L2 [%0];" :: "l"(mem0 + tid * 64));
    if (h < 2) { for (int i = tid; i < 320; i += 384) asm volatile("prefetch.global.L2 [%0];" :: "l"(xptr + (size_t)h * 32 * DM + i * 64)); }
    {
        const int w12 = tid >> 5;
        if (lane == 0 && w12 < 7) {
            uint32_t* pp = (w12 < 6) ? g_pool + (size_t)(cta * 6 + w12) * 1024 + 512 : g_pool + (size_t)NPOOL * 1024 + (cta & 31) * 32 + (cta >> 5) * 8;
            const unsigned lat = probe_latency(pp, blockIdx.y);
            if (w12 < 6) g_cls[cta * 6 + w12] = lat > CAL_THR ? 1u : 0u; else g_side[cta] = lat > CAL_THR ? 1u : 0u;
        }
        __syncwarp();
        uint4* z = reinterpret_cast<uint4*>(g_pool + (size_t)cta * 6 * 1024);
        #pragma unroll
        for (int q = 0; q < 4; q++) z[tid + 384 * q] = make_uint4(0, 0, 0, 0);
        __threadfence();
        __syncwarp();
        if (lane == 0) atomicAdd(&g_calcnt, 1u);
    }
    __syncthreads();
    if (tid == 0) {
        const int ntile = (rank == 2) ? 4 : 3;
        const int tile0 = (rank == 2) ? 0 : (rank == 0 ? 4 : 7);
        mbar_expect_tx(sb + B_P, 163840 + ntile * 16384);
        const void* m0 = (rank == 2) ? &wvmap : &wqmap;
        const void* m1 = (rank == 2) ? &wvmap : &wkmap;
        const int c0 = h * DH + (rank == 1 ? 64 : 0), c1 = h * DH + (rank == 0 ? 0 : 64);
        for (int b = 0; b < 5; b++) {
            tma_load_2d(sb + b * 16384, m0, c0, b * 128, sb + B_P);
            tma_load_2d(sb + 81920 + b * 16384, m1, c1, b * 128, sb + B_P);
        }
        for (int lt = 0; lt < ntile; lt++) {
            tma_load_2d(sb + SM_WO + lt * 16384, &womap, (tile0 + lt) * 64, h * DH, sb + B_P);
            tma_load_2d(sb + SM_WO + lt * 16384 + 8192, &womap, (tile0 + lt) * 64, h * DH + 64, sb + B_P);
        }
    }
    {
        const int tile0 = (rank == 2) ? 0 : (rank == 0 ? 4 : 7);
        if (wg == 2) {
            const int ct = tid & 127;
            if (ct == 0) {
                const unsigned target = (*reinterpret_cast<volatile unsigned*>(&g_epoch) + 1u) * (96u * 12u);
                int guard = 0;
                while ((int)(ld_acquire(&g_calcnt) - target) < 0 && ++guard < (1 << 22)) {}
            }
            nbar_sync(4, 128);
            uint32_t* bm = reinterpret_cast<uint32_t*>(smem + SM_CAL);
            {
                unsigned v[5];
                #pragma unroll
                for (int q = 0; q < 5; q++) { const int b = ct + 128 * q; v[q] = (b < NPOOL) ? (__ldcg(&g_cls[b]) ^ __ldcg(&g_side[b / 6])) : 0u; }
                const unsigned sv = (ct < 96) ? __ldcg(&g_side[ct]) : 0u;
                #pragma unroll
                for (int q = 0; q < 5; q++) { const unsigned m = __ballot_sync(~0u, v[q] & 1u); if (lane == 0 && q * 4 + warp < 18) bm[q * 4 + warp] = m; }
                const unsigned m = __ballot_sync(~0u, sv & 1u);
                if (lane == 0 && warp < 3) bm[18 + warp] = m;
            }
            nbar_sync(4, 128);
            int nblk1 = 0;
            for (int i = 0; i < 18; i++) nblk1 += __popc(bm[i]);
            const unsigned red_last = (1u << (NRED - 64)) - 1u;
            const int nred1 = __popc(bm[18]) + __popc(bm[19]) + __popc(bm[20] & red_last);
            auto side_of = [&](int c) -> int { return (bm[18 + (c >> 5)] >> (c & 31)) & 1; };
            auto rank_of = [&](int c) -> int {
                int ones = 0;
                for (int i = 0; i < (c >> 5); i++) ones += __popc(bm[18 + i]);
                ones += __popc(bm[18 + (c >> 5)] & ((1u << (c & 31)) - 1u));
                return side_of(c) ? ones : c - ones;
            };
            auto nth = [&](int side, int idx) -> uint32_t {
                for (int i = 0; i < 18; i++) {
                    const unsigned m = side ? bm[i] : ~bm[i];
                    const int n = __popc(m);
                    if (idx < n) return (uint32_t)(i * 32 + __fns(m, 0, idx + 1));
                    idx -= n;
                }
                return 0u;
            };
            auto phys = [&](int side, int idx) -> uint32_t {
                const int c = side ? nblk1 : NPOOL - nblk1;
                return (idx < c) ? nth(side, idx) : nth(side ^ 1, (NPOOL - c) - 1 - (idx - c));
            };
            const int e = ct;
            if (e < 64) {
                const int slot = e >> 5, lt = (e >> 3) & 3, w = (e >> 1) & 3, hf = e & 1;
                const int tile = min(tile0 + lt, 9);
                const int r = 2 * (4 * tile + w) + hf;
                reinterpret_cast<uint32_t*>(smem + SM_TPM)[e] = phys(side_of(r), 4 * rank_of(r) + slot * 2 + (h >> 4)) * 4096u + (h & 15) * 256u;
            } else if (e < 68) {
                const int i = e - 64;
                reinterpret_cast<uint32_t*>(smem + SM_TRD)[i] = (cta < NRED) ? phys(side_of(cta), 4 * rank_of(cta) + i) * 4096u : 0u;
            } else if (e < 100) {
                const int i = e - 68, slot = i >> 3, rep = i & 7, side = (rep / RPS) & 1;
                reinterpret_cast<uint32_t*>(smem + SM_TPUB)[i] = phys(side, 4 * (side ? nred1 : NRED - nred1) + (slot * RPS + (rep % RPS)) * 3 + (cta >> 5)) * 4096u + (cta & 31) * 128u;
            } else if (e < 112) {
                const int i = e - 100, slot = i / 3, b = i % 3, side = side_of(cta);
                reinterpret_cast<uint32_t*>(smem + SM_TGAT)[slot * 4 + b] = phys(side, 4 * (side ? nred1 : NRED - nred1) + (slot * RPS + (h % RPS)) * 3 + b) * 4096u;
            }
        }
    }
    __syncthreads();
    mbar_wait_sleep(sb + B_P, 0);

    if (wg == 2) {
        asm volatile("setmaxnreg.dec.sync.aligned.u32 " COMM_REGS ";");
        const int ct = tid & 127;
        nbar_sync(5, 384);
        for (int c = ct; c < 640; c += 128) {
            int ks = c >> 4, hf = (c >> 3) & 1, r = c & 7;
            *reinterpret_cast<uint4*>(smem + SM_MEMB + c * 16) = *reinterpret_cast<const uint4*>(mem0 + r * DM + ks * 16 + hf * 8);
        }
        if (ct == 0) {
            for (int sg = 0; sg < 2; sg++) {
                mbar_expect_tx(sb + B_X + 8 * sg, 40960);
                tma_load_3d(sb + SM_XB + sg * 40960, &xmap, 0, sg * 32, 0, sb + B_X + 8 * sg);
            }
            mbar_expect_tx(sb + B_SC, rank < 2 ? 1280 : 2560);
            if (rank < 2) mbar_expect_tx(sb + B_V, 8192 + 2048);
        }
        nbar_sync(5, 384);
        cluster_sync_all();
        unsigned char* const pool = reinterpret_cast<unsigned char*>(g_pool);
        for (int s = 0; s < NSEG - 1; s++) {
            if (warp == 1) nbar_sync(12, 288);
            if (warp == 0) {
                const int g = lane >> 2, t = lane & 3;
                mbar_wait(sb + B_SC + 8 * (s & 1), (s >> 1) & 1);
                TR(5);
                const uint32_t sa = sb + SM_SC + (s & 1) * 2560 + (g * 40 + 2 * t) * 4;
                float v[5][2], u[5][2];
                #pragma unroll
                for (int q = 0; q < 5; q++) {
                    asm volatile("ld.shared.v2.f32 {%0,%1}, [%2];" : "=f"(v[q][0]), "=f"(v[q][1]) : "r"(sa + 32 * q) : "memory");
                    asm volatile("ld.shared.v2.f32 {%0,%1}, [%2];" : "=f"(u[q][0]), "=f"(u[q][1]) : "r"(sa + 1280 + 32 * q) : "memory");
                }
                float mx = -3.0e38f;
                #pragma unroll
                for (int q = 0; q < 5; q++) {
                    v[q][0] += u[q][0]; v[q][1] += u[q][1];
                    mx = fmaxf(mx, fmaxf(v[q][0], v[q][1]));
                }
                mx = fmaxf(mx, __shfl_xor_sync(~0u, mx, 1));
                mx = fmaxf(mx, __shfl_xor_sync(~0u, mx, 2));
                const float sc2 = 0.08838834764831845f * 1.4426950408889634f;
                const float mxs = mx * sc2;
                uint32_t* pbs = reinterpret_cast<uint32_t*>(smem + SM_PB);
                #pragma unroll
                for (int q = 0; q < 5; q++) {
                    const float e0 = ex2_approx(fmaf(v[q][0], sc2, -mxs)), e1 = ex2_approx(fmaf(v[q][1], sc2, -mxs));
                    pbs[q * 32 + lane] = pack_bf16(e0, e1);
                }
                __syncwarp();
                TR(0);
                nbar_arrive(9, 288);
            } else if (warp == 1 && lane == 0) {
                if (s + 1 < NSEG - 1) {
                    mbar_expect_tx(sb + B_SC + 8 * ((s + 1) & 1), rank < 2 ? 1280 : 2560);
                    if (rank < 2) mbar_expect_tx(sb + B_V + 8 * ((s + 1) & 1), 8192 + 2048);
                }
                if (s + 2 < NSEG) {
                    mbar_expect_tx(sb + B_X + 8 * (s & 1), 40960);
                    tma_load_3d(sb + SM_XB + (s & 1) * 40960, &xmap, 0, (s + 2) * 32, 0, sb + B_X + 8 * (s & 1));
                }
                export_issue(sb, s, h, rank);
                if (s >= NSEG - 4) export_signal(s, h);
            }
            __syncwarp();
            nbar_sync(3, 384);
            const uint32_t tg = tag_of(s);
            if (cta < NRED) {
                const unsigned char* base = pool + reinterpret_cast<const uint32_t*>(smem + SM_TRD)[(s & 1) * 2 + (warp >> 1)] + (warp & 1) * 2048 + lane * 16;
                uint4 v[4]; int guard = 0;
                #pragma unroll
                for (int j = 0; j < 4; j++) v[j] = make_uint4(0, 0, 0, 0);
                uint32_t pend = 0xF;
                do {
                    #pragma unroll
                    for (int j = 0; j < 4; j++) if (pend & (1u << j)) v[j] = ld_relaxed4(base + j * 512);
                    #pragma unroll
                    for (int j = 0; j < 4; j++)
                        if (((v[j].x & 3) == tg) && ((v[j].y & 3) == tg) && ((v[j].z & 3) == tg) && ((v[j].w & 3) == tg)) pend &= ~(1u << j);
                } while (__any_sync(~0u, pend != 0) && ++guard < (1 << 20));
                if (warp == 0) TR(9);
                float a0 = 0, a1 = 0, a2 = 0, a3 = 0;
                #pragma unroll
                for (int j = 0; j < 4; j++) { a0 += __uint_as_float(v[j].x); a1 += __uint_as_float(v[j].y); a2 += __uint_as_float(v[j].z); a3 += __uint_as_float(v[j].w); }
                a0 += __shfl_xor_sync(~0u, a0, 16); a1 += __shfl_xor_sync(~0u, a1, 16); a2 += __shfl_xor_sync(~0u, a2, 16); a3 += __shfl_xor_sync(~0u, a3, 16);
                float* cr = reinterpret_cast<float*>(smem + SM_CRED);
                if (lane < 16) *reinterpret_cast<float4*>(cr + warp * 64 + lane * 4) = make_float4(a0, a1, a2, a3);
                nbar_sync(4, 128);
                {
                    int rho = lane >> 2, pp = lane & 3;
                    int i0 = ((2 * pp) * 4 + (rho >> 1)) * 2 + (rho & 1), i1 = i0 + 8;
                    uint32_t wv = pack_bf16((cr[i0] + cr[64 + i0]) + (cr[128 + i0] + cr[192 + i0]), (cr[i1] + cr[64 + i1]) + (cr[128 + i1] + cr[192 + i1]));
                    if (wv == 0) wv = 0x8000u;
                    if (warp == 0) TR(10);
                    const uint32_t* tp = reinterpret_cast<const uint32_t*>(smem + SM_TPUB) + warp;
                    if (warp < 2 * RPS) st_relaxed1(pool + tp[((s + 1) & 3) * 8] + lane * 4, wv);
                    if (RPS == 4) st_relaxed1(pool + tp[((s + 1) & 3) * 8 + 4] + lane * 4, wv);
                    if (warp < 2 * RPS) st_relaxed1(pool + tp[(s & 3) * 8] + lane * 4, 0u);
                    if (RPS == 4) st_relaxed1(pool + tp[(s & 3) * 8 + 4] + lane * 4, 0u);
                }
            }
            {
                const int c0 = warp * 160 + lane;
                const uint32_t* tg3 = reinterpret_cast<const uint32_t*>(smem + SM_TGAT) + ((s + 1) & 3) * 4;
                const uint32_t g0 = tg3[0], g1 = tg3[1], g2 = tg3[2];
                uint4 v[5]; int guard = 0;
                #pragma unroll
                for (int j = 0; j < 5; j++) v[j] = make_uint4(0, 0, 0, 0);
                uint32_t pend = 0x1F;
                do {
                    #pragma unroll
                    for (int j = 0; j < 5; j++) {
                        const int c = c0 + 32 * j;
                        if (pend & (1u << j)) v[j] = ld_relaxed4(pool + ((c >> 8) == 0 ? g0 : ((c >> 8) == 1 ? g1 : g2)) + (c & 255) * 16);
                    }
                    #pragma unroll
                    for (int j = 0; j < 5; j++) if (v[j].x && v[j].y && v[j].z && v[j].w) pend &= ~(1u << j);
                } while (__any_sync(~0u, pend != 0) && ++guard < (1 << 20));
                #pragma unroll
                for (int j = 0; j < 5; j++) *reinterpret_cast<uint4*>(smem + SM_MEMB + (c0 + 32 * j) * 16) = v[j];
                if (warp == 0) TR(11);
                if (warp == 3) TR(12);
                nbar_arrive(warp < 2 ? 7 + warp : 8 + warp, 160);
            }
            if (warp == 1 && lane == 0 && s < NSEG - 4) export_signal(s, h);
            __syncwarp();
        }
        if (warp == 1) { nbar_sync(12, 288); if (lane == 0) { export_issue(sb, NSEG - 1, h, rank); export_signal(NSEG - 1, h); } }
        __syncwarp();
        nbar_sync(3, 384);
        __syncwarp();
        cluster_sync_all();
    } else {
        asm volatile("setmaxnreg.inc.sync.aligned.u32 232;");
        const int wtid = tid & 127;
        const int cw = wg * 4 + warp;
        uint32_t areg[2][20][4];
        #pragma unroll
        for (int mt = 0; mt < 2; mt++)
            #pragma unroll
            for (int kk = 0; kk < 20; kk++) {
                int mi = lane >> 3;
                int row = 16 * (20 * wg + kk) + (mi >> 1) * 8 + (lane & 7);
                int chunk = 2 * warp + (mi & 1);
                ldsm4t(areg[mt][kk], sb + mt * 81920 + row * 128 + ((chunk ^ (row & 7)) << 4));
            }
        nbar_sync(5, 384);
        nbar_sync(5, 384);
        cluster_sync_all();

        for (int s = -1; s < NSEG; s++) {
            const int sl = s & 1;
            if (s >= 0) {
            if (s > 0) nbar_sync(7 + 3 * wg, 160);
            float fin[4];
            {
                float acc[2][2][4];
                #pragma unroll
                for (int i = 0; i < 2; i++)
                    #pragma unroll
                    for (int j = 0; j < 2; j++) { acc[i][j][0] = acc[i][j][1] = acc[i][j][2] = acc[i][j][3] = 0.f; }
                uint32_t b[3][4];
                const uint32_t mb = sb + SM_MEMB + (20 * wg) * 256 + lane * 16;
                ldsm4(b[0], mb); ldsm4(b[1], mb + 512);
                #pragma unroll
                for (int kp = 0; kp < 10; kp++) {
                    if (kp == 3 && s > 0) nbar_sync(8 + 3 * wg, 160);
                    if (kp + 2 < 10) ldsm4(b[(kp + 2) % 3], mb + (kp + 2) * 512);
                    const uint32_t (&bb)[4] = b[kp % 3];
                    mma_bf16(acc[0][0], areg[0][2 * kp][0], areg[0][2 * kp][1], areg[0][2 * kp][2], areg[0][2 * kp][3], bb[0], bb[1]);
                    mma_bf16(acc[1][0], areg[1][2 * kp][0], areg[1][2 * kp][1], areg[1][2 * kp][2], areg[1][2 * kp][3], bb[0], bb[1]);
                    mma_bf16(acc[0][1], areg[0][2 * kp + 1][0], areg[0][2 * kp + 1][1], areg[0][2 * kp + 1][2], areg[0][2 * kp + 1][3], bb[2], bb[3]);
                    mma_bf16(acc[1][1], areg[1][2 * kp + 1][0], areg[1][2 * kp + 1][1], areg[1][2 * kp + 1][2], areg[1][2 * kp + 1][3], bb[2], bb[3]);
                }
                float4* red = reinterpret_cast<float4*>(smem + SM_RED);
                float m0[4], m1[4];
                #pragma unroll
                for (int i = 0; i < 4; i++) { m0[i] = acc[0][0][i] + acc[0][1][i]; m1[i] = acc[1][0][i] + acc[1][1][i]; }
                red[(wg ^ 1) * 128 + wtid] = wg == 0 ? make_float4(m1[0], m1[1], m1[2], m1[3]) : make_float4(m0[0], m0[1], m0[2], m0[3]);
                nbar_sync(1, 256);
                float4 r = red[wg * 128 + wtid];
                fin[0] = (wg == 0 ? m0[0] : m1[0]) + r.x; fin[1] = (wg == 0 ? m0[1] : m1[1]) + r.y;
                fin[2] = (wg == 0 ? m0[2] : m1[2]) + r.z; fin[3] = (wg == 0 ? m0[3] : m1[3]) + r.w;
            }
            if (cw == 0) TR(1);
            {
                uint32_t p0 = pack_bf16(fin[0], fin[1]), p1 = pack_bf16(fin[2], fin[3]);
                const uint32_t doff = (rank == 2) ? SM_VT + sl * 10240 + wg * 5120 : (wg == 0 ? SM_QS : SM_KT + sl * 5120);
                const int r = lane & 7, chunk = 2 * warp + ((lane >> 3) & 1);
                const uint32_t coff = doff + r * 128 + ((chunk ^ r) << 4);
                stsm2t(sb + coff, p0, p1);
                if (rank == 2 && s < NSEG - 1) {
                    __syncwarp();
                    const uint4 v = *reinterpret_cast<const uint4*>(smem + coff);
                    const uint32_t rb = mapa(sb, lane >> 4);
                    st_async4u(rb + coff, v, rb + B_V + 8 * sl);
                }
            }
            fence_async();
            nbar_sync(1, 256);
            nbar_arrive(12, 288);
            if (cw == 0) TR(2);
            if (rank < 2 && s < NSEG - 1) {
                if (wg == 1) score_tile(sb, sl, 1 + warp, lane, rank);
                else if (warp == 0) score_tile(sb, sl, 0, lane, rank);
            }
            if (s == NSEG - 1) break;
            if (cw == 0) TR(3);
            if (wg == 0 || rank == 2) u_pass<2>(smem, sb, s, rank, wg, warp, lane);
            else                      u_pass<1>(smem, sb, s, rank, wg, warp, lane);
            if (cw == 0) TR(7);
            nbar_arrive(3, 384);
            }
            {
                const int sn = s + 1, sln = sn & 1;
                mbar_wait(sb + B_X + 8 * sln, (sn >> 1) & 1);
                float acc[2][16];
                wg_fence();
                #pragma unroll
                for (int mt = 0; mt < 2; mt++)
                    #pragma unroll
                    for (int kk = 0; kk < 20; kk++) {
                        uint64_t db = make_desc(sb + SM_XB + sln * 40960 + (5 * wg + (kk >> 2)) * 4096 + (kk & 3) * 32, 16, 1024);
                        wgmma_n32_rs(acc[mt], areg[mt][kk], db, kk > 0);
                    }
                wg_commit();
                if (cw == 0 && s >= 0) TR(14);
                wg_wait0();
                if (cw == 0 && s >= 0) TR(15);
                float4* red = reinterpret_cast<float4*>(smem + SM_RED);
                #pragma unroll
                for (int j = 0; j < 4; j++) {
                    red[((wg ^ 1) * 4 + j) * 128 + wtid] = make_float4(wg == 0 ? acc[1][4 * j] : acc[0][4 * j], wg == 0 ? acc[1][4 * j + 1] : acc[0][4 * j + 1],
                                                                       wg == 0 ? acc[1][4 * j + 2] : acc[0][4 * j + 2], wg == 0 ? acc[1][4 * j + 3] : acc[0][4 * j + 3]);
                }
                if (s >= 0) mbar_wait(sb + B_EXP, s & 1);
                nbar_sync(1, 256);
                uint32_t pk[8];
                #pragma unroll
                for (int j = 0; j < 4; j++) {
                    float4 r = red[(wg * 4 + j) * 128 + wtid];
                    pk[2 * j] = pack_bf16((wg == 0 ? acc[0][4 * j] : acc[1][4 * j]) + r.x, (wg == 0 ? acc[0][4 * j + 1] : acc[1][4 * j + 1]) + r.y);
                    pk[2 * j + 1] = pack_bf16((wg == 0 ? acc[0][4 * j + 2] : acc[1][4 * j + 2]) + r.z, (wg == 0 ? acc[0][4 * j + 3] : acc[1][4 * j + 3]) + r.w);
                }
                const uint32_t dst = (rank == 2) ? sb + SM_VT + sln * 10240 + wg * 5120 + 1024 : (wg == 0 ? sb + SM_QT : sb + SM_KT + sln * 5120 + 1024);
                #pragma unroll
                for (int jj = 0; jj < 2; jj++) {
                    int mi = lane >> 3, tok = 8 * (2 * jj + (mi >> 1)) + (lane & 7), chunk = 2 * warp + (mi & 1);
                    stsm4t(dst + tok * 128 + ((chunk ^ (tok & 7)) << 4), pk[4 * jj], pk[4 * jj + 1], pk[4 * jj + 2], pk[4 * jj + 3]);
                }
                fence_async();
                nbar_sync(1, 256);
                if (rank == 2 && lane == 0 && cw < 4 && sn < NSEG - 1) {
                    const uint32_t off = SM_VT + sln * 10240 + (cw & 1) * 5120 + 1024;
                    const uint32_t rb = mapa(sb, cw >> 1);
                    bulk_s2c(rb + off, sb + off, 4096, rb + B_V + 8 * sln);
                }
                if (cw == 0 && s >= 0) TR(13);
            }
        }
        nbar_arrive(3, 384);
        __syncwarp();
        cluster_sync_all();
    }
}

#define NAUX 36
__device__ __align__(1024) bf16 g_Oimg[16 * 64 * 128 * 64];
__device__ float    g_part[4 * SEQ * DM];
__device__ float    g_part31[3 * 13 * 64 * DM];
__device__ unsigned g_ocnt[32];
__device__ unsigned g_gcnt[32][2];
__device__ unsigned g_ssmcnt, g_auxdone, g_taskctr, g_gemmctr;
#define NATT 8
#define ATR(i) do {} while (0)
#define ATRID(i, id) do {} while (0)

__device__ __forceinline__ void wait_counter(const unsigned* p, unsigned target) {
    int guard = 0;
    while ((int)(ld_acquire(p) - target) < 0 && ++guard < (1 << 22)) __nanosleep(64);
}
__device__ __forceinline__ void fence_async_all() { asm volatile("fence.proxy.async;" ::: "memory"); }
template <int OFF>
__device__ __forceinline__ void wgmma_n192_tB(float (&d)[160], uint64_t da, uint64_t db) {
    asm volatile("wgmma.mma_async.sync.aligned.m64n192k16.f32.bf16.bf16 {%0,%1,%2,%3,%4,%5,%6,%7,%8,%9,%10,%11,%12,%13,%14,%15,%16,%17,%18,%19,%20,%21,%22,%23,%24,%25,%26,%27,%28,%29,%30,%31,%32,%33,%34,%35,%36,%37,%38,%39,%40,%41,%42,%43,%44,%45,%46,%47,%48,%49,%50,%51,%52,%53,%54,%55,%56,%57,%58,%59,%60,%61,%62,%63,%64,%65,%66,%67,%68,%69,%70,%71,%72,%73,%74,%75,%76,%77,%78,%79,%80,%81,%82,%83,%84,%85,%86,%87,%88,%89,%90,%91,%92,%93,%94,%95}, %96, %97, 1, 1, 1, 0, 1;\n"
        : "+f"(d[OFF + 0]), "+f"(d[OFF + 1]), "+f"(d[OFF + 2]), "+f"(d[OFF + 3]), "+f"(d[OFF + 4]), "+f"(d[OFF + 5]), "+f"(d[OFF + 6]), "+f"(d[OFF + 7]), "+f"(d[OFF + 8]), "+f"(d[OFF + 9]), "+f"(d[OFF + 10]), "+f"(d[OFF + 11]), "+f"(d[OFF + 12]), "+f"(d[OFF + 13]), "+f"(d[OFF + 14]), "+f"(d[OFF + 15]), "+f"(d[OFF + 16]), "+f"(d[OFF + 17]), "+f"(d[OFF + 18]), "+f"(d[OFF + 19]), "+f"(d[OFF + 20]), "+f"(d[OFF + 21]), "+f"(d[OFF + 22]), "+f"(d[OFF + 23]), "+f"(d[OFF + 24]), "+f"(d[OFF + 25]), "+f"(d[OFF + 26]), "+f"(d[OFF + 27]), "+f"(d[OFF + 28]), "+f"(d[OFF + 29]), "+f"(d[OFF + 30]), "+f"(d[OFF + 31]), "+f"(d[OFF + 32]), "+f"(d[OFF + 33]), "+f"(d[OFF + 34]), "+f"(d[OFF + 35]), "+f"(d[OFF + 36]), "+f"(d[OFF + 37]), "+f"(d[OFF + 38]), "+f"(d[OFF + 39]), "+f"(d[OFF + 40]), "+f"(d[OFF + 41]), "+f"(d[OFF + 42]), "+f"(d[OFF + 43]), "+f"(d[OFF + 44]), "+f"(d[OFF + 45]), "+f"(d[OFF + 46]), "+f"(d[OFF + 47]), "+f"(d[OFF + 48]), "+f"(d[OFF + 49]), "+f"(d[OFF + 50]), "+f"(d[OFF + 51]), "+f"(d[OFF + 52]), "+f"(d[OFF + 53]), "+f"(d[OFF + 54]), "+f"(d[OFF + 55]), "+f"(d[OFF + 56]), "+f"(d[OFF + 57]), "+f"(d[OFF + 58]), "+f"(d[OFF + 59]), "+f"(d[OFF + 60]), "+f"(d[OFF + 61]), "+f"(d[OFF + 62]), "+f"(d[OFF + 63]), "+f"(d[OFF + 64]), "+f"(d[OFF + 65]), "+f"(d[OFF + 66]), "+f"(d[OFF + 67]), "+f"(d[OFF + 68]), "+f"(d[OFF + 69]), "+f"(d[OFF + 70]), "+f"(d[OFF + 71]), "+f"(d[OFF + 72]), "+f"(d[OFF + 73]), "+f"(d[OFF + 74]), "+f"(d[OFF + 75]), "+f"(d[OFF + 76]), "+f"(d[OFF + 77]), "+f"(d[OFF + 78]), "+f"(d[OFF + 79]), "+f"(d[OFF + 80]), "+f"(d[OFF + 81]), "+f"(d[OFF + 82]), "+f"(d[OFF + 83]), "+f"(d[OFF + 84]), "+f"(d[OFF + 85]), "+f"(d[OFF + 86]), "+f"(d[OFF + 87]), "+f"(d[OFF + 88]), "+f"(d[OFF + 89]), "+f"(d[OFF + 90]), "+f"(d[OFF + 91]), "+f"(d[OFF + 92]), "+f"(d[OFF + 93]), "+f"(d[OFF + 94]), "+f"(d[OFF + 95])
        : "l"(da), "l"(db));
}
template <int OFF>
__device__ __forceinline__ void wgmma_n128_tB(float (&d)[160], uint64_t da, uint64_t db) {
    asm volatile("wgmma.mma_async.sync.aligned.m64n128k16.f32.bf16.bf16 {%0,%1,%2,%3,%4,%5,%6,%7,%8,%9,%10,%11,%12,%13,%14,%15,%16,%17,%18,%19,%20,%21,%22,%23,%24,%25,%26,%27,%28,%29,%30,%31,%32,%33,%34,%35,%36,%37,%38,%39,%40,%41,%42,%43,%44,%45,%46,%47,%48,%49,%50,%51,%52,%53,%54,%55,%56,%57,%58,%59,%60,%61,%62,%63}, %64, %65, 1, 1, 1, 0, 1;\n"
        : "+f"(d[OFF + 0]), "+f"(d[OFF + 1]), "+f"(d[OFF + 2]), "+f"(d[OFF + 3]), "+f"(d[OFF + 4]), "+f"(d[OFF + 5]), "+f"(d[OFF + 6]), "+f"(d[OFF + 7]), "+f"(d[OFF + 8]), "+f"(d[OFF + 9]), "+f"(d[OFF + 10]), "+f"(d[OFF + 11]), "+f"(d[OFF + 12]), "+f"(d[OFF + 13]), "+f"(d[OFF + 14]), "+f"(d[OFF + 15]), "+f"(d[OFF + 16]), "+f"(d[OFF + 17]), "+f"(d[OFF + 18]), "+f"(d[OFF + 19]), "+f"(d[OFF + 20]), "+f"(d[OFF + 21]), "+f"(d[OFF + 22]), "+f"(d[OFF + 23]), "+f"(d[OFF + 24]), "+f"(d[OFF + 25]), "+f"(d[OFF + 26]), "+f"(d[OFF + 27]), "+f"(d[OFF + 28]), "+f"(d[OFF + 29]), "+f"(d[OFF + 30]), "+f"(d[OFF + 31]), "+f"(d[OFF + 32]), "+f"(d[OFF + 33]), "+f"(d[OFF + 34]), "+f"(d[OFF + 35]), "+f"(d[OFF + 36]), "+f"(d[OFF + 37]), "+f"(d[OFF + 38]), "+f"(d[OFF + 39]), "+f"(d[OFF + 40]), "+f"(d[OFF + 41]), "+f"(d[OFF + 42]), "+f"(d[OFF + 43]), "+f"(d[OFF + 44]), "+f"(d[OFF + 45]), "+f"(d[OFF + 46]), "+f"(d[OFF + 47]), "+f"(d[OFF + 48]), "+f"(d[OFF + 49]), "+f"(d[OFF + 50]), "+f"(d[OFF + 51]), "+f"(d[OFF + 52]), "+f"(d[OFF + 53]), "+f"(d[OFF + 54]), "+f"(d[OFF + 55]), "+f"(d[OFF + 56]), "+f"(d[OFF + 57]), "+f"(d[OFF + 58]), "+f"(d[OFF + 59]), "+f"(d[OFF + 60]), "+f"(d[OFF + 61]), "+f"(d[OFF + 62]), "+f"(d[OFF + 63])
        : "l"(da), "l"(db));
}
__device__ __forceinline__ void stsm4(uint32_t addr, uint32_t r0, uint32_t r1, uint32_t r2, uint32_t r3) {
    asm volatile("stmatrix.sync.aligned.m8n8.x4.shared.b16 [%0], {%1,%2,%3,%4};" :: "r"(addr), "r"(r0), "r"(r1), "r"(r2), "r"(r3) : "memory");
}

#define AX_BAR   0
#define NST_G 4
#define AX_EMPTY (AX_BAR + 16 + 8 * NST_G)
#define AX_DATA  1024
#define AX_UNIT  28672
#define AX_STAGE 57344
#define AX_TOTAL (AX_DATA + 8 * AX_UNIT)

__device__ __forceinline__ void attn_compute(unsigned char* smem, uint32_t sb, uint32_t buf, int warp, int lane);
__device__ __forceinline__ void attn_producer(unsigned char* smem, int hg, unsigned epoch) {
    const uint32_t sb = smem_u32(smem);
    const int lane = threadIdx.x & 31;
    {
        for (int s = 0; s < NSEG; s++) {
            const uint32_t buf = AX_DATA + (s & 1) * (4 * AX_UNIT), bar = sb + AX_BAR + 8 * (s & 1);
            if (lane < 4) wait_counter(&g_flag[s][4 * hg + lane], (epoch + 1) * 3u);
            if (lane == 4) mbar_wait_sleep(sb + AX_EMPTY + 8 * (s & 1), ((s >> 1) & 1) ^ 1);
            __syncwarp();
            if (lane == 0) mbar_expect_tx(bar, 4 * AX_UNIT);
            __syncwarp();
            if (lane < 24) {
                fence_async_all();
                const int u = lane / 6, r = lane % 6, hf = r & 1, kind = r >> 1;
                const uint32_t ub = sb + buf + u * AX_UNIT;
                const size_t img = ((size_t)(s * NH + 4 * hg + u) * 2) + hf;
                if (kind == 0) bulk_g2s(ub + hf * 4096, g_Qimg + img * 2048, 4096, bar);
                else if (kind == 1) bulk_g2s(ub + 8192 + hf * 5120, g_Kimg + img * 2560, 5120, bar);
                else bulk_g2s(ub + 18432 + hf * 5120, g_Vimg + img * 2560, 5120, bar);
            }
            __syncwarp();
        }
    }
}
__device__ __forceinline__ void attn_loop(unsigned char* smem, int hg, unsigned epoch) {
    const uint32_t sb = smem_u32(smem);
    const int tid = threadIdx.x, warp = tid >> 5, lane = tid & 31;
    for (int s = 0; s < NSEG; s++) {
        const uint32_t buf = AX_DATA + (s & 1) * (4 * AX_UNIT), bar = sb + AX_BAR + 8 * (s & 1);
        mbar_wait_sleep(bar, (s >> 1) & 1);
        if (s >= 36) ATR(2 + 2 * (s - 36));
        attn_compute(smem, sb, buf, warp, lane);
        if (s >= 36) ATR(3 + 2 * (s - 36));
        fence_async();
        __syncwarp();
        if (lane == 0) mbar_arrive(sb + AX_EMPTY + 16 + 8 * (s & 1));
    }
}
__device__ __forceinline__ void attn_storer(unsigned char* smem, int hg) {
    const uint32_t sb = smem_u32(smem);
    const int lane = threadIdx.x & 31;
    for (int s = 0; s < NSEG; s++) {
        const uint32_t buf = AX_DATA + (s & 1) * (4 * AX_UNIT);
        mbar_wait_sleep(sb + AX_EMPTY + 16 + 8 * (s & 1), (s >> 1) & 1);
        if (lane < 8) {
            const int uu = lane >> 1, hf = lane & 1, hh = 4 * hg + uu;
            bulk_s2g(g_Oimg + (((size_t)(s >> 2) * 64 + hh * 2 + hf) * 128 + (s & 3) * 32) * 64, sb + buf + uu * AX_UNIT + hf * 4096, 4096);
            bulk_commit();
            bulk_wait_read0();
            mbar_arrive(sb + AX_EMPTY + 8 * (s & 1));
            bulk_wait0();
            fence_async_all();
            __threadfence();
            atomicAdd(&g_ocnt[s >> 1], 1u);
        }
        __syncwarp();
    }
}
__device__ __forceinline__ void attn_compute(unsigned char* smem, uint32_t sb, uint32_t buf, int warp, int lane) {
    const int g = lane >> 2, t = lane & 3;
    const int u = warp >> 1, qh = warp & 1;
    const uint32_t ub = sb + buf + u * AX_UNIT;
    float sc[5][4];
    #pragma unroll
    for (int j = 0; j < 5; j++) { sc[j][0] = sc[j][1] = sc[j][2] = sc[j][3] = 0.f; }
    #pragma unroll
    for (int ks = 0; ks < 8; ks++) {
        const int hf = ks >> 2, c0 = (ks & 3) * 2;
        uint32_t a[4];
        { int mi = lane >> 3, row = 16 * qh + (mi & 1) * 8 + (lane & 7), chunk = c0 + (mi >> 1);
          ldsm4(a, ub + hf * 4096 + row * 128 + ((chunk ^ (row & 7)) << 4)); }
        #pragma unroll
        for (int jp = 0; jp < 3; jp++) {
            uint32_t b[4];
            int mi = lane >> 3, nt = 2 * jp + (mi >> 1); if (nt > 4) nt = 4;
            int row = 8 * nt + (lane & 7), chunk = c0 + (mi & 1);
            ldsm4(b, ub + 8192 + hf * 5120 + row * 128 + ((chunk ^ (row & 7)) << 4));
            mma_bf16(sc[2 * jp], a[0], a[1], a[2], a[3], b[0], b[1]);
            if (jp < 2) mma_bf16(sc[2 * jp + 1], a[0], a[1], a[2], a[3], b[2], b[3]);
        }
    }
    uint32_t pa[3][4];
    {
        const float sc2 = 0.08838834764831845f * 1.4426950408889634f;
        float mx0 = -3.0e38f, mx1 = -3.0e38f;
        const int q0 = 16 * qh + g, q1 = q0 + 8;
        #pragma unroll
        for (int j = 0; j < 5; j++)
            #pragma unroll
            for (int e = 0; e < 2; e++) {
                int key = 8 * j + 2 * t + e - 8;
                sc[j][e] = (key <= q0) ? sc[j][e] * sc2 : -3.0e38f;
                sc[j][2 + e] = (key <= q1) ? sc[j][2 + e] * sc2 : -3.0e38f;
                mx0 = fmaxf(mx0, sc[j][e]); mx1 = fmaxf(mx1, sc[j][2 + e]);
            }
        mx0 = fmaxf(mx0, __shfl_xor_sync(~0u, mx0, 1)); mx0 = fmaxf(mx0, __shfl_xor_sync(~0u, mx0, 2));
        mx1 = fmaxf(mx1, __shfl_xor_sync(~0u, mx1, 1)); mx1 = fmaxf(mx1, __shfl_xor_sync(~0u, mx1, 2));
        float s0 = 0.f, s1 = 0.f;
        #pragma unroll
        for (int j = 0; j < 5; j++)
            #pragma unroll
            for (int e = 0; e < 2; e++) {
                sc[j][e] = ex2_approx(sc[j][e] - mx0); sc[j][2 + e] = ex2_approx(sc[j][2 + e] - mx1);
                s0 += sc[j][e]; s1 += sc[j][2 + e];
            }
        s0 += __shfl_xor_sync(~0u, s0, 1); s0 += __shfl_xor_sync(~0u, s0, 2);
        s1 += __shfl_xor_sync(~0u, s1, 1); s1 += __shfl_xor_sync(~0u, s1, 2);
        const float i0 = __frcp_rn(s0), i1 = __frcp_rn(s1);
        #pragma unroll
        for (int k = 0; k < 3; k++) {
            pa[k][0] = pack_bf16(sc[2 * k][0] * i0, sc[2 * k][1] * i0);
            pa[k][1] = pack_bf16(sc[2 * k][2] * i1, sc[2 * k][3] * i1);
            if (k < 2) { pa[k][2] = pack_bf16(sc[2 * k + 1][0] * i0, sc[2 * k + 1][1] * i0); pa[k][3] = pack_bf16(sc[2 * k + 1][2] * i1, sc[2 * k + 1][3] * i1); }
            else { pa[k][2] = 0u; pa[k][3] = 0u; }
        }
    }
    __syncwarp();
    nbar_sync(5 + u, 64);
    #pragma unroll
    for (int np = 0; np < 8; np++) {
        const int hf = np >> 2, c0 = (np & 3) * 2;
        float o0[4] = {0, 0, 0, 0}, o1[4] = {0, 0, 0, 0};
        #pragma unroll
        for (int k = 0; k < 3; k++) {
            uint32_t b[4];
            int mi = lane >> 3;
            int row = 16 * k + (mi & 1) * 8 + (lane & 7); if (row > 39) row = 39 - 7 + (lane & 7);
            int chunk = c0 + (mi >> 1);
            ldsm4t(b, ub + 18432 + hf * 5120 + row * 128 + ((chunk ^ (row & 7)) << 4));
            mma_bf16(o0, pa[k][0], pa[k][1], pa[k][2], pa[k][3], b[0], k < 2 ? b[1] : 0u);
            mma_bf16(o1, pa[k][0], pa[k][1], pa[k][2], pa[k][3], b[2], k < 2 ? b[3] : 0u);
        }
        int mi = lane >> 3, row = 16 * qh + (mi & 1) * 8 + (lane & 7), chunk = c0 + (mi >> 1);
        stsm4(ub + hf * 4096 + row * 128 + ((chunk ^ (row & 7)) << 4), pack_bf16(o0[0], o0[1]), pack_bf16(o0[2], o0[3]), pack_bf16(o1[0], o1[1]), pack_bf16(o1[2], o1[3]));
    }
}

template <int V> struct IntC { static constexpr int value = V; };
struct Task { int type, rb, c, k0, nch, plane; };
#define NFINE 29
#define NGEMM (8 + 144 + 8 * 2 + 4 + 8 * 4 + 26 * 3 + 16 * 3)
__device__ __forceinline__ Task decode_task(int j) {
    Task t; t.type = 0; t.rb = 0; t.c = 0; t.k0 = 0; t.nch = 16; t.plane = 0;
    auto H = [&](int rb, int i) { t.type = 1; t.rb = rb; t.c = i & 1; t.plane = i >> 1; t.k0 = t.plane * 16; };
    auto CF = [&](int rb, int i) { t.type = 2; t.rb = rb; t.c = i & 1; t.k0 = rb * 64 + (i >> 1) * 16; t.nch = 16; };
    auto H13 = [&](int rb, int i) { t.type = 1; t.rb = rb; t.c = i & 1; t.plane = i >> 1; t.k0 = t.plane * 5; t.nch = (t.plane == 12) ? 4 : 5; };
    auto C13 = [&](int rb, int i) { t.type = 2; t.rb = rb; t.c = i & 1; t.k0 = rb * 64 + (i >> 1) * 8; t.nch = 8; };
    if (j >= NGEMM) { t.type = 3; return t; }
    if (j < 8) { t.c = j & 1; t.plane = j >> 1; t.k0 = t.plane * 16; return t; }
    j -= 8;
    if (j < 144) {
        const int q = j / 12, r = j % 12;
        if (r < 8) { t.rb = 2 * (q + 1); t.c = r & 1; t.plane = r >> 1; t.k0 = t.plane * 16; }
        else { t.type = 2; t.rb = 2 * q + ((r - 8) >> 1); t.c = r & 1; t.k0 = t.rb * 64; t.nch = 64; }
        return t;
    }
    j -= 144;
    if (j < 8) { H(26, j); return t; }
    j -= 8;
    if (j < 8) { H(27, j); return t; }
    j -= 8;
    if (j < 4) { t.type = 2; t.rb = 24 + (j >> 1); t.c = j & 1; t.k0 = t.rb * 64; t.nch = 64; return t; }
    j -= 4;
    if (j < 8) { H(28, j); return t; }
    j -= 8;
    if (j < 8) { CF(26, j); return t; }
    j -= 8;
    if (j < 8) { CF(27, j); return t; }
    j -= 8;
    if (j < 26) { H13(29, j); return t; }
    j -= 26;
    if (j < 8) { CF(28, j); return t; }
    j -= 8;
    if (j < 26) { H13(30, j); return t; }
    j -= 26;
    if (j < 16) { C13(29, j); return t; }
    j -= 16;
    if (j < 26) { H13(31, j); return t; }
    j -= 26;
    if (j < 16) { C13(30, j); return t; }
    j -= 16;
    C13(31, j);
    return t;
}
__device__ __forceinline__ void gemm_producer(unsigned char* smem, const CUtensorMap* womap, unsigned epoch, volatile int* s_tasks) {
    const uint32_t sb = smem_u32(smem);
    uint32_t st = 0, ph = 1;
    for (int n = 0;; n++) {
        const int j = (int)(atomicAdd(&g_gemmctr, 1u) - epoch * (unsigned)(NGEMM + NAUX - NATT));
        const Task t = decode_task(j);
        if (t.type <= 1) {
            wait_counter(&g_ocnt[t.rb], (epoch + 1) * 128u);
            if (t.type == 0) wait_counter(&g_ocnt[t.rb + 1], (epoch + 1) * 128u);
            fence_async_all();
        } else if (t.type == 2) {
            wait_counter(&g_gcnt[t.rb][t.c], (epoch + 1) * (t.rb >= NFINE ? 13u : 4u));
            wait_counter(&g_ssmcnt, (epoch + 1) * 80u);
        }
        const int nch = (t.type <= 1) ? t.nch : 1;
        for (int kc = 0; kc < nch; kc++) {
            mbar_wait_sleep(sb + AX_EMPTY + 8 * st, ph);
            const uint32_t a = sb + AX_DATA + st * AX_STAGE, bar = sb + AX_BAR + 16 + 8 * st;
            if (kc == 0) s_tasks[n & 7] = j;
            if (t.type > 1) mbar_arrive(bar);
            else {
                const bf16* asrc = g_Oimg + ((size_t)(t.rb >> 1) * 64 + t.k0 + kc) * 8192 + (t.rb & 1) * 4096;
                if (t.type == 0) { mbar_expect_tx(bar, AX_STAGE); bulk_g2s(a, asrc, 8192, bar); bulk_g2s(a + 8192, asrc + 4096, 8192, bar); }
                else { mbar_expect_tx(bar, AX_STAGE - 8192); bulk_g2s(a, asrc, 8192, bar); }
                #pragma unroll
                for (int b = 0; b < 5; b++) tma_load_2d(a + 16384 + b * 8192, womap, t.c * 320 + b * 64, (t.k0 + kc) * 64, bar);
            }
            if (++st == NST_G) { st = 0; ph ^= 1; }
        }
        if (t.type == 3) break;
    }
}
__device__ __forceinline__ void gemm_signaller(volatile int* s_done) {
    for (int n = 0;; n++) {
        nbar_sync(2, 288);
        const int j = s_done[n & 7];
        if (j < 0) break;
        if ((threadIdx.x & 31) == 0) {
            const Task t = decode_task(j);
            __threadfence();
            atomicAdd(&g_gcnt[t.rb][t.c], 1u);
            if (t.type == 0) atomicAdd(&g_gcnt[t.rb + 1][t.c], 1u);
        }
        __syncwarp();
    }
}
__device__ __forceinline__ void gemm_consumer(unsigned char* smem, bf16* __restrict__ out, volatile int* s_tasks, volatile int* s_done) {
    const uint32_t sb = smem_u32(smem);
    const int tid = threadIdx.x, lane = tid & 31;
    const int wg = __shfl_sync(~0u, tid >> 7, 0), warp = __shfl_sync(~0u, (tid >> 5) & 3, 0);
    uint32_t st = 0, ph = 0;
    int ndone = 0;
    for (int n = 0;; n++) {
        mbar_wait_sleep(sb + AX_BAR + 16 + 8 * st, ph);
        const Task t = decode_task(__shfl_sync(~0u, s_tasks[n & 7], 0));
        if (t.type > 1) {
            nbar_sync(1, 256);
            if ((tid & 127) == 0) mbar_arrive(sb + AX_EMPTY + 8 * st);
            if (++st == NST_G) { st = 0; ph ^= 1; }
            if (t.type == 3) break;
            const int np = (t.rb >= NFINE) ? 13 : 4;
            const float* pbase = (t.rb >= NFINE) ? g_part31 + (size_t)(t.rb - NFINE) * 13 * 64 * DM - (size_t)t.rb * 64 * DM : g_part;
            const size_t pstride = (t.rb >= NFINE) ? (size_t)64 * DM : (size_t)SEQ * DM;
            auto combine = [&](int i, auto NP) {
                const int r = t.k0 + i / 80, cc = t.c * 320 + (i % 80) * 4;
                float4 v[NP.value];
                #pragma unroll
                for (int q = 0; q < NP.value; q++) v[q] = __ldcg(reinterpret_cast<const float4*>(pbase + q * pstride + (size_t)r * DM + cc));
                const float gt = __ldcg(g_g + r);
                const uint2 bb = __ldcg(reinterpret_cast<const uint2*>(g_b + (size_t)r * DM + cc));
                float4 a = v[0];
                #pragma unroll
                for (int q = 1; q < NP.value; q++) { a.x += v[q].x; a.y += v[q].y; a.z += v[q].z; a.w += v[q].w; }
                const float b0 = __uint_as_float(bb.x << 16), b1 = __uint_as_float(bb.x & 0xffff0000u), b2 = __uint_as_float(bb.y << 16), b3 = __uint_as_float(bb.y & 0xffff0000u);
                uint2 o; o.x = pack_bf16(gt * a.x + (1.f - gt) * b0, gt * a.y + (1.f - gt) * b1); o.y = pack_bf16(gt * a.z + (1.f - gt) * b2, gt * a.w + (1.f - gt) * b3);
                *reinterpret_cast<uint2*>(out + (size_t)r * DM + cc) = o;
            };
            if (np == 4) {
                const int nit = t.nch * 80 / 256;
                for (int it0 = 0; it0 < nit; it0 += 5) {
                    #pragma unroll
                    for (int it = 0; it < 5; it++) combine(tid + 256 * (it0 + it), IntC<4>());
                }
            } else {
                #pragma unroll
                for (int it = 0; it < 3; it++) { const int i = tid + 256 * it; if (i < 640) combine(i, IntC<13>()); }
            }
            if (n < 56) ATRID(6 + n, s_tasks[n & 7]);
            continue;
        }
        const int g = lane >> 2, tq = lane & 3;
        if (t.type == 0) {
            float acc[160];
            #pragma unroll
            for (int i = 0; i < 160; i++) acc[i] = 0.f;
            uint32_t prev = 0;
            for (int kc = 0; kc < 16; kc++) {
                mbar_wait(sb + AX_BAR + 16 + 8 * st, ph);
                const uint32_t a = sb + AX_DATA + st * AX_STAGE;
                const uint64_t da = make_desc(a + wg * 8192, 16, 1024), db = make_desc(a + 16384, 8192, 1024);
                wg_fence();
                #pragma unroll
                for (int ks = 0; ks < 4; ks++) {
                    wgmma_n192_tB<0>(acc, da + ks * 2, db + ks * 128);
                    wgmma_n128_tB<96>(acc, da + ks * 2, db + ks * 128 + 3 * 512);
                }
                wg_commit();
                asm volatile("wgmma.wait_group.sync.aligned 1;" ::: "memory");
                if (kc > 0 && (tid & 127) == 0) mbar_arrive(sb + AX_EMPTY + 8 * prev);
                prev = st;
                if (++st == NST_G) { st = 0; ph ^= 1; }
            }
            wg_wait0();
            if ((tid & 127) == 0) mbar_arrive(sb + AX_EMPTY + 8 * prev);
            float* base = g_part + ((size_t)t.plane * SEQ + t.rb * 64 + wg * 64 + warp * 16 + g) * DM + t.c * 320 + 2 * tq;
            #pragma unroll
            for (int q = 0; q < 40; q++) {
                *reinterpret_cast<float2*>(base + q * 8) = make_float2(acc[4 * q], acc[4 * q + 1]);
                *reinterpret_cast<float2*>(base + 8 * DM + q * 8) = make_float2(acc[4 * q + 2], acc[4 * q + 3]);
            }
        } else {
            float* base = (t.rb >= NFINE ? g_part31 + (size_t)((t.rb - NFINE) * 13 + t.plane) * 64 * DM : g_part + ((size_t)t.plane * SEQ + t.rb * 64) * DM) + (size_t)(warp * 16 + g) * DM + t.c * 320 + 2 * tq;
            if (wg == 0) {
                float acc[160];
                #pragma unroll
                for (int i = 0; i < 96; i++) acc[i] = 0.f;
                uint32_t prev = 0;
                for (int kc = 0; kc < t.nch; kc++) {
                    mbar_wait(sb + AX_BAR + 16 + 8 * st, ph);
                    const uint32_t a = sb + AX_DATA + st * AX_STAGE;
                    const uint64_t da = make_desc(a, 16, 1024), db = make_desc(a + 16384, 8192, 1024);
                    wg_fence();
                    #pragma unroll
                    for (int ks = 0; ks < 4; ks++) wgmma_n192_tB<0>(acc, da + ks * 2, db + ks * 128);
                    wg_commit();
                    asm volatile("wgmma.wait_group.sync.aligned 1;" ::: "memory");
                    if (kc > 0 && (tid & 127) == 0) mbar_arrive(sb + AX_EMPTY + 8 * prev);
                    prev = st;
                    if (++st == NST_G) { st = 0; ph ^= 1; }
                }
                wg_wait0();
                if ((tid & 127) == 0) mbar_arrive(sb + AX_EMPTY + 8 * prev);
                #pragma unroll
                for (int q = 0; q < 24; q++) {
                    *reinterpret_cast<float2*>(base + q * 8) = make_float2(acc[4 * q], acc[4 * q + 1]);
                    *reinterpret_cast<float2*>(base + 8 * DM + q * 8) = make_float2(acc[4 * q + 2], acc[4 * q + 3]);
                }
            } else {
                float acc[160];
                #pragma unroll
                for (int i = 96; i < 160; i++) acc[i] = 0.f;
                uint32_t prev = 0;
                for (int kc = 0; kc < t.nch; kc++) {
                    mbar_wait(sb + AX_BAR + 16 + 8 * st, ph);
                    const uint32_t a = sb + AX_DATA + st * AX_STAGE;
                    const uint64_t da = make_desc(a, 16, 1024), db = make_desc(a + 16384, 8192, 1024);
                    wg_fence();
                    #pragma unroll
                    for (int ks = 0; ks < 4; ks++) wgmma_n128_tB<96>(acc, da + ks * 2, db + ks * 128 + 3 * 512);
                    wg_commit();
                    asm volatile("wgmma.wait_group.sync.aligned 1;" ::: "memory");
                    if (kc > 0 && (tid & 127) == 0) mbar_arrive(sb + AX_EMPTY + 8 * prev);
                    prev = st;
                    if (++st == NST_G) { st = 0; ph ^= 1; }
                }
                wg_wait0();
                if ((tid & 127) == 0) mbar_arrive(sb + AX_EMPTY + 8 * prev);
                #pragma unroll
                for (int q = 24; q < 40; q++) {
                    *reinterpret_cast<float2*>(base + q * 8) = make_float2(acc[4 * q], acc[4 * q + 1]);
                    *reinterpret_cast<float2*>(base + 8 * DM + q * 8) = make_float2(acc[4 * q + 2], acc[4 * q + 3]);
                }
            }
        }
        if (tid == 0) s_done[ndone & 7] = s_tasks[n & 7];
        ndone++;
        nbar_arrive(2, 288);
        if (n < 56) ATRID(6 + n, s_tasks[n & 7]);
    }
    if (tid == 0) s_done[ndone & 7] = -1;
    nbar_arrive(2, 288);
}

__global__ void __launch_bounds__(384, 1)
k_aux(const __grid_constant__ CUtensorMap womap, const bf16* __restrict__ x, const bf16* __restrict__ A_re, const bf16* __restrict__ A_im,
      const bf16* __restrict__ B_re, const bf16* __restrict__ B_im, const bf16* __restrict__ C_re, const bf16* __restrict__ C_im,
      const bf16* __restrict__ log_dt, const bf16* __restrict__ Dskip, const bf16* __restrict__ gw, bf16* __restrict__ out) {
    extern __shared__ __align__(1024) unsigned char smem[];
    const uint32_t sb = smem_u32(smem);
    const int tid = threadIdx.x, warp = tid >> 5, lane = tid & 31;
    __shared__ unsigned s_epoch;
    __shared__ int s_task, s_tasks[8], s_done[8];
    if (tid == 0) {
        for (int i = 0; i < 2 + NST_G; i++) mbar_init(sb + AX_BAR + 8 * i, 1);
        for (int i = 0; i < NST_G; i++) mbar_init(sb + AX_EMPTY + 8 * i, blockIdx.x < NATT ? 8 : 2);
        asm volatile("fence.mbarrier_init.release.cluster;" ::: "memory");
        s_epoch = *reinterpret_cast<volatile unsigned*>(&g_epoch);
    }
    __syncthreads();
    const unsigned epoch = s_epoch;
    ATR(0);
    const int wg = __shfl_sync(~0u, tid >> 7, 0);
    if (wg == 2) {
        asm volatile("setmaxnreg.dec.sync.aligned.u32 40;");
        if (blockIdx.x < NATT) { if (warp == 8) attn_producer(smem, blockIdx.x, epoch); else if (warp == 9) attn_storer(smem, blockIdx.x); }
        else {
            nbar_sync(3, 384);
            if (warp == 8) { if (lane == 0) gemm_producer(smem, &womap, epoch, s_tasks); }
            else if (warp == 9) gemm_signaller(s_done);
        }
        __syncwarp();
        nbar_sync(4, 384);
    } else {
        asm volatile("setmaxnreg.inc.sync.aligned.u32 232;");
        if (blockIdx.x < NATT) attn_loop(smem, blockIdx.x, epoch);
        else {
            int ntask = 0;
            for (;;) {
                nbar_sync(1, 256);
                if (tid == 0) s_task = (int)(atomicAdd(&g_taskctr, 1u) - epoch * (unsigned)(80 + NAUX - NATT));
                nbar_sync(1, 256);
                const int task = s_task;
                if (task >= 80) break;
                for (int r = task * 26 + warp; r < min(SEQ, task * 26 + 26); r += 8) {
                    float sum = 0.f;
                    for (int i = lane * 2; i < DM; i += 64) {
                        __nv_bfloat162 xv = *reinterpret_cast<const __nv_bfloat162*>(x + (size_t)r * DM + i), wv = *reinterpret_cast<const __nv_bfloat162*>(gw + i);
                        sum += bf2f(xv.x) * bf2f(wv.x) + bf2f(xv.y) * bf2f(wv.y);
                    }
                    #pragma unroll
                    for (int o = 16; o; o >>= 1) sum += __shfl_xor_sync(~0u, sum, o);
                    if (lane == 0) g_g[r] = 1.f / (1.f + expf(-sum));
                }
                ssm_group(smem + AX_DATA, task, x, A_re, A_im, B_re, B_im, C_re, C_im, log_dt, Dskip);
                nbar_sync(1, 256);
                if (tid == 0) { __threadfence(); atomicAdd(&g_ssmcnt, 1u); }
                if (ntask < 4) ATR(2 + ntask);
                ntask++;
            }
            fence_async();
            nbar_sync(3, 384);
            gemm_consumer(smem, out, s_tasks, s_done);
        }
        nbar_sync(4, 384);
        if (tid == 0) {
            __threadfence();
            unsigned old = atomicAdd(&g_auxdone, 1u);
            if (old == NAUX - 1) { g_auxdone = 0; __threadfence(); atomicAdd(&g_epoch, 1u); }
        }
    }
    asm volatile("griddepcontrol.wait;" ::: "memory");
}

extern "C" void kernel_launch(void* const* d_in, const int* in_sizes, int n_in, void* d_out, int out_size) {
    const bf16* x = (const bf16*)d_in[0];
    const bf16* mem0 = (const bf16*)d_in[1];
    const bf16* Wq = (const bf16*)d_in[2];
    const bf16* Wk = (const bf16*)d_in[3];
    const bf16* Wv = (const bf16*)d_in[4];
    const bf16* Wo = (const bf16*)d_in[5];
    const bf16 *A_re = (const bf16*)d_in[8], *A_im = (const bf16*)d_in[9], *B_re = (const bf16*)d_in[10], *B_im = (const bf16*)d_in[11];
    const bf16 *C_re = (const bf16*)d_in[12], *C_im = (const bf16*)d_in[13], *log_dt = (const bf16*)d_in[14], *Dskip = (const bf16*)d_in[15];
    const bf16* gw = (const bf16*)d_in[16];
    bf16* out = (bf16*)d_out;
    cudaStream_t st = cudaStreamPerThread;
    static bool init = false;
    static CUtensorMap xmap, womap, wqmap, wkmap, wvmap;
    static const void* xmap_ptr = nullptr; static const void* womap_ptr = nullptr; static const void* w_ptr[3] = {nullptr, nullptr, nullptr};
    if (!init) {
        cudaFuncSetAttribute(k_chain, cudaFuncAttributeMaxDynamicSharedMemorySize, SM_TOTAL);
        cudaFuncSetAttribute(k_aux, cudaFuncAttributeMaxDynamicSharedMemorySize, AX_TOTAL);
        init = true;
    }
    if (xmap_ptr != (const void*)x || womap_ptr != (const void*)Wo || w_ptr[0] != Wq || w_ptr[1] != Wk || w_ptr[2] != Wv) {
        void* fn = nullptr; cudaDriverEntryPointQueryResult qres;
        cudaGetDriverEntryPoint("cuTensorMapEncodeTiled", &fn, cudaEnableDefault, &qres);
        typedef CUresult (*EncFn)(CUtensorMap*, CUtensorMapDataType, cuuint32_t, void*, const cuuint64_t*, const cuuint64_t*, const cuuint32_t*, const cuuint32_t*,
                                  CUtensorMapInterleave, CUtensorMapSwizzle, CUtensorMapL2promotion, CUtensorMapFloatOOBfill);
        cuuint32_t es[2] = {1, 1};
        {
          cuuint64_t dims[3] = {64, SEQ, 10}; cuuint64_t strides[2] = {DM * 2, 128}; cuuint32_t box[3] = {64, 32, 10}; cuuint32_t es3[3] = {1, 1, 1};
          ((EncFn)fn)(&xmap, CU_TENSOR_MAP_DATA_TYPE_BFLOAT16, 3, (void*)x, dims, strides, box, es3, CU_TENSOR_MAP_INTERLEAVE_NONE, CU_TENSOR_MAP_SWIZZLE_128B,
                      CU_TENSOR_MAP_L2_PROMOTION_L2_128B, CU_TENSOR_MAP_FLOAT_OOB_FILL_NONE); }
        { cuuint64_t dims[2] = {DM, HD}; cuuint64_t strides[1] = {DM * 2}; cuuint32_t box[2] = {64, 64};
          ((EncFn)fn)(&womap, CU_TENSOR_MAP_DATA_TYPE_BFLOAT16, 2, (void*)Wo, dims, strides, box, es, CU_TENSOR_MAP_INTERLEAVE_NONE, CU_TENSOR_MAP_SWIZZLE_128B,
                      CU_TENSOR_MAP_L2_PROMOTION_L2_128B, CU_TENSOR_MAP_FLOAT_OOB_FILL_NONE); }
        { cuuint64_t dims[2] = {HD, DM}; cuuint64_t strides[1] = {HD * 2}; cuuint32_t box[2] = {64, 128};
          const bf16* ws[3] = {Wq, Wk, Wv}; CUtensorMap* ms[3] = {&wqmap, &wkmap, &wvmap};
          for (int i = 0; i < 3; i++)
              ((EncFn)fn)(ms[i], CU_TENSOR_MAP_DATA_TYPE_BFLOAT16, 2, (void*)ws[i], dims, strides, box, es, CU_TENSOR_MAP_INTERLEAVE_NONE, CU_TENSOR_MAP_SWIZZLE_128B,
                          CU_TENSOR_MAP_L2_PROMOTION_L2_128B, CU_TENSOR_MAP_FLOAT_OOB_FILL_NONE); }
        xmap_ptr = (const void*)x; womap_ptr = (const void*)Wo; w_ptr[0] = Wq; w_ptr[1] = Wk; w_ptr[2] = Wv;
    }
    k_chain<<<96, 384, SM_TOTAL, st>>>(xmap, wqmap, wkmap, wvmap, womap, x, mem0);
    {
        cudaLaunchConfig_t cfg = {};
        cfg.gridDim = dim3(NAUX); cfg.blockDim = dim3(384); cfg.dynamicSmemBytes = AX_TOTAL; cfg.stream = st;
        cudaLaunchAttribute at[1];
        at[0].id = cudaLaunchAttributeProgrammaticStreamSerialization; at[0].val.programmaticStreamSerializationAllowed = 1;
        cfg.attrs = at; cfg.numAttrs = 1;
        cudaLaunchKernelEx(&cfg, k_aux, womap, x, A_re, A_im, B_re, B_im, C_re, C_im, log_dt, Dskip, gw, out);
    }
}
```

```cpp
#include <cuda_runtime.h>
#include <cuda_bf16.h>
#include <stdint.h>
#include <cuda.h>

typedef __nv_bfloat16 bf16;

#define SEQ 2048
#define DM 640
#define NH 32
#define DH 128
#define NM 8
#define SEG 32
#define NSEG 64
#define NST 128
#define HD 4096

__device__ bf16  g_b[SEQ * DM];
__device__ float g_g[SEQ];

__device__ __forceinline__ float bf2f(bf16 v) { return __bfloat162float(v); }
__device__ __forceinline__ uint32_t pack_bf16(float lo, float hi) {
    uint32_t r; asm("cvt.rn.bf16x2.f32 %0, %1, %2;" : "=r"(r) : "f"(hi), "f"(lo)); return r;
}
__device__ __forceinline__ uint32_t f2tf32(float x) { uint32_t r; asm("cvt.rna.tf32.f32 %0, %1;" : "=r"(r) : "f"(x)); return r; }
__device__ __forceinline__ void mma_tf32(float (&d)[4], uint32_t a0, uint32_t a1, uint32_t a2, uint32_t a3, uint32_t b0, uint32_t b1) {
    asm volatile("mma.sync.aligned.m16n8k8.row.col.f32.tf32.tf32.f32 {%0,%1,%2,%3}, {%4,%5,%6,%7}, {%8,%9}, {%0,%1,%2,%3};\n"
        : "+f"(d[0]), "+f"(d[1]), "+f"(d[2]), "+f"(d[3]) : "r"(a0), "r"(a1), "r"(a2), "r"(a3), "r"(b0), "r"(b1));
}
__device__ __forceinline__ void mma_bf16(float (&d)[4], uint32_t a0, uint32_t a1, uint32_t a2, uint32_t a3, uint32_t b0, uint32_t b1) {
    asm volatile("mma.sync.aligned.m16n8k16.row.col.f32.bf16.bf16.f32 {%0,%1,%2,%3}, {%4,%5,%6,%7}, {%8,%9}, {%0,%1,%2,%3};\n"
        : "+f"(d[0]), "+f"(d[1]), "+f"(d[2]), "+f"(d[3]) : "r"(a0), "r"(a1), "r"(a2), "r"(a3), "r"(b0), "r"(b1));
}
struct cf { float re, im; };
__device__ __forceinline__ cf cmul(cf a, cf b) { cf r; r.re = a.re * b.re - a.im * b.im; r.im = a.re * b.im + a.im * b.re; return r; }
__device__ __forceinline__ cf csq(cf a) { cf r; r.re = a.re * a.re - a.im * a.im; r.im = 2.f * a.re * a.im; return r; }
__device__ __forceinline__ cf cexpL(float zr, float zi, float L) {
    float e = __expf(zr * L);
    float ang = zi * L;
    float k = rintf(ang * 0.15915494309189535f);
    ang = fmaf(-k, 6.2831854820251465f, ang);
    ang = fmaf(-k, -1.7484555314695172e-07f, ang);
    cf r; r.re = e * __cosf(ang); r.im = e * __sinf(ang); return r;
}

#define SSM_CH 8
#define KC_PITCH 648
#define XS_PAD 128
#define XS_PITCH (XS_PAD + 2048 + 8)
#define YS_PITCH (2048 + 8)
#define KT_LEN (2048 + 48)
struct SsmSmem {
    float Kc[SSM_CH][KC_PITCH];
    bf16  xs[SSM_CH][XS_PITCH];
    union {
        bf16  KT[SSM_CH][2][KT_LEN];
        float st[SSM_CH][NST][8];
    } u;
    bf16  ys[SSM_CH][YS_PITCH];
    uint16_t kidx[2048];
};

__device__ __forceinline__ int kc_index(int l) {
    return l < 256 ? l : (l < 512 ? 256 + ((l - 256) >> 1) : (l < 1024 ? 384 + ((l - 512) >> 2) : 512 + ((l - 1024) >> 3)));
}

__device__ __forceinline__ void ssm_group(unsigned char* smem_raw, int grp, const bf16* __restrict__ x, const bf16* __restrict__ A_re, const bf16* __restrict__ A_im,
        const bf16* __restrict__ B_re, const bf16* __restrict__ B_im, const bf16* __restrict__ C_re, const bf16* __restrict__ C_im,
        const bf16* __restrict__ log_dt, const bf16* __restrict__ Dskip) {
    SsmSmem& S = *reinterpret_cast<SsmSmem*>(smem_raw);
    const int tid = threadIdx.x, w = tid >> 5, lane = tid & 31, g = lane >> 2, t = lane & 3;
    const int d0 = grp * SSM_CH;
    asm volatile("bar.sync 1, 256;" ::: "memory");
    #pragma unroll
    for (int it = 0; it < 8; it++) {
        const int l = tid + 256 * it;
        uint4 v = *reinterpret_cast<const uint4*>(x + (size_t)l * DM + d0);
        const bf16* p = reinterpret_cast<const bf16*>(&v);
        const int lr = (l & ~15) | (15 - (l & 15));
        #pragma unroll
        for (int c = 0; c < 8; c++) S.xs[c][XS_PAD + lr] = p[c];
        S.kidx[l] = (uint16_t)((int)bf2f(__float2bfloat16_rn((float)l)) == 2048 ? 640 : kc_index((int)bf2f(__float2bfloat16_rn((float)l))));
    }
    for (int i = tid; i < SSM_CH * XS_PAD / 2; i += 256) reinterpret_cast<uint32_t*>(&S.xs[i / (XS_PAD / 2)][0])[i % (XS_PAD / 2)] = 0u;
    {
        const int d = d0 + w;
        const float dt = bf2f(__float2bfloat16_rn(expf(bf2f(log_dt[d]))));
        #pragma unroll
        for (int i = 0; i < 4; i++) {
            const int n = lane + 32 * i;
            float zr = dt * bf2f(A_re[d * NST + n]), zi = dt * bf2f(A_im[d * NST + n]);
            cf dB; dB.re = dt * bf2f(B_re[d * NST + n]); dB.im = dt * bf2f(B_im[d * NST + n]);
            cf C; C.re = bf2f(C_re[d * NST + n]); C.im = bf2f(C_im[d * NST + n]);
            cf wv = cmul(C, dB);
            cf u8 = cexpL(zr, zi, 8.f), u128 = cexpL(zr, zi, 128.f);
            float* st = S.u.st[w][n];
            *reinterpret_cast<float4*>(st) = make_float4(zr, zi, wv.re, wv.im);
            *reinterpret_cast<float4*>(st + 4) = make_float4(u8.re, u8.im, u128.re, u128.im);
        }
        __syncwarp();
        float a0a[4] = {0, 0, 0, 0}, a0b[4] = {0, 0, 0, 0}, a1[4] = {0, 0, 0, 0}, a2a[4] = {0, 0, 0, 0}, a2b[4] = {0, 0, 0, 0};
        float k2048 = 0.f;
        const float Lg = (g < 4) ? (512.f + 4.f * g) : (g < 6 ? 1024.f + 8.f * (g - 4) : 1536.f + 8.f * (g - 6));
        #pragma unroll 4
        for (int kk = 0; kk < 32; kk++) {
            const float* st = S.u.st[w][4 * kk + t];
            float4 s0 = *reinterpret_cast<const float4*>(st), s1 = *reinterpret_cast<const float4*>(st + 4);
            cf wv; wv.re = s0.z; wv.im = s0.w;
            cf u8; u8.re = s1.x; u8.im = s1.y;
            cf u128; u128.re = s1.z; u128.im = s1.w;
            cf e1 = cexpL(s0.x, s0.y, (float)g);
            cf e23 = cexpL(s0.x, s0.y, Lg);
            cf e1b = cmul(e1, u8);
            cf e2 = csq(e1);
            cf p = csq(csq(csq(e2)));
            cf f0 = cmul(wv, p), f1 = cmul(f0, u128), f2 = cmul(f1, u128), f3 = cmul(f2, u128);
            uint32_t A00 = f2tf32(f0.re), A01 = f2tf32(f1.re), A02 = f2tf32(-f0.im), A03 = f2tf32(-f1.im);
            uint32_t A10 = f2tf32(f2.re), A11 = f2tf32(f3.re), A12 = f2tf32(-f2.im), A13 = f2tf32(-f3.im);
            mma_tf32(a0a, A00, A01, A02, A03, f2tf32(e1.re), f2tf32(e1.im));
            mma_tf32(a0b, A00, A01, A02, A03, f2tf32(e1b.re), f2tf32(e1b.im));
            mma_tf32(a1, A10, A11, A12, A13, f2tf32(e2.re), f2tf32(e2.im));
            uint32_t E0 = f2tf32(e23.re), E1 = f2tf32(e23.im);
            mma_tf32(a2a, A00, A01, A02, A03, E0, E1);
            mma_tf32(a2b, A10, A11, A12, A13, E0, E1);
            cf e2048 = csq(e23);
            k2048 += wv.re * e2048.re - wv.im * e2048.im;
        }
        k2048 += __shfl_xor_sync(~0u, k2048, 1);
        k2048 += __shfl_xor_sync(~0u, k2048, 2);
        float* Kc = S.Kc[w];
        Kc[16 * g + 2 * t] = a0a[0]; Kc[16 * g + 2 * t + 1] = a0a[1]; Kc[16 * (g + 8) + 2 * t] = a0a[2]; Kc[16 * (g + 8) + 2 * t + 1] = a0a[3];
        Kc[16 * g + 8 + 2 * t] = a0b[0]; Kc[16 * g + 8 + 2 * t + 1] = a0b[1]; Kc[16 * (g + 8) + 8 + 2 * t] = a0b[2]; Kc[16 * (g + 8) + 8 + 2 * t + 1] = a0b[3];
        Kc[256 + 8 * g + 2 * t] = a1[0]; Kc[256 + 8 * g + 2 * t + 1] = a1[1]; Kc[256 + 8 * (g + 8) + 2 * t] = a1[2]; Kc[256 + 8 * (g + 8) + 2 * t + 1] = a1[3];
        #pragma unroll
        for (int mt = 0; mt < 2; mt++) {
            #pragma unroll
            for (int e = 0; e < 4; e++) {
                int A = mt * 16 + g + (e >> 1) * 8, j = 2 * t + (e & 1);
                int Lj = (j < 4) ? 512 + 4 * j : (j < 6 ? 1024 + 8 * (j - 4) : 1536 + 8 * (j - 6));
                Kc[kc_index(Lj + 16 * A)] = mt ? a2b[e] : a2a[e];
            }
        }
        if (lane == 16) Kc[640] = k2048;
    }
    __syncwarp();
    {
        asm volatile("bar.sync 1, 256;" ::: "memory");
        bf16* k0 = S.u.KT[w][0];
        bf16* k1 = S.u.KT[w][1];
        const float* Kc = S.Kc[w];
        #pragma unroll 8
        for (int j = lane; j < 2048; j += 32) {
            const bf16 v = __float2bfloat16_rn(Kc[S.kidx[j]]);
            k0[16 + j] = v;
            k1[15 + j] = v;
        }
        if (lane < 16) { k0[lane] = __float2bfloat16_rn(0.f); if (lane < 15) k1[lane] = __float2bfloat16_rn(0.f); }
        k0[2064 + lane] = __float2bfloat16_rn(0.f); k1[2063 + lane] = __float2bfloat16_rn(0.f);
        __syncwarp();
    }
    {
        float acc[16][4];
        #pragma unroll
        for (int v = 0; v < 16; v++) { acc[v][0] = acc[v][1] = acc[v][2] = acc[v][3] = 0.f; }
        const bf16* kt = (g & 1) ? &S.u.KT[w][0][0] : &S.u.KT[w][1][0];
        const int ibase0 = g + 1 + 2 * t - ((g & 1) ? 0 : 1);
        #pragma unroll 1
        for (int r = 0; r < 8; r++) {
            uint32_t B[16][2];
            #pragma unroll
            for (int v = 0; v < 16; v++) {
                const bf16* p = &S.xs[w][XS_PAD + 16 * (8 * v + g - r) + 2 * t];
                B[v][0] = *reinterpret_cast<const uint32_t*>(p);
                B[v][1] = *reinterpret_cast<const uint32_t*>(p + 8);
            }
            #pragma unroll
            for (int q = 0; q < 16; q++) {
                const int i0 = ibase0 + 16 * r + 128 * q;
                const uint32_t A0 = *reinterpret_cast<const uint32_t*>(kt + i0);
                const uint32_t A1 = *reinterpret_cast<const uint32_t*>(kt + i0 + 8);
                const uint32_t A3 = *reinterpret_cast<const uint32_t*>(kt + i0 + 16);
                #pragma unroll
                for (int v = q; v < 16; v++) mma_bf16(acc[v], A0, A1, A1, A3, B[v - q][0], B[v - q][1]);
            }
        }
        bf16* ys = S.ys[w];
        #pragma unroll
        for (int v = 0; v < 16; v++) {
            const int a = 8 * v + 2 * t;
            ys[16 * a + g] = __float2bfloat16_rn(acc[v][0]); ys[16 * (a + 1) + g] = __float2bfloat16_rn(acc[v][1]);
            ys[16 * a + g + 8] = __float2bfloat16_rn(acc[v][2]); ys[16 * (a + 1) + g + 8] = __float2bfloat16_rn(acc[v][3]);
        }
    }
    asm volatile("bar.sync 1, 256;" ::: "memory");
    {
        float dsk[8];
        #pragma unroll
        for (int c = 0; c < 8; c++) dsk[c] = bf2f(Dskip[d0 + c]);
        #pragma unroll 2
        for (int it = 0; it < 8; it++) {
            const int l = tid + 256 * it;
            const int lr = XS_PAD + ((l & ~15) | (15 - (l & 15)));
            float o[8];
            #pragma unroll
            for (int c = 0; c < 8; c++) o[c] = bf2f(S.ys[c][l]) + bf2f(__float2bfloat16_rn(bf2f(S.xs[c][lr]) * dsk[c]));
            *reinterpret_cast<uint4*>(g_b + (size_t)l * DM + d0) = make_uint4(pack_bf16(o[0], o[1]), pack_bf16(o[2], o[3]), pack_bf16(o[4], o[5]), pack_bf16(o[6], o[7]));
        }
    }
}

__device__ __forceinline__ uint32_t smem_u32(const void* p) { return (uint32_t)__cvta_generic_to_shared(p); }
__device__ __forceinline__ void mbar_init(uint32_t bar, uint32_t cnt) { asm volatile("mbarrier.init.shared::cta.b64 [%0], %1;" :: "r"(bar), "r"(cnt) : "memory"); }
__device__ __forceinline__ void mbar_expect_tx(uint32_t bar, uint32_t bytes) { asm volatile("mbarrier.arrive.expect_tx.shared::cta.b64 _, [%0], %1;" :: "r"(bar), "r"(bytes) : "memory"); }
__device__ __forceinline__ void mbar_arrive(uint32_t bar) { asm volatile("mbarrier.arrive.shared::cta.b64 _, [%0];" :: "r"(bar) : "memory"); }
__device__ __forceinline__ void mbar_wait(uint32_t bar, uint32_t parity) {
    uint32_t ok; int guard = 0;
    do {
        asm volatile("{\n.reg .pred P1;\nmbarrier.test_wait.parity.shared::cta.b64 P1, [%1], %2;\nselp.u32 %0,1,0,P1;\n}" : "=r"(ok) : "r"(bar), "r"(parity) : "memory");
    } while (!ok && ++guard < (1 << 26));
}
__device__ __forceinline__ void mbar_wait_sleep(uint32_t bar, uint32_t parity) {
    uint32_t ok; int guard = 0;
    do {
        asm volatile("{\n.reg .pred P1;\nmbarrier.try_wait.parity.shared::cta.b64 P1, [%1], %2;\nselp.u32 %0,1,0,P1;\n}" : "=r"(ok) : "r"(bar), "r"(parity) : "memory");
    } while (!ok && ++guard < (1 << 22));
}
__device__ __forceinline__ uint32_t mapa(uint32_t addr, uint32_t rank) { uint32_t r; asm volatile("mapa.shared::cluster.u32 %0, %1, %2;" : "=r"(r) : "r"(addr), "r"(rank)); return r; }
__device__ __forceinline__ void st_async4(uint32_t addr, float a, float b, float c, float d, uint32_t bar) {
    asm volatile("st.async.weak.shared::cluster.mbarrier::complete_tx::bytes.v4.f32 [%0], {%1,%2,%3,%4}, [%5];" :: "r"(addr), "f"(a), "f"(b), "f"(c), "f"(d), "r"(bar) : "memory");
}
__device__ __forceinline__ void bulk_s2c(uint32_t dst, uint32_t src, uint32_t bytes, uint32_t bar) {
    asm volatile("cp.async.bulk.shared::cluster.shared::cta.mbarrier::complete_tx::bytes [%0], [%1], %2, [%3];" :: "r"(dst), "r"(src), "r"(bytes), "r"(bar) : "memory");
}
__device__ __forceinline__ void bulk_g2s(uint32_t dst, const void* src, uint32_t bytes, uint32_t bar) {
    asm volatile("cp.async.bulk.shared::cluster.global.mbarrier::complete_tx::bytes [%0], [%1], %2, [%3];" :: "r"(dst), "l"(src), "r"(bytes), "r"(bar) : "memory");
}
__device__ __forceinline__ void bulk_s2g(void* dst, uint32_t src, uint32_t bytes) {
    asm volatile("cp.async.bulk.global.shared::cta.bulk_group [%0], [%1], %2;" :: "l"(dst), "r"(src), "r"(bytes) : "memory");
}
__device__ __forceinline__ void bulk_commit() { asm volatile("cp.async.bulk.commit_group;" ::: "memory"); }
__device__ __forceinline__ void bulk_wait_read0() { asm volatile("cp.async.bulk.wait_group.read 0;" ::: "memory"); }
__device__ __forceinline__ void bulk_wait0() { asm volatile("cp.async.bulk.wait_group 0;" ::: "memory"); }
__device__ __forceinline__ void fence_async() { asm volatile("fence.proxy.async.shared::cta;" ::: "memory"); }
__device__ __forceinline__ void nbar_sync(int id, int n) { asm volatile("bar.sync %0, %1;" :: "r"(id), "r"(n) : "memory"); }
__device__ __forceinline__ void nbar_arrive(int id, int n) { asm volatile("bar.arrive %0, %1;" :: "r"(id), "r"(n) : "memory"); }
__device__ __forceinline__ void cp_async16(uint32_t dst, const void* src) { asm volatile("cp.async.cg.shared.global [%0], [%1], 16;" :: "r"(dst), "l"(src) : "memory"); }
__device__ __forceinline__ void cp_async_wait_all() { asm volatile("cp.async.wait_all;" ::: "memory"); }
__device__ __forceinline__ void ldsm4(uint32_t (&r)[4], uint32_t addr) {
    asm volatile("ldmatrix.sync.aligned.m8n8.x4.shared.b16 {%0,%1,%2,%3}, [%4];" : "=r"(r[0]), "=r"(r[1]), "=r"(r[2]), "=r"(r[3]) : "r"(addr) : "memory");
}
__device__ __forceinline__ void ldsm4t(uint32_t (&r)[4], uint32_t addr) {
    asm volatile("ldmatrix.sync.aligned.m8n8.x4.trans.shared.b16 {%0,%1,%2,%3}, [%4];" : "=r"(r[0]), "=r"(r[1]), "=r"(r[2]), "=r"(r[3]) : "r"(addr) : "memory");
}
__device__ __forceinline__ void stsm2t(uint32_t addr, uint32_t r0, uint32_t r1) {
    asm volatile("stmatrix.sync.aligned.m8n8.x2.trans.shared.b16 [%0], {%1,%2};" :: "r"(addr), "r"(r0), "r"(r1) : "memory");
}
__device__ __forceinline__ uint4 ld_relaxed4(const void* p) { uint4 v; asm volatile("ld.relaxed.gpu.global.v4.u32 {%0,%1,%2,%3}, [%4];" : "=r"(v.x), "=r"(v.y), "=r"(v.z), "=r"(v.w) : "l"(p) : "memory"); return v; }
__device__ __forceinline__ void st_relaxed2(void* p, uint32_t a, uint32_t b) { asm volatile("st.relaxed.gpu.global.v2.u32 [%0], {%1,%2};" :: "l"(p), "r"(a), "r"(b) : "memory"); }
__device__ __forceinline__ void st_relaxed1(void* p, uint32_t a) { asm volatile("st.relaxed.gpu.global.u32 [%0], %1;" :: "l"(p), "r"(a) : "memory"); }
__device__ __forceinline__ unsigned ld_acquire(const unsigned* p) { unsigned v; asm volatile("ld.acquire.gpu.global.u32 %0, [%1];" : "=r"(v) : "l"(p) : "memory"); return v; }
__device__ __forceinline__ float ex2_approx(float x) { float r; asm("ex2.approx.ftz.f32 %0, %1;" : "=f"(r) : "f"(x)); return r; }
__device__ __forceinline__ uint64_t make_desc(uint32_t saddr, uint32_t lbo, uint32_t sbo) {
    return (uint64_t)((saddr & 0x3FFFF) >> 4) | ((uint64_t)((lbo & 0x3FFFF) >> 4) << 16) | ((uint64_t)((sbo & 0x3FFFF) >> 4) << 32) | (1ull << 62);
}
__device__ __forceinline__ void wg_fence() { asm volatile("wgmma.fence.sync.aligned;" ::: "memory"); }
__device__ __forceinline__ void wg_commit() { asm volatile("wgmma.commit_group.sync.aligned;" ::: "memory"); }
__device__ __forceinline__ void wg_wait0() { asm volatile("wgmma.wait_group.sync.aligned 0;" ::: "memory"); }
__device__ __forceinline__ void wgmma_n40_tA(float (&d)[20], uint64_t da, uint64_t db, int scale_d) {
    asm volatile("{\n.reg .pred p;\nsetp.ne.b32 p, %22, 0;\n"
        "wgmma.mma_async.sync.aligned.m64n40k16.f32.bf16.bf16 {%0,%1,%2,%3,%4,%5,%6,%7,%8,%9,%10,%11,%12,%13,%14,%15,%16,%17,%18,%19}, %20, %21, p, 1, 1, 1, 0;\n}\n"
        : "+f"(d[0]), "+f"(d[1]), "+f"(d[2]), "+f"(d[3]), "+f"(d[4]), "+f"(d[5]), "+f"(d[6]), "+f"(d[7]), "+f"(d[8]), "+f"(d[9]),
          "+f"(d[10]), "+f"(d[11]), "+f"(d[12]), "+f"(d[13]), "+f"(d[14]), "+f"(d[15]), "+f"(d[16]), "+f"(d[17]), "+f"(d[18]), "+f"(d[19])
        : "l"(da), "l"(db), "r"(scale_d));
}

#define NREP 8
#define NRED 80
#define CAL_THR 410u
#define COMM_REGS "40"
#define NPOOL 576
#define RPS 1
__device__ __align__(4096) uint32_t g_pool[(NPOOL + 1) * 1024];
__device__ unsigned g_cls[NPOOL];
__device__ unsigned g_side[96];
__device__ unsigned g_calcnt;
__device__ unsigned g_epoch;
__device__ unsigned g_flag[NSEG][NH];
__device__ __align__(1024) bf16 g_Qimg[NSEG * NH * 2 * 32 * 64];
__device__ __align__(1024) bf16 g_Kimg[NSEG * NH * 2 * 40 * 64];
__device__ __align__(1024) bf16 g_Vimg[NSEG * NH * 2 * 40 * 64];

#define SM_XB    0
#define SM_VT    81920
#define SM_KT    (SM_VT + 20480)
#define SM_QT    (SM_KT + 10240)
#define SM_QS    (SM_QT + 4096)
#define SM_MEMB  (SM_QS + 1024)
#define SM_RED   (SM_MEMB + 10240)
#define SM_SC    (SM_RED + 16384)
#define SM_CRED  (SM_SC + 5120)
#define SM_PB    (SM_CRED + 1024)
#define SM_TRACE (SM_PB + 1024)
#define SM_WO    163840
#define SM_BAR   (SM_WO + 65536)
#define SM_TPM   (SM_BAR + 256)
#define SM_TRD   (SM_TPM + 256)
#define SM_TPUB  (SM_TRD + 16)
#define SM_TGAT  (SM_TPUB + 128)
#define SM_CAL   (SM_TGAT + 64)
#define SM_TOTAL (SM_CAL + 128)
#define B_SC   (SM_BAR + 0)
#define B_V    (SM_BAR + 16)
#define B_MEM  (SM_BAR + 32)
#define B_P    (SM_BAR + 48)
#define B_X    (SM_BAR + 56)
#define B_EXP  (SM_BAR + 72)

#define TR(ev) do {} while (0)
__device__ __forceinline__ uint32_t tag_of(int s) { return (uint32_t)(((s >> 1) & 1) + 1); }
__device__ __forceinline__ unsigned probe_latency(uint32_t* p, uint32_t zero) {
    uint32_t v, best = 0xffffffffu;
    asm volatile("atom.relaxed.gpu.global.add.u32 %0, [%1], 0;" : "=r"(v) : "l"(p) : "memory");
    #pragma unroll 1
    for (int r = 0; r < 4; r++) {
        uint32_t c0, c1;
        asm volatile("mov.u32 %0, %%clock;" : "=r"(c0) : "r"(v) : "memory");
        asm volatile("atom.relaxed.gpu.global.add.u32 %0, [%1], 0;" : "=r"(v) : "l"(p + ((v + c0) & zero)) : "memory");
        asm volatile("{\n.reg .u32 t;\nand.b32 t, %1, %2;\nmov.u32 %0, %%clock;\nadd.u32 %0, %0, t;\n}" : "=r"(c1) : "r"(v), "r"(zero) : "memory");
        best = min(best, c1 - c0);
    }
    return best;
}
__device__ __forceinline__ void cluster_sync_all() { asm volatile("barrier.cluster.arrive.release.aligned;\nbarrier.cluster.wait.acquire.aligned;" ::: "memory"); }
__device__ __forceinline__ void tma_load_2d(uint32_t dst, const void* map, int c0, int c1, uint32_t bar) {
    asm volatile("cp.async.bulk.tensor.2d.shared::cluster.global.mbarrier::complete_tx::bytes [%0], [%1, {%3, %4}], [%2];"
        :: "r"(dst), "l"(map), "r"(bar), "r"(c0), "r"(c1) : "memory");
}
__device__ __forceinline__ void tma_load_3d(uint32_t dst, const void* map, int c0, int c1, int c2, uint32_t bar) {
    asm volatile("cp.async.bulk.tensor.3d.shared::cluster.global.mbarrier::complete_tx::bytes [%0], [%1, {%3, %4, %5}], [%2];"
        :: "r"(dst), "l"(map), "r"(bar), "r"(c0), "r"(c1), "r"(c2) : "memory");
}
__device__ __forceinline__ void stsm4t(uint32_t addr, uint32_t r0, uint32_t r1, uint32_t r2, uint32_t r3) {
    asm volatile("stmatrix.sync.aligned.m8n8.x4.trans.shared.b16 [%0], {%1,%2,%3,%4};" :: "r"(addr), "r"(r0), "r"(r1), "r"(r2), "r"(r3) : "memory");
}
__device__ __forceinline__ void wgmma_n32_rs(float (&d)[16], const uint32_t (&a)[4], uint64_t db, int scale_d) {
    asm volatile("{\n.reg .pred p;\nsetp.ne.b32 p, %21, 0;\n"
        "wgmma.mma_async.sync.aligned.m64n32k16.f32.bf16.bf16 {%0,%1,%2,%3,%4,%5,%6,%7,%8,%9,%10,%11,%12,%13,%14,%15}, {%16,%17,%18,%19}, %20, p, 1, 1, 0;\n}\n"
        : "+f"(d[0]), "+f"(d[1]), "+f"(d[2]), "+f"(d[3]), "+f"(d[4]), "+f"(d[5]), "+f"(d[6]), "+f"(d[7]),
          "+f"(d[8]), "+f"(d[9]), "+f"(d[10]), "+f"(d[11]), "+f"(d[12]), "+f"(d[13]), "+f"(d[14]), "+f"(d[15])
        : "r"(a[0]), "r"(a[1]), "r"(a[2]), "r"(a[3]), "l"(db), "r"(scale_d));
}

__device__ __forceinline__ void st_async4u(uint32_t addr, uint4 v, uint32_t bar) {
    asm volatile("st.async.weak.shared::cluster.mbarrier::complete_tx::bytes.v4.u32 [%0], {%1,%2,%3,%4}, [%5];" :: "r"(addr), "r"(v.x), "r"(v.y), "r"(v.z), "r"(v.w), "r"(bar) : "memory");
}
__device__ __forceinline__ void export_issue(uint32_t sb, int s, int h, uint32_t rank) {
    const size_t img = (size_t)(s * NH + h) * 2;
    const int sl = s & 1;
    if (rank == 2) {
        bulk_s2g(g_Vimg + img * 2560, sb + SM_VT + sl * 10240, 5120);
        bulk_s2g(g_Vimg + (img + 1) * 2560, sb + SM_VT + sl * 10240 + 5120, 5120);
    } else {
        bulk_s2g(g_Qimg + (img + rank) * 2048, sb + SM_QT, 4096);
        bulk_s2g(g_Kimg + (img + rank) * 2560, sb + SM_KT + sl * 5120, 5120);
    }
    bulk_commit();
    bulk_wait_read0();
    mbar_arrive(sb + B_EXP);
}
__device__ __forceinline__ void export_signal(int s, int h) {
    bulk_wait0();
    asm volatile("fence.proxy.async;" ::: "memory");
    __threadfence();
    atomicAdd(&g_flag[s][h], 1u);
}

__device__ __forceinline__ void score_tile(uint32_t sb, int sl, int nt, int lane, uint32_t rank) {
    float sc[4] = {0, 0, 0, 0}, sd[4] = {0, 0, 0, 0};
    const int r = lane & 7;
    uint32_t qa[2][4], kb[2][4];
    #pragma unroll
    for (int j = 0; j < 2; j++) {
        const int chunk = (lane >> 3) + 4 * j;
        ldsm4(kb[j], sb + SM_KT + sl * 5120 + (8 * nt + r) * 128 + ((chunk ^ r) << 4));
        ldsm4(qa[j], sb + SM_QS + r * 128 + ((chunk ^ r) << 4));
    }
    mma_bf16(sc, qa[0][0], 0u, qa[0][1], 0u, kb[0][0], kb[0][1]);
    mma_bf16(sd, qa[1][0], 0u, qa[1][1], 0u, kb[1][0], kb[1][1]);
    mma_bf16(sc, qa[0][2], 0u, qa[0][3], 0u, kb[0][2], kb[0][3]);
    mma_bf16(sd, qa[1][2], 0u, qa[1][3], 0u, kb[1][2], kb[1][3]);
    sc[0] += sd[0]; sc[1] += sd[1];
    const float o0 = __shfl_down_sync(~0u, sc[0], 1), o1 = __shfl_down_sync(~0u, sc[1], 1);
    if ((lane & 1) == 0) {
        const uint32_t a = SM_SC + sl * 2560 + rank * 1280 + ((lane >> 2) * 40 + 8 * nt + 2 * (lane & 3)) * 4;
        const uint32_t bo = B_SC + 8 * sl;
        { const uint32_t rb = mapa(sb, 2); st_async4(rb + a, sc[0], sc[1], o0, o1, rb + bo); }
        { const uint32_t rb = mapa(sb, rank ^ 1); st_async4(rb + a, sc[0], sc[1], o0, o1, rb + bo); }
        asm volatile("st.shared.v4.f32 [%0], {%1,%2,%3,%4};" :: "r"(sb + a), "f"(sc[0]), "f"(sc[1]), "f"(o0), "f"(o1) : "memory");
    }
    __syncwarp();
    if (lane == 0) mbar_arrive(sb + B_SC + 8 * sl);
}
__device__ __forceinline__ void wgmma_n40_rs(float (&d)[20], const uint32_t (&a)[4], uint64_t db, int scale_d) {
    asm volatile("{\n.reg .pred p;\nsetp.ne.b32 p, %25, 0;\n"
        "wgmma.mma_async.sync.aligned.m64n40k16.f32.bf16.bf16 {%0,%1,%2,%3,%4,%5,%6,%7,%8,%9,%10,%11,%12,%13,%14,%15,%16,%17,%18,%19}, {%20,%21,%22,%23}, %24, p, 1, 1, 0;\n}\n"
        : "+f"(d[0]), "+f"(d[1]), "+f"(d[2]), "+f"(d[3]), "+f"(d[4]), "+f"(d[5]), "+f"(d[6]), "+f"(d[7]), "+f"(d[8]), "+f"(d[9]),
          "+f"(d[10]), "+f"(d[11]), "+f"(d[12]), "+f"(d[13]), "+f"(d[14]), "+f"(d[15]), "+f"(d[16]), "+f"(d[17]), "+f"(d[18]), "+f"(d[19])
        : "r"(a[0]), "r"(a[1]), "r"(a[2]), "r"(a[3]), "l"(db), "r"(scale_d));
}
__device__ __forceinline__ void pu_mma(float (&o)[4], const float (&u)[20], const uint32_t (&pb)[5]) {
    float o2[4] = {0, 0, 0, 0};
    o[0] = o[1] = o[2] = o[3] = 0.f;
    mma_bf16(o, pack_bf16(u[0], u[1]), pack_bf16(u[2], u[3]), pack_bf16(u[4], u[5]), pack_bf16(u[6], u[7]), pb[0], pb[1]);
    mma_bf16(o2, pack_bf16(u[8], u[9]), pack_bf16(u[10], u[11]), pack_bf16(u[12], u[13]), pack_bf16(u[14], u[15]), pb[2], pb[3]);
    mma_bf16(o, pack_bf16(u[16], u[17]), pack_bf16(u[18], u[19]), 0u, 0u, pb[4], 0u);
    o[0] += o2[0]; o[1] += o2[1]; o[2] += o2[2]; o[3] += o2[3];
}
__device__ __forceinline__ void pu_store(const float (&o)[4], float2 inv, uint2 off, int lane, uint32_t tg) {
    unsigned char* pool = reinterpret_cast<unsigned char*>(g_pool) + lane * 8;
    st_relaxed2(pool + off.x, (__float_as_uint(o[0] * inv.x) & ~3u) | tg, (__float_as_uint(o[1] * inv.y) & ~3u) | tg);
    st_relaxed2(pool + off.y, (__float_as_uint(o[2] * inv.x) & ~3u) | tg, (__float_as_uint(o[3] * inv.y) & ~3u) | tg);
}
__device__ __forceinline__ float rcp_approx(float x) { float r; asm("rcp.approx.ftz.f32 %0, %1;" : "=f"(r) : "f"(x)); return r; }
template <int NT>
__device__ __forceinline__ void u_pass(unsigned char* smem, uint32_t sb, int s, uint32_t rank, int wg, int warp, int lane) {
    const int sl = s & 1;
#define NRS_V 6
    constexpr int NRS = NRS_V;
    uint32_t wa[NRS][4];
    {
        const int mi = lane >> 3, chunk = 2 * warp + (mi & 1);
        #pragma unroll
        for (int ks = 0; ks < NRS; ks++) {
            const int row = 16 * ks + (mi >> 1) * 8 + (lane & 7);
            ldsm4t(wa[ks], sb + SM_WO + (2 * wg) * 16384 + row * 128 + ((chunk ^ (row & 7)) << 4));
        }
    }
    if (rank < 2) { mbar_wait(sb + B_V + 8 * sl, (s >> 1) & 1); fence_async(); }
    if (wg == 0 && warp == 0) TR(4);
    float U0[20];
    wg_fence();
    #pragma unroll
    for (int ks = 0; ks < NRS; ks++)
        wgmma_n40_rs(U0, wa[ks], make_desc(sb + SM_VT + sl * 10240 + (ks >> 2) * 5120 + (ks & 3) * 32, 16, 1024), ks > 0);
    #pragma unroll
    for (int ks = NRS; ks < 8; ks++)
        wgmma_n40_tA(U0, make_desc(sb + SM_WO + (2 * wg) * 16384 + ks * 2048, 1024, 1024),
                     make_desc(sb + SM_VT + sl * 10240 + (ks >> 2) * 5120 + (ks & 3) * 32, 16, 1024), 1);
    wg_commit();
    const uint32_t tg = tag_of(s);
    uint32_t pb[5];
    float sm[4], sm2[4];
    auto get_p = [&]() {
        nbar_sync(9, 288);
        const uint32_t* pbs = reinterpret_cast<const uint32_t*>(smem + SM_PB);
        #pragma unroll
        for (int q = 0; q < 5; q++) pb[q] = pbs[q * 32 + lane];
        sm[0] = sm[1] = sm[2] = sm[3] = 0.f; sm2[0] = sm2[1] = sm2[2] = sm2[3] = 0.f;
        const uint32_t one = 0x3f803f80u;
        mma_bf16(sm, one, one, one, one, pb[0], pb[1]);
        mma_bf16(sm2, one, one, one, one, pb[2], pb[3]);
        mma_bf16(sm, one, one, 0u, 0u, pb[4], 0u);
    };
    const uint2* tpm = reinterpret_cast<const uint2*>(smem + SM_TPM) + (sl * 4 + 2 * wg) * 4 + warp;
    if (NT == 2) {
        wg_wait0();
        float U1[20];
        wg_fence();
        #pragma unroll
        for (int ks = 0; ks < 8; ks++)
            wgmma_n40_tA(U1, make_desc(sb + SM_WO + (2 * wg + 1) * 16384 + ks * 2048, 1024, 1024),
                         make_desc(sb + SM_VT + sl * 10240 + (ks >> 2) * 5120 + (ks & 3) * 32, 16, 1024), ks > 0);
        wg_commit();
        const uint2 off0 = tpm[0], off1 = tpm[4];
        get_p();
        float o0[4], o1[4];
        pu_mma(o0, U0, pb);
        wg_wait0();
        pu_mma(o1, U1, pb);
        const float2 inv = make_float2(rcp_approx(sm[0] + sm2[0]), rcp_approx(sm[1] + sm2[1]));
        if (wg == 0 && warp == 0) TR(8);
        pu_store(o0, inv, off0, lane, tg);
        pu_store(o1, inv, off1, lane, tg);
        if (wg == 0 && warp == 0) TR(6);
    } else {
        const uint2 off0 = tpm[0];
        wg_wait0();
        get_p();
        float o0[4];
        pu_mma(o0, U0, pb);
        const float2 inv = make_float2(rcp_approx(sm[0] + sm2[0]), rcp_approx(sm[1] + sm2[1]));
        pu_store(o0, inv, off0, lane, tg);
    }
}

__global__ void __cluster_dims__(3, 1, 1) __launch_bounds__(384, 1)
k_chain(const __grid_constant__ CUtensorMap xmap, const __grid_constant__ CUtensorMap wqmap, const __grid_constant__ CUtensorMap wkmap,
        const __grid_constant__ CUtensorMap wvmap, const __grid_constant__ CUtensorMap womap, const bf16* __restrict__ xptr, const bf16* __restrict__ mem0) {
    extern __shared__ __align__(1024) unsigned char smem[];
    const uint32_t sb = smem_u32(smem);
    const int tid = threadIdx.x, lane = tid & 31;
    const int wg = __shfl_sync(~0u, tid >> 7, 0), warp = __shfl_sync(~0u, (tid >> 5) & 3, 0);
    uint32_t rank; asm volatile("mov.u32 %0, %%cluster_ctarank;" : "=r"(rank));
    const int cta = blockIdx.x, h = cta / 3;
    asm volatile("griddepcontrol.launch_dependents;");
    if (tid == 0) {
        for (int i = 0; i < 2; i++) { mbar_init(sb + B_SC + 8 * i, rank < 2 ? 6 : 1); mbar_init(sb + B_V + 8 * i, 1); mbar_init(sb + B_MEM + 8 * i, 64); mbar_init(sb + B_X + 8 * i, 1); }
        mbar_init(sb + B_P, 1); mbar_init(sb + B_EXP, 1);
        asm volatile("fence.mbarrier_init.release.cluster;" ::: "memory");
    }
    if (tid < 80) asm volatile("prefetch.global.L2 [%0];" :: "l"(mem0 + tid * 64));
    if (h < 2) { for (int i = tid; i < 320; i += 384) asm volatile("prefetch.global.L2 [%0];" :: "l"(xptr + (size_t)h * 32 * DM + i * 64)); }
    {
        const int w12 = tid >> 5;
        if (lane == 0 && w12 < 7) {
            uint32_t* pp = (w12 < 6) ? g_pool + (size_t)(cta * 6 + w12) * 1024 + 512 : g_pool + (size_t)NPOOL * 1024 + (cta & 31) * 32 + (cta >> 5) * 8;
            const unsigned lat = probe_latency(pp, blockIdx.y);
            if (w12 < 6) g_cls[cta * 6 + w12] = lat > CAL_THR ? 1u : 0u; else g_side[cta] = lat > CAL_THR ? 1u : 0u;
        }
        __syncwarp();
        uint4* z = reinterpret_cast<uint4*>(g_pool + (size_t)cta * 6 * 1024);
        #pragma unroll
        for (int q = 0; q < 4; q++) z[tid + 384 * q] = make_uint4(0, 0, 0, 0);
        __threadfence();
        __syncwarp();
        if (lane == 0) atomicAdd(&g_calcnt, 1u);
    }
    __syncthreads();
    if (tid == 0) {
        const int ntile = (rank == 2) ? 4 : 3;
        const int tile0 = (rank == 2) ? 0 : (rank == 0 ? 4 : 7);
        mbar_expect_tx(sb + B_P, 163840 + ntile * 16384);
        const void* m0 = (rank == 2) ? &wvmap : &wqmap;
        const void* m1 = (rank == 2) ? &wvmap : &wkmap;
        const int c0 = h * DH + (rank == 1 ? 64 : 0), c1 = h * DH + (rank == 0 ? 0 : 64);
        for (int b = 0; b < 5; b++) {
            tma_load_2d(sb + b * 16384, m0, c0, b * 128, sb + B_P);
            tma_load_2d(sb + 81920 + b * 16384, m1, c1, b * 128, sb + B_P);
        }
        for (int lt = 0; lt < ntile; lt++) {
            tma_load_2d(sb + SM_WO + lt * 16384, &womap, (tile0 + lt) * 64, h * DH, sb + B_P);
            tma_load_2d(sb + SM_WO + lt * 16384 + 8192, &womap, (tile0 + lt) * 64, h * DH + 64, sb + B_P);
        }
    }
    {
        const int tile0 = (rank == 2) ? 0 : (rank == 0 ? 4 : 7);
        if (wg == 2) {
            const int ct = tid & 127;
            if (ct == 0) {
                const unsigned target = (*reinterpret_cast<volatile unsigned*>(&g_epoch) + 1u) * (96u * 12u);
                int guard = 0;
                while ((int)(ld_acquire(&g_calcnt) - target) < 0 && ++guard < (1 << 22)) {}
            }
            nbar_sync(4, 128);
            uint32_t* bm = reinterpret_cast<uint32_t*>(smem + SM_CAL);
            {
                unsigned v[5];
                #pragma unroll
                for (int q = 0; q < 5; q++) { const int b = ct + 128 * q; v[q] = (b < NPOOL) ? (__ldcg(&g_cls[b]) ^ __ldcg(&g_side[b / 6])) : 0u; }
                const unsigned sv = (ct < 96) ? __ldcg(&g_side[ct]) : 0u;
                #pragma unroll
                for (int q = 0; q < 5; q++) { const unsigned m = __ballot_sync(~0u, v[q] & 1u); if (lane == 0 && q * 4 + warp < 18) bm[q * 4 + warp] = m; }
                const unsigned m = __ballot_sync(~0u, sv & 1u);
                if (lane == 0 && warp < 3) bm[18 + warp] = m;
            }
            nbar_sync(4, 128);
            int nblk1 = 0;
            for (int i = 0; i < 18; i++) nblk1 += __popc(bm[i]);
            const unsigned red_last = (1u << (NRED - 64)) - 1u;
            const int nred1 = __popc(bm[18]) + __popc(bm[19]) + __popc(bm[20] & red_last);
            auto side_of = [&](int c) -> int { return (bm[18 + (c >> 5)] >> (c & 31)) & 1; };
            auto rank_of = [&](int c) -> int {
                int ones = 0;
                for (int i = 0; i < (c >> 5); i++) ones += __popc(bm[18 + i]);
                ones += __popc(bm[18 + (c >> 5)] & ((1u << (c & 31)) - 1u));
                return side_of(c) ? ones : c - ones;
            };
            auto nth = [&](int side, int idx) -> uint32_t {
                for (int i = 0; i < 18; i++) {
                    const unsigned m = side ? bm[i] : ~bm[i];
                    const int n = __popc(m);
                    if (idx < n) return (uint32_t)(i * 32 + __fns(m, 0, idx + 1));
                    idx -= n;
                }
                return 0u;
            };
            auto phys = [&](int side, int idx) -> uint32_t {
                const int c = side ? nblk1 : NPOOL - nblk1;
                return (idx < c) ? nth(side, idx) : nth(side ^ 1, (NPOOL - c) - 1 - (idx - c));
            };
            const int e = ct;
            if (e < 64) {
                const int slot = e >> 5, lt = (e >> 3) & 3, w = (e >> 1) & 3, hf = e & 1;
                const int tile = min(tile0 + lt, 9);
                const int r = 2 * (4 * tile + w) + hf;
                reinterpret_cast<uint32_t*>(smem + SM_TPM)[e] = phys(side_of(r), 4 * rank_of(r) + slot * 2 + (h >> 4)) * 4096u + (h & 15) * 256u;
            } else if (e < 68) {
                const int i = e - 64;
                reinterpret_cast<uint32_t*>(smem + SM_TRD)[i] = (cta < NRED) ? phys(side_of(cta), 4 * rank_of(cta) + i) * 4096u : 0u;
            } else if (e < 100) {
                const int i = e - 68, slot = i >> 3, rep = i & 7, side = (rep / RPS) & 1;
                reinterpret_cast<uint32_t*>(smem + SM_TPUB)[i] = phys(side, 4 * (side ? nred1 : NRED - nred1) + (slot * RPS + (rep % RPS)) * 3 + (cta >> 5)) * 4096u + (cta & 31) * 128u;
            } else if (e < 112) {
                const int i = e - 100, slot = i / 3, b = i % 3, side = side_of(cta);
                reinterpret_cast<uint32_t*>(smem + SM_TGAT)[slot * 4 + b] = phys(side, 4 * (side ? nred1 : NRED - nred1) + (slot * RPS + (h % RPS)) * 3 + b) * 4096u;
            }
        }
    }
    __syncthreads();
    mbar_wait_sleep(sb + B_P, 0);

    if (wg == 2) {
        asm volatile("setmaxnreg.dec.sync.aligned.u32 " COMM_REGS ";");
        const int ct = tid & 127;
        nbar_sync(5, 384);
        for (int c = ct; c < 640; c += 128) {
            int ks = c >> 4, hf = (c >> 3) & 1, r = c & 7;
            *reinterpret_cast<uint4*>(smem + SM_MEMB + c * 16) = *reinterpret_cast<const uint4*>(mem0 + r * DM + ks * 16 + hf * 8);
        }
        if (ct == 0) {
            for (int sg = 0; sg < 2; sg++) {
                mbar_expect_tx(sb + B_X + 8 * sg, 40960);
                tma_load_3d(sb + SM_XB + sg * 40960, &xmap, 0, sg * 32, 0, sb + B_X + 8 * sg);
            }
            mbar_expect_tx(sb + B_SC, rank < 2 ? 1280 : 2560);
            if (rank < 2) mbar_expect_tx(sb + B_V, 8192 + 2048);
        }
        nbar_sync(5, 384);
        cluster_sync_all();
        unsigned char* const pool = reinterpret_cast<unsigned char*>(g_pool);
        for (int s = 0; s < NSEG - 1; s++) {
            if (warp == 1) nbar_sync(12, 288);
            if (warp == 0) {
                const int g = lane >> 2, t = lane & 3;
                mbar_wait(sb + B_SC + 8 * (s & 1), (s >> 1) & 1);
                TR(5);
                const uint32_t sa = sb + SM_SC + (s & 1) * 2560 + (g * 40 + 2 * t) * 4;
                float v[5][2], u[5][2];
                #pragma unroll
                for (int q = 0; q < 5; q++) {
                    asm volatile("ld.shared.v2.f32 {%0,%1}, [%2];" : "=f"(v[q][0]), "=f"(v[q][1]) : "r"(sa + 32 * q) : "memory");
                    asm volatile("ld.shared.v2.f32 {%0,%1}, [%2];" : "=f"(u[q][0]), "=f"(u[q][1]) : "r"(sa + 1280 + 32 * q) : "memory");
                }
                float mx = -3.0e38f;
                #pragma unroll
                for (int q = 0; q < 5; q++) {
                    v[q][0] += u[q][0]; v[q][1] += u[q][1];
                    mx = fmaxf(mx, fmaxf(v[q][0], v[q][1]));
                }
                mx = fmaxf(mx, __shfl_xor_sync(~0u, mx, 1));
                mx = fmaxf(mx, __shfl_xor_sync(~0u, mx, 2));
                const float sc2 = 0.08838834764831845f * 1.4426950408889634f;
                const float mxs = mx * sc2;
                uint32_t* pbs = reinterpret_cast<uint32_t*>(smem + SM_PB);
                #pragma unroll
                for (int q = 0; q < 5; q++) {
                    const float e0 = ex2_approx(fmaf(v[q][0], sc2, -mxs)), e1 = ex2_approx(fmaf(v[q][1], sc2, -mxs));
                    pbs[q * 32 + lane] = pack_bf16(e0, e1);
                }
                __syncwarp();
                TR(0);
                nbar_arrive(9, 288);
            } else if (warp == 1 && lane == 0) {
                if (s + 1 < NSEG - 1) {
                    mbar_expect_tx(sb + B_SC + 8 * ((s + 1) & 1), rank < 2 ? 1280 : 2560);
                    if (rank < 2) mbar_expect_tx(sb + B_V + 8 * ((s + 1) & 1), 8192 + 2048);
                }
                if (s + 2 < NSEG) {
                    mbar_expect_tx(sb + B_X + 8 * (s & 1), 40960);
                    tma_load_3d(sb + SM_XB + (s & 1) * 40960, &xmap, 0, (s + 2) * 32, 0, sb + B_X + 8 * (s & 1));
                }
                export_issue(sb, s, h, rank);
                if (s >= NSEG - 4) export_signal(s, h);
            }
            __syncwarp();
            nbar_sync(3, 384);
            const uint32_t tg = tag_of(s);
            if (cta < NRED) {
                const unsigned char* base = pool + reinterpret_cast<const uint32_t*>(smem + SM_TRD)[(s & 1) * 2 + (warp >> 1)] + (warp & 1) * 2048 + lane * 16;
                uint4 v[4]; int guard = 0;
                #pragma unroll
                for (int j = 0; j < 4; j++) v[j] = make_uint4(0, 0, 0, 0);
                uint32_t pend = 0xF;
                do {
                    #pragma unroll
                    for (int j = 0; j < 4; j++) if (pend & (1u << j)) v[j] = ld_relaxed4(base + j * 512);
                    #pragma unroll
                    for (int j = 0; j < 4; j++)
                        if (((v[j].x & 3) == tg) && ((v[j].y & 3) == tg) && ((v[j].z & 3) == tg) && ((v[j].w & 3) == tg)) pend &= ~(1u << j);
                } while (__any_sync(~0u, pend != 0) && ++guard < (1 << 20));
                if (warp == 0) TR(9);
                float a0 = 0, a1 = 0, a2 = 0, a3 = 0;
                #pragma unroll
                for (int j = 0; j < 4; j++) { a0 += __uint_as_float(v[j].x); a1 += __uint_as_float(v[j].y); a2 += __uint_as_float(v[j].z); a3 += __uint_as_float(v[j].w); }
                a0 += __shfl_xor_sync(~0u, a0, 16); a1 += __shfl_xor_sync(~0u, a1, 16); a2 += __shfl_xor_sync(~0u, a2, 16); a3 += __shfl_xor_sync(~0u, a3, 16);
                float* cr = reinterpret_cast<float*>(smem + SM_CRED);
                if (lane < 16) *reinterpret_cast<float4*>(cr + warp * 64 + lane * 4) = make_float4(a0, a1, a2, a3);
                nbar_sync(4, 128);
                {
                    int rho = lane >> 2, pp = lane & 3;
                    int i0 = ((2 * pp) * 4 + (rho >> 1)) * 2 + (rho & 1), i1 = i0 + 8;
                    uint32_t wv = pack_bf16((cr[i0] + cr[64 + i0]) + (cr[128 + i0] + cr[192 + i0]), (cr[i1] + cr[64 + i1]) + (cr[128 + i1] + cr[192 + i1]));
                    if (wv == 0) wv = 0x8000u;
                    if (warp == 0) TR(10);
                    const uint32_t* tp = reinterpret_cast<const uint32_t*>(smem + SM_TPUB) + warp;
                    if (warp < 2 * RPS) st_relaxed1(pool + tp[((s + 1) & 3) * 8] + lane * 4, wv);
                    if (RPS == 4) st_relaxed1(pool + tp[((s + 1) & 3) * 8 + 4] + lane * 4, wv);
                    if (warp < 2 * RPS) st_relaxed1(pool + tp[(s & 3) * 8] + lane * 4, 0u);
                    if (RPS == 4) st_relaxed1(pool + tp[(s & 3) * 8 + 4] + lane * 4, 0u);
                }
            }
            {
                const int c0 = warp * 160 + lane;
                const uint32_t* tg3 = reinterpret_cast<const uint32_t*>(smem + SM_TGAT) + ((s + 1) & 3) * 4;
                const uint32_t g0 = tg3[0], g1 = tg3[1], g2 = tg3[2];
                uint4 v[5]; int guard = 0;
                #pragma unroll
                for (int j = 0; j < 5; j++) v[j] = make_uint4(0, 0, 0, 0);
                uint32_t pend = 0x1F;
                do {
                    #pragma unroll
                    for (int j = 0; j < 5; j++) {
                        const int c = c0 + 32 * j;
                        if (pend & (1u << j)) v[j] = ld_relaxed4(pool + ((c >> 8) == 0 ? g0 : ((c >> 8) == 1 ? g1 : g2)) + (c & 255) * 16);
                    }
                    #pragma unroll
                    for (int j = 0; j < 5; j++) if (v[j].x && v[j].y && v[j].z && v[j].w) pend &= ~(1u << j);
                } while (__any_sync(~0u, pend != 0) && ++guard < (1 << 20));
                #pragma unroll
                for (int j = 0; j < 5; j++) *reinterpret_cast<uint4*>(smem + SM_MEMB + (c0 + 32 * j) * 16) = v[j];
                if (warp == 0) TR(11);
                if (warp == 3) TR(12);
                nbar_arrive(warp < 2 ? 7 + warp : 8 + warp, 160);
            }
            if (warp == 1 && lane == 0 && s < NSEG - 4) export_signal(s, h);
            __syncwarp();
        }
        if (warp == 1) { nbar_sync(12, 288); if (lane == 0) { export_issue(sb, NSEG - 1, h, rank); export_signal(NSEG - 1, h); } }
        __syncwarp();
        nbar_sync(3, 384);
        __syncwarp();
        cluster_sync_all();
    } else {
        asm volatile("setmaxnreg.inc.sync.aligned.u32 232;");
        const int wtid = tid & 127;
        const int cw = wg * 4 + warp;
        uint32_t areg[2][20][4];
        #pragma unroll
        for (int mt = 0; mt < 2; mt++)
            #pragma unroll
            for (int kk = 0; kk < 20; kk++) {
                int mi = lane >> 3;
                int row = 16 * (20 * wg + kk) + (mi >> 1) * 8 + (lane & 7);
                int chunk = 2 * warp + (mi & 1);
                ldsm4t(areg[mt][kk], sb + mt * 81920 + row * 128 + ((chunk ^ (row & 7)) << 4));
            }
        nbar_sync(5, 384);
        nbar_sync(5, 384);
        cluster_sync_all();

        for (int s = -1; s < NSEG; s++) {
            const int sl = s & 1;
            if (s >= 0) {
            if (s > 0) nbar_sync(7 + 3 * wg, 160);
            float fin[4];
            {
                float acc[2][2][4];
                #pragma unroll
                for (int i = 0; i < 2; i++)
                    #pragma unroll
                    for (int j = 0; j < 2; j++) { acc[i][j][0] = acc[i][j][1] = acc[i][j][2] = acc[i][j][3] = 0.f; }
                uint32_t b[3][4];
                const uint32_t mb = sb + SM_MEMB + (20 * wg) * 256 + lane * 16;
                ldsm4(b[0], mb); ldsm4(b[1], mb + 512);
                #pragma unroll
                for (int kp = 0; kp < 10; kp++) {
                    if (kp == 3 && s > 0) nbar_sync(8 + 3 * wg, 160);
                    if (kp + 2 < 10) ldsm4(b[(kp + 2) % 3], mb + (kp + 2) * 512);
                    const uint32_t (&bb)[4] = b[kp % 3];
                    mma_bf16(acc[0][0], areg[0][2 * kp][0], areg[0][2 * kp][1], areg[0][2 * kp][2], areg[0][2 * kp][3], bb[0], bb[1]);
                    mma_bf16(acc[1][0], areg[1][2 * kp][0], areg[1][2 * kp][1], areg[1][2 * kp][2], areg[1][2 * kp][3], bb[0], bb[1]);
                    mma_bf16(acc[0][1], areg[0][2 * kp + 1][0], areg[0][2 * kp + 1][1], areg[0][2 * kp + 1][2], areg[0][2 * kp + 1][3], bb[2], bb[3]);
                    mma_bf16(acc[1][1], areg[1][2 * kp + 1][0], areg[1][2 * kp + 1][1], areg[1][2 * kp + 1][2], areg[1][2 * kp + 1][3], bb[2], bb[3]);
                }
                float4* red = reinterpret_cast<float4*>(smem + SM_RED);
                float m0[4], m1[4];
                #pragma unroll
                for (int i = 0; i < 4; i++) { m0[i] = acc[0][0][i] + acc[0][1][i]; m1[i] = acc[1][0][i] + acc[1][1][i]; }
                red[(wg ^ 1) * 128 + wtid] = wg == 0 ? make_float4(m1[0], m1[1], m1[2], m1[3]) : make_float4(m0[0], m0[1], m0[2], m0[3]);
                nbar_sync(1, 256);
                float4 r = red[wg * 128 + wtid];
                fin[0] = (wg == 0 ? m0[0] : m1[0]) + r.x; fin[1] = (wg == 0 ? m0[1] : m1[1]) + r.y;
                fin[2] = (wg == 0 ? m0[2] : m1[2]) + r.z; fin[3] = (wg == 0 ? m0[3] : m1[3]) + r.w;
            }
            if (cw == 0) TR(1);
            {
                uint32_t p0 = pack_bf16(fin[0], fin[1]), p1 = pack_bf16(fin[2], fin[3]);
                const uint32_t doff = (rank == 2) ? SM_VT + sl * 10240 + wg * 5120 : (wg == 0 ? SM_QS : SM_KT + sl * 5120);
                const int r = lane & 7, chunk = 2 * warp + ((lane >> 3) & 1);
                const uint32_t coff = doff + r * 128 + ((chunk ^ r) << 4);
                stsm2t(sb + coff, p0, p1);
                if (rank == 2 && s < NSEG - 1) {
                    __syncwarp();
                    const uint4 v = *reinterpret_cast<const uint4*>(smem + coff);
                    const uint32_t rb = mapa(sb, lane >> 4);
                    st_async4u(rb + coff, v, rb + B_V + 8 * sl);
                }
            }
            fence_async();
            nbar_sync(1, 256);
            nbar_arrive(12, 288);
            if (cw == 0) TR(2);
            if (rank < 2 && s < NSEG - 1) {
                if (wg == 1) score_tile(sb, sl, 1 + warp, lane, rank);
                else if (warp == 0) score_tile(sb, sl, 0, lane, rank);
            }
            if (s == NSEG - 1) break;
            if (cw == 0) TR(3);
            if (wg == 0 || rank == 2) u_pass<2>(smem, sb, s, rank, wg, warp, lane);
            else                      u_pass<1>(smem, sb, s, rank, wg, warp, lane);
            if (cw == 0) TR(7);
            nbar_arrive(3, 384);
            }
            {
                const int sn = s + 1, sln = sn & 1;
                mbar_wait(sb + B_X + 8 * sln, (sn >> 1) & 1);
                float acc[2][16];
                wg_fence();
                #pragma unroll
                for (int mt = 0; mt < 2; mt++)
                    #pragma unroll
                    for (int kk = 0; kk < 20; kk++) {
                        uint64_t db = make_desc(sb + SM_XB + sln * 40960 + (5 * wg + (kk >> 2)) * 4096 + (kk & 3) * 32, 16, 1024);
                        wgmma_n32_rs(acc[mt], areg[mt][kk], db, kk > 0);
                    }
                wg_commit();
                if (cw == 0 && s >= 0) TR(14);
                wg_wait0();
                if (cw == 0 && s >= 0) TR(15);
                float4* red = reinterpret_cast<float4*>(smem + SM_RED);
                #pragma unroll
                for (int j = 0; j < 4; j++) {
                    red[((wg ^ 1) * 4 + j) * 128 + wtid] = make_float4(wg == 0 ? acc[1][4 * j] : acc[0][4 * j], wg == 0 ? acc[1][4 * j + 1] : acc[0][4 * j + 1],
                                                                       wg == 0 ? acc[1][4 * j + 2] : acc[0][4 * j + 2], wg == 0 ? acc[1][4 * j + 3] : acc[0][4 * j + 3]);
                }
                if (s >= 0) mbar_wait(sb + B_EXP, s & 1);
                nbar_sync(1, 256);
                uint32_t pk[8];
                #pragma unroll
                for (int j = 0; j < 4; j++) {
                    float4 r = red[(wg * 4 + j) * 128 + wtid];
                    pk[2 * j] = pack_bf16((wg == 0 ? acc[0][4 * j] : acc[1][4 * j]) + r.x, (wg == 0 ? acc[0][4 * j + 1] : acc[1][4 * j + 1]) + r.y);
                    pk[2 * j + 1] = pack_bf16((wg == 0 ? acc[0][4 * j + 2] : acc[1][4 * j + 2]) + r.z, (wg == 0 ? acc[0][4 * j + 3] : acc[1][4 * j + 3]) + r.w);
                }
                const uint32_t dst = (rank == 2) ? sb + SM_VT + sln * 10240 + wg * 5120 + 1024 : (wg == 0 ? sb + SM_QT : sb + SM_KT + sln * 5120 + 1024);
                #pragma unroll
                for (int jj = 0; jj < 2; jj++) {
                    int mi = lane >> 3, tok = 8 * (2 * jj + (mi >> 1)) + (lane & 7), chunk = 2 * warp + (mi & 1);
                    stsm4t(dst + tok * 128 + ((chunk ^ (tok & 7)) << 4), pk[4 * jj], pk[4 * jj + 1], pk[4 * jj + 2], pk[4 * jj + 3]);
                }
                fence_async();
                nbar_sync(1, 256);
                if (rank == 2 && lane == 0 && cw < 4 && sn < NSEG - 1) {
                    const uint32_t off = SM_VT + sln * 10240 + (cw & 1) * 5120 + 1024;
                    const uint32_t rb = mapa(sb, cw >> 1);
                    bulk_s2c(rb + off, sb + off, 4096, rb + B_V + 8 * sln);
                }
                if (cw == 0 && s >= 0) TR(13);
            }
        }
        nbar_arrive(3, 384);
        __syncwarp();
        cluster_sync_all();
    }
}

#define NAUX 36
__device__ __align__(1024) bf16 g_Oimg[16 * 64 * 128 * 64];
__device__ float    g_part[4 * SEQ * DM];
__device__ float    g_part31[3 * 13 * 64 * DM];
__device__ unsigned g_ocnt[32];
__device__ unsigned g_gcnt[32][2];
__device__ unsigned g_ssmcnt, g_auxdone, g_taskctr, g_gemmctr;
#define NATT 8
#define ATR(i) do {} while (0)
#define ATRID(i, id) do {} while (0)

__device__ __forceinline__ void wait_counter(const unsigned* p, unsigned target) {
    int guard = 0;
    while ((int)(ld_acquire(p) - target) < 0 && ++guard < (1 << 22)) __nanosleep(64);
}
__device__ __forceinline__ void fence_async_all() { asm volatile("fence.proxy.async;" ::: "memory"); }
template <int OFF>
__device__ __forceinline__ void wgmma_n192_tB(float (&d)[160], uint64_t da, uint64_t db) {
    asm volatile("wgmma.mma_async.sync.aligned.m64n192k16.f32.bf16.bf16 {%0,%1,%2,%3,%4,%5,%6,%7,%8,%9,%10,%11,%12,%13,%14,%15,%16,%17,%18,%19,%20,%21,%22,%23,%24,%25,%26,%27,%28,%29,%30,%31,%32,%33,%34,%35,%36,%37,%38,%39,%40,%41,%42,%43,%44,%45,%46,%47,%48,%49,%50,%51,%52,%53,%54,%55,%56,%57,%58,%59,%60,%61,%62,%63,%64,%65,%66,%67,%68,%69,%70,%71,%72,%73,%74,%75,%76,%77,%78,%79,%80,%81,%82,%83,%84,%85,%86,%87,%88,%89,%90,%91,%92,%93,%94,%95}, %96, %97, 1, 1, 1, 0, 1;\n"
        : "+f"(d[OFF + 0]), "+f"(d[OFF + 1]), "+f"(d[OFF + 2]), "+f"(d[OFF + 3]), "+f"(d[OFF + 4]), "+f"(d[OFF + 5]), "+f"(d[OFF + 6]), "+f"(d[OFF + 7]), "+f"(d[OFF + 8]), "+f"(d[OFF + 9]), "+f"(d[OFF + 10]), "+f"(d[OFF + 11]), "+f"(d[OFF + 12]), "+f"(d[OFF + 13]), "+f"(d[OFF + 14]), "+f"(d[OFF + 15]), "+f"(d[OFF + 16]), "+f"(d[OFF + 17]), "+f"(d[OFF + 18]), "+f"(d[OFF + 19]), "+f"(d[OFF + 20]), "+f"(d[OFF + 21]), "+f"(d[OFF + 22]), "+f"(d[OFF + 23]), "+f"(d[OFF + 24]), "+f"(d[OFF + 25]), "+f"(d[OFF + 26]), "+f"(d[OFF + 27]), "+f"(d[OFF + 28]), "+f"(d[OFF + 29]), "+f"(d[OFF + 30]), "+f"(d[OFF + 31]), "+f"(d[OFF + 32]), "+f"(d[OFF + 33]), "+f"(d[OFF + 34]), "+f"(d[OFF + 35]), "+f"(d[OFF + 36]), "+f"(d[OFF + 37]), "+f"(d[OFF + 38]), "+f"(d[OFF + 39]), "+f"(d[OFF + 40]), "+f"(d[OFF + 41]), "+f"(d[OFF + 42]), "+f"(d[OFF + 43]), "+f"(d[OFF + 44]), "+f"(d[OFF + 45]), "+f"(d[OFF + 46]), "+f"(d[OFF + 47]), "+f"(d[OFF + 48]), "+f"(d[OFF + 49]), "+f"(d[OFF + 50]), "+f"(d[OFF + 51]), "+f"(d[OFF + 52]), "+f"(d[OFF + 53]), "+f"(d[OFF + 54]), "+f"(d[OFF + 55]), "+f"(d[OFF + 56]), "+f"(d[OFF + 57]), "+f"(d[OFF + 58]), "+f"(d[OFF + 59]), "+f"(d[OFF + 60]), "+f"(d[OFF + 61]), "+f"(d[OFF + 62]), "+f"(d[OFF + 63]), "+f"(d[OFF + 64]), "+f"(d[OFF + 65]), "+f"(d[OFF + 66]), "+f"(d[OFF + 67]), "+f"(d[OFF + 68]), "+f"(d[OFF + 69]), "+f"(d[OFF + 70]), "+f"(d[OFF + 71]), "+f"(d[OFF + 72]), "+f"(d[OFF + 73]), "+f"(d[OFF + 74]), "+f"(d[OFF + 75]), "+f"(d[OFF + 76]), "+f"(d[OFF + 77]), "+f"(d[OFF + 78]), "+f"(d[OFF + 79]), "+f"(d[OFF + 80]), "+f"(d[OFF + 81]), "+f"(d[OFF + 82]), "+f"(d[OFF + 83]), "+f"(d[OFF + 84]), "+f"(d[OFF + 85]), "+f"(d[OFF + 86]), "+f"(d[OFF + 87]), "+f"(d[OFF + 88]), "+f"(d[OFF + 89]), "+f"(d[OFF + 90]), "+f"(d[OFF + 91]), "+f"(d[OFF + 92]), "+f"(d[OFF + 93]), "+f"(d[OFF + 94]), "+f"(d[OFF + 95])
        : "l"(da), "l"(db));
}
template <int OFF>
__device__ __forceinline__ void wgmma_n128_tB(float (&d)[160], uint64_t da, uint64_t db) {
    asm volatile("wgmma.mma_async.sync.aligned.m64n128k16.f32.bf16.bf16 {%0,%1,%2,%3,%4,%5,%6,%7,%8,%9,%10,%11,%12,%13,%14,%15,%16,%17,%18,%19,%20,%21,%22,%23,%24,%25,%26,%27,%28,%29,%30,%31,%32,%33,%34,%35,%36,%37,%38,%39,%40,%41,%42,%43,%44,%45,%46,%47,%48,%49,%50,%51,%52,%53,%54,%55,%56,%57,%58,%59,%60,%61,%62,%63}, %64, %65, 1, 1, 1, 0, 1;\n"
        : "+f"(d[OFF + 0]), "+f"(d[OFF + 1]), "+f"(d[OFF + 2]), "+f"(d[OFF + 3]), "+f"(d[OFF + 4]), "+f"(d[OFF + 5]), "+f"(d[OFF + 6]), "+f"(d[OFF + 7]), "+f"(d[OFF + 8]), "+f"(d[OFF + 9]), "+f"(d[OFF + 10]), "+f"(d[OFF + 11]), "+f"(d[OFF + 12]), "+f"(d[OFF + 13]), "+f"(d[OFF + 14]), "+f"(d[OFF + 15]), "+f"(d[OFF + 16]), "+f"(d[OFF + 17]), "+f"(d[OFF + 18]), "+f"(d[OFF + 19]), "+f"(d[OFF + 20]), "+f"(d[OFF + 21]), "+f"(d[OFF + 22]), "+f"(d[OFF + 23]), "+f"(d[OFF + 24]), "+f"(d[OFF + 25]), "+f"(d[OFF + 26]), "+f"(d[OFF + 27]), "+f"(d[OFF + 28]), "+f"(d[OFF + 29]), "+f"(d[OFF + 30]), "+f"(d[OFF + 31]), "+f"(d[OFF + 32]), "+f"(d[OFF + 33]), "+f"(d[OFF + 34]), "+f"(d[OFF + 35]), "+f"(d[OFF + 36]), "+f"(d[OFF + 37]), "+f"(d[OFF + 38]), "+f"(d[OFF + 39]), "+f"(d[OFF + 40]), "+f"(d[OFF + 41]), "+f"(d[OFF + 42]), "+f"(d[OFF + 43]), "+f"(d[OFF + 44]), "+f"(d[OFF + 45]), "+f"(d[OFF + 46]), "+f"(d[OFF + 47]), "+f"(d[OFF + 48]), "+f"(d[OFF + 49]), "+f"(d[OFF + 50]), "+f"(d[OFF + 51]), "+f"(d[OFF + 52]), "+f"(d[OFF + 53]), "+f"(d[OFF + 54]), "+f"(d[OFF + 55]), "+f"(d[OFF + 56]), "+f"(d[OFF + 57]), "+f"(d[OFF + 58]), "+f"(d[OFF + 59]), "+f"(d[OFF + 60]), "+f"(d[OFF + 61]), "+f"(d[OFF + 62]), "+f"(d[OFF + 63])
        : "l"(da), "l"(db));
}
__device__ __forceinline__ void stsm4(uint32_t addr, uint32_t r0, uint32_t r1, uint32_t r2, uint32_t r3) {
    asm volatile("stmatrix.sync.aligned.m8n8.x4.shared.b16 [%0], {%1,%2,%3,%4};" :: "r"(addr), "r"(r0), "r"(r1), "r"(r2), "r"(r3) : "memory");
}

#define AX_BAR   0
#define NST_G 4
#define AX_EMPTY (AX_BAR + 16 + 8 * NST_G)
#define AX_DATA  1024
#define AX_UNIT  28672
#define AX_STAGE 57344
#define AX_TOTAL (AX_DATA + 8 * AX_UNIT)

__device__ __forceinline__ void attn_compute(unsigned char* smem, uint32_t sb, uint32_t buf, int warp, int lane);
__device__ __forceinline__ void attn_producer(unsigned char* smem, int hg, unsigned epoch) {
    const uint32_t sb = smem_u32(smem);
    const int lane = threadIdx.x & 31;
    {
        for (int s = 0; s < NSEG; s++) {
            const uint32_t buf = AX_DATA + (s & 1) * (4 * AX_UNIT), bar = sb + AX_BAR + 8 * (s & 1);
            if (lane < 4) wait_counter(&g_flag[s][4 * hg + lane], (epoch + 1) * 3u);
            if (lane == 4) mbar_wait_sleep(sb + AX_EMPTY + 8 * (s & 1), ((s >> 1) & 1) ^ 1);
            __syncwarp();
            if (lane == 0) mbar_expect_tx(bar, 4 * AX_UNIT);
            __syncwarp();
            if (lane < 24) {
                fence_async_all();
                const int u = lane / 6, r = lane % 6, hf = r & 1, kind = r >> 1;
                const uint32_t ub = sb + buf + u * AX_UNIT;
                const size_t img = ((size_t)(s * NH + 4 * hg + u) * 2) + hf;
                if (kind == 0) bulk_g2s(ub + hf * 4096, g_Qimg + img * 2048, 4096, bar);
                else if (kind == 1) bulk_g2s(ub + 8192 + hf * 5120, g_Kimg + img * 2560, 5120, bar);
                else bulk_g2s(ub + 18432 + hf * 5120, g_Vimg + img * 2560, 5120, bar);
            }
            __syncwarp();
        }
    }
}
__device__ __forceinline__ void attn_loop(unsigned char* smem, int hg, unsigned epoch) {
    const uint32_t sb = smem_u32(smem);
    const int tid = threadIdx.x, warp = tid >> 5, lane = tid & 31;
    for (int s = 0; s < NSEG; s++) {
        const uint32_t buf = AX_DATA + (s & 1) * (4 * AX_UNIT), bar = sb + AX_BAR + 8 * (s & 1);
        mbar_wait_sleep(bar, (s >> 1) & 1);
        if (s >= 36) ATR(2 + 2 * (s - 36));
        attn_compute(smem, sb, buf, warp, lane);
        if (s >= 36) ATR(3 + 2 * (s - 36));
        fence_async();
        __syncwarp();
        if (lane == 0) mbar_arrive(sb + AX_EMPTY + 16 + 8 * (s & 1));
    }
}
__device__ __forceinline__ void attn_storer(unsigned char* smem, int hg) {
    const uint32_t sb = smem_u32(smem);
    const int lane = threadIdx.x & 31;
    for (int s = 0; s < NSEG; s++) {
        const uint32_t buf = AX_DATA + (s & 1) * (4 * AX_UNIT);
        mbar_wait_sleep(sb + AX_EMPTY + 16 + 8 * (s & 1), (s >> 1) & 1);
        if (lane < 8) {
            const int uu = lane >> 1, hf = lane & 1, hh = 4 * hg + uu;
            bulk_s2g(g_Oimg + (((size_t)(s >> 2) * 64 + hh * 2 + hf) * 128 + (s & 3) * 32) * 64, sb + buf + uu * AX_UNIT + hf * 4096, 4096);
            bulk_commit();
            bulk_wait_read0();
            mbar_arrive(sb + AX_EMPTY + 8 * (s & 1));
            bulk_wait0();
            fence_async_all();
            __threadfence();
            atomicAdd(&g_ocnt[s >> 1], 1u);
        }
        __syncwarp();
    }
}
__device__ __forceinline__ void attn_compute(unsigned char* smem, uint32_t sb, uint32_t buf, int warp, int lane) {
    const int g = lane >> 2, t = lane & 3;
    const int u = warp >> 1, qh = warp & 1;
    const uint32_t ub = sb + buf + u * AX_UNIT;
    float sc[5][4];
    #pragma unroll
    for (int j = 0; j < 5; j++) { sc[j][0] = sc[j][1] = sc[j][2] = sc[j][3] = 0.f; }
    #pragma unroll
    for (int ks = 0; ks < 8; ks++) {
        const int hf = ks >> 2, c0 = (ks & 3) * 2;
        uint32_t a[4];
        { int mi = lane >> 3, row = 16 * qh + (mi & 1) * 8 + (lane & 7), chunk = c0 + (mi >> 1);
          ldsm4(a, ub + hf * 4096 + row * 128 + ((chunk ^ (row & 7)) << 4)); }
        #pragma unroll
        for (int jp = 0; jp < 3; jp++) {
            uint32_t b[4];
            int mi = lane >> 3, nt = 2 * jp + (mi >> 1); if (nt > 4) nt = 4;
            int row = 8 * nt + (lane & 7), chunk = c0 + (mi & 1);
            ldsm4(b, ub + 8192 + hf * 5120 + row * 128 + ((chunk ^ (row & 7)) << 4));
            mma_bf16(sc[2 * jp], a[0], a[1], a[2], a[3], b[0], b[1]);
            if (jp < 2) mma_bf16(sc[2 * jp + 1], a[0], a[1], a[2], a[3], b[2], b[3]);
        }
    }
    uint32_t pa[3][4];
    {
        const float sc2 = 0.08838834764831845f * 1.4426950408889634f;
        float mx0 = -3.0e38f, mx1 = -3.0e38f;
        const int q0 = 16 * qh + g, q1 = q0 + 8;
        #pragma unroll
        for (int j = 0; j < 5; j++)
            #pragma unroll
            for (int e = 0; e < 2; e++) {
                int key = 8 * j + 2 * t + e - 8;
                sc[j][e] = (key <= q0) ? sc[j][e] * sc2 : -3.0e38f;
                sc[j][2 + e] = (key <= q1) ? sc[j][2 + e] * sc2 : -3.0e38f;
                mx0 = fmaxf(mx0, sc[j][e]); mx1 = fmaxf(mx1, sc[j][2 + e]);
            }
        mx0 = fmaxf(mx0, __shfl_xor_sync(~0u, mx0, 1)); mx0 = fmaxf(mx0, __shfl_xor_sync(~0u, mx0, 2));
        mx1 = fmaxf(mx1, __shfl_xor_sync(~0u, mx1, 1)); mx1 = fmaxf(mx1, __shfl_xor_sync(~0u, mx1, 2));
        float s0 = 0.f, s1 = 0.f;
        #pragma unroll
        for (int j = 0; j < 5; j++)
            #pragma unroll
            for (int e = 0; e < 2; e++) {
                sc[j][e] = ex2_approx(sc[j][e] - mx0); sc[j][2 + e] = ex2_approx(sc[j][2 + e] - mx1);
                s0 += sc[j][e]; s1 += sc[j][2 + e];
            }
        s0 += __shfl_xor_sync(~0u, s0, 1); s0 += __shfl_xor_sync(~0u, s0, 2);
        s1 += __shfl_xor_sync(~0u, s1, 1); s1 += __shfl_xor_sync(~0u, s1, 2);
        const float i0 = __frcp_rn(s0), i1 = __frcp_rn(s1);
        #pragma unroll
        for (int k = 0; k < 3; k++) {
            pa[k][0] = pack_bf16(sc[2 * k][0] * i0, sc[2 * k][1] * i0);
            pa[k][1] = pack_bf16(sc[2 * k][2] * i1, sc[2 * k][3] * i1);
            if (k < 2) { pa[k][2] = pack_bf16(sc[2 * k + 1][0] * i0, sc[2 * k + 1][1] * i0); pa[k][3] = pack_bf16(sc[2 * k + 1][2] * i1, sc[2 * k + 1][3] * i1); }
            else { pa[k][2] = 0u; pa[k][3] = 0u; }
        }
    }
    __syncwarp();
    nbar_sync(5 + u, 64);
    #pragma unroll
    for (int np = 0; np < 8; np++) {
        const int hf = np >> 2, c0 = (np & 3) * 2;
        float o0[4] = {0, 0, 0, 0}, o1[4] = {0, 0, 0, 0};
        #pragma unroll
        for (int k = 0; k < 3; k++) {
            uint32_t b[4];
            int mi = lane >> 3;
            int row = 16 * k + (mi & 1) * 8 + (lane & 7); if (row > 39) row = 39 - 7 + (lane & 7);
            int chunk = c0 + (mi >> 1);
            ldsm4t(b, ub + 18432 + hf * 5120 + row * 128 + ((chunk ^ (row & 7)) << 4));
            mma_bf16(o0, pa[k][0], pa[k][1], pa[k][2], pa[k][3], b[0], k < 2 ? b[1] : 0u);
            mma_bf16(o1, pa[k][0], pa[k][1], pa[k][2], pa[k][3], b[2], k < 2 ? b[3] : 0u);
        }
        int mi = lane >> 3, row = 16 * qh + (mi & 1) * 8 + (lane & 7), chunk = c0 + (mi >> 1);
        stsm4(ub + hf * 4096 + row * 128 + ((chunk ^ (row & 7)) << 4), pack_bf16(o0[0], o0[1]), pack_bf16(o0[2], o0[3]), pack_bf16(o1[0], o1[1]), pack_bf16(o1[2], o1[3]));
    }
}

template <int V> struct IntC { static constexpr int value = V; };
struct Task { int type, rb, c, k0, nch, plane; };
#define NFINE 29
#define NGEMM (8 + 144 + 8 * 2 + 4 + 8 * 4 + 26 * 3 + 16 * 3)
__device__ __forceinline__ Task decode_task(int j) {
    Task t; t.type = 0; t.rb = 0; t.c = 0; t.k0 = 0; t.nch = 16; t.plane = 0;
    auto H = [&](int rb, int i) { t.type = 1; t.rb = rb; t.c = i & 1; t.plane = i >> 1; t.k0 = t.plane * 16; };
    auto CF = [&](int rb, int i) { t.type = 2; t.rb = rb; t.c = i & 1; t.k0 = rb * 64 + (i >> 1) * 16; t.nch = 16; };
    auto H13 = [&](int rb, int i) { t.type = 1; t.rb = rb; t.c = i & 1; t.plane = i >> 1; t.k0 = t.plane * 5; t.nch = (t.plane == 12) ? 4 : 5; };
    auto C13 = [&](int rb, int i) { t.type = 2; t.rb = rb; t.c = i & 1; t.k0 = rb * 64 + (i >> 1) * 8; t.nch = 8; };
    if (j >= NGEMM) { t.type = 3; return t; }
    if (j < 8) { t.c = j & 1; t.plane = j >> 1; t.k0 = t.plane * 16; return t; }
    j -= 8;
    if (j < 144) {
        const int q = j / 12, r = j % 12;
        if (r < 8) { t.rb = 2 * (q + 1); t.c = r & 1; t.plane = r >> 1; t.k0 = t.plane * 16; }
        else { t.type = 2; t.rb = 2 * q + ((r - 8) >> 1); t.c = r & 1; t.k0 = t.rb * 64; t.nch = 64; }
        return t;
    }
    j -= 144;
    if (j < 8) { H(26, j); return t; }
    j -= 8;
    if (j < 8) { H(27, j); return t; }
    j -= 8;
    if (j < 4) { t.type = 2; t.rb = 24 + (j >> 1); t.c = j & 1; t.k0 = t.rb * 64; t.nch = 64; return t; }
    j -= 4;
    if (j < 8) { H(28, j); return t; }
    j -= 8;
    if (j < 8) { CF(26, j); return t; }
    j -= 8;
    if (j < 8) { CF(27, j); return t; }
    j -= 8;
    if (j < 26) { H13(29, j); return t; }
    j -= 26;
    if (j < 8) { CF(28, j); return t; }
    j -= 8;
    if (j < 26) { H13(30, j); return t; }
    j -= 26;
    if (j < 16) { C13(29, j); return t; }
    j -= 16;
    if (j < 26) { H13(31, j); return t; }
    j -= 26;
    if (j < 16) { C13(30, j); return t; }
    j -= 16;
    C13(31, j);
    return t;
}
__device__ __forceinline__ void gemm_producer(unsigned char* smem, const CUtensorMap* womap, unsigned epoch, volatile int* s_tasks) {
    const uint32_t sb = smem_u32(smem);
    uint32_t st = 0, ph = 1;
    for (int n = 0;; n++) {
        const int j = (int)(atomicAdd(&g_gemmctr, 1u) - epoch * (unsigned)(NGEMM + NAUX));
        const Task t = decode_task(j);
        if (t.type <= 1) {
            wait_counter(&g_ocnt[t.rb], (epoch + 1) * 128u);
            if (t.type == 0) wait_counter(&g_ocnt[t.rb + 1], (epoch + 1) * 128u);
            fence_async_all();
        } else if (t.type == 2) {
            wait_counter(&g_gcnt[t.rb][t.c], (epoch + 1) * (t.rb >= NFINE ? 13u : 4u));
            wait_counter(&g_ssmcnt, (epoch + 1) * 80u);
        }
        const int nch = (t.type <= 1) ? t.nch : 1;
        for (int kc = 0; kc < nch; kc++) {
            mbar_wait_sleep(sb + AX_EMPTY + 8 * st, ph);
            const uint32_t a = sb + AX_DATA + st * AX_STAGE, bar = sb + AX_BAR + 16 + 8 * st;
            if (kc == 0) s_tasks[n & 7] = j;
            if (t.type > 1) mbar_arrive(bar);
            else {
                const bf16* asrc = g_Oimg + ((size_t)(t.rb >> 1) * 64 + t.k0 + kc) * 8192 + (t.rb & 1) * 4096;
                if (t.type == 0) { mbar_expect_tx(bar, AX_STAGE); bulk_g2s(a, asrc, 8192, bar); bulk_g2s(a + 8192, asrc + 4096, 8192, bar); }
                else { mbar_expect_tx(bar, AX_STAGE - 8192); bulk_g2s(a, asrc, 8192, bar); }
                #pragma unroll
                for (int b = 0; b < 5; b++) tma_load_2d(a + 16384 + b * 8192, womap, t.c * 320 + b * 64, (t.k0 + kc) * 64, bar);
            }
            if (++st == NST_G) { st = 0; ph ^= 1; }
        }
        if (t.type == 3) break;
    }
}
__device__ __forceinline__ void gemm_signaller(volatile int* s_done) {
    for (int n = 0;; n++) {
        nbar_sync(2, 288);
        const int j = s_done[n & 7];
        if (j < 0) break;
        if ((threadIdx.x & 31) == 0) {
            const Task t = decode_task(j);
            __threadfence();
            atomicAdd(&g_gcnt[t.rb][t.c], 1u);
            if (t.type == 0) atomicAdd(&g_gcnt[t.rb + 1][t.c], 1u);
        }
        __syncwarp();
    }
}
__device__ __forceinline__ void gemm_consumer(unsigned char* smem, bf16* __restrict__ out, volatile int* s_tasks, volatile int* s_done) {
    const uint32_t sb = smem_u32(smem);
    const int tid = threadIdx.x, lane = tid & 31;
    const int wg = __shfl_sync(~0u, tid >> 7, 0), warp = __shfl_sync(~0u, (tid >> 5) & 3, 0);
    uint32_t st = 0, ph = 0;
    int ndone = 0;
    for (int n = 0;; n++) {
        mbar_wait_sleep(sb + AX_BAR + 16 + 8 * st, ph);
        const Task t = decode_task(__shfl_sync(~0u, s_tasks[n & 7], 0));
        if (t.type > 1) {
            nbar_sync(1, 256);
            if ((tid & 127) == 0) mbar_arrive(sb + AX_EMPTY + 8 * st);
            if (++st == NST_G) { st = 0; ph ^= 1; }
            if (t.type == 3) break;
            const int np = (t.rb >= NFINE) ? 13 : 4;
            const float* pbase = (t.rb >= NFINE) ? g_part31 + (size_t)(t.rb - NFINE) * 13 * 64 * DM - (size_t)t.rb * 64 * DM : g_part;
            const size_t pstride = (t.rb >= NFINE) ? (size_t)64 * DM : (size_t)SEQ * DM;
            auto combine = [&](int i, auto NP) {
                const int r = t.k0 + i / 80, cc = t.c * 320 + (i % 80) * 4;
                float4 v[NP.value];
                #pragma unroll
                for (int q = 0; q < NP.value; q++) v[q] = __ldcg(reinterpret_cast<const float4*>(pbase + q * pstride + (size_t)r * DM + cc));
                const float gt = __ldcg(g_g + r);
                const uint2 bb = __ldcg(reinterpret_cast<const uint2*>(g_b + (size_t)r * DM + cc));
                float4 a = v[0];
                #pragma unroll
                for (int q = 1; q < NP.value; q++) { a.x += v[q].x; a.y += v[q].y; a.z += v[q].z; a.w += v[q].w; }
                const float b0 = __uint_as_float(bb.x << 16), b1 = __uint_as_float(bb.x & 0xffff0000u), b2 = __uint_as_float(bb.y << 16), b3 = __uint_as_float(bb.y & 0xffff0000u);
                uint2 o; o.x = pack_bf16(gt * a.x + (1.f - gt) * b0, gt * a.y + (1.f - gt) * b1); o.y = pack_bf16(gt * a.z + (1.f - gt) * b2, gt * a.w + (1.f - gt) * b3);
                *reinterpret_cast<uint2*>(out + (size_t)r * DM + cc) = o;
            };
            if (np == 4) {
                const int nit = t.nch * 80 / 256;
                for (int it0 = 0; it0 < nit; it0 += 5) {
                    #pragma unroll
                    for (int it = 0; it < 5; it++) combine(tid + 256 * (it0 + it), IntC<4>());
                }
            } else {
                #pragma unroll
                for (int it = 0; it < 3; it++) { const int i = tid + 256 * it; if (i < 640) combine(i, IntC<13>()); }
            }
            if (n < 56) ATRID(6 + n, s_tasks[n & 7]);
            continue;
        }
        const int g = lane >> 2, tq = lane & 3;
        if (t.type == 0) {
            float acc[160];
            #pragma unroll
            for (int i = 0; i < 160; i++) acc[i] = 0.f;
            uint32_t prev = 0;
            for (int kc = 0; kc < 16; kc++) {
                mbar_wait(sb + AX_BAR + 16 + 8 * st, ph);
                const uint32_t a = sb + AX_DATA + st * AX_STAGE;
                const uint64_t da = make_desc(a + wg * 8192, 16, 1024), db = make_desc(a + 16384, 8192, 1024);
                wg_fence();
                #pragma unroll
                for (int ks = 0; ks < 4; ks++) {
                    wgmma_n192_tB<0>(acc, da + ks * 2, db + ks * 128);
                    wgmma_n128_tB<96>(acc, da + ks * 2, db + ks * 128 + 3 * 512);
                }
                wg_commit();
                asm volatile("wgmma.wait_group.sync.aligned 1;" ::: "memory");
                if (kc > 0 && (tid & 127) == 0) mbar_arrive(sb + AX_EMPTY + 8 * prev);
                prev = st;
                if (++st == NST_G) { st = 0; ph ^= 1; }
            }
            wg_wait0();
            if ((tid & 127) == 0) mbar_arrive(sb + AX_EMPTY + 8 * prev);
            float* base = g_part + ((size_t)t.plane * SEQ + t.rb * 64 + wg * 64 + warp * 16 + g) * DM + t.c * 320 + 2 * tq;
            #pragma unroll
            for (int q = 0; q < 40; q++) {
                *reinterpret_cast<float2*>(base + q * 8) = make_float2(acc[4 * q], acc[4 * q + 1]);
                *reinterpret_cast<float2*>(base + 8 * DM + q * 8) = make_float2(acc[4 * q + 2], acc[4 * q + 3]);
            }
        } else {
            float* base = (t.rb >= NFINE ? g_part31 + (size_t)((t.rb - NFINE) * 13 + t.plane) * 64 * DM : g_part + ((size_t)t.plane * SEQ + t.rb * 64) * DM) + (size_t)(warp * 16 + g) * DM + t.c * 320 + 2 * tq;
            if (wg == 0) {
                float acc[160];
                #pragma unroll
                for (int i = 0; i < 96; i++) acc[i] = 0.f;
                uint32_t prev = 0;
                for (int kc = 0; kc < t.nch; kc++) {
                    mbar_wait(sb + AX_BAR + 16 + 8 * st, ph);
                    const uint32_t a = sb + AX_DATA + st * AX_STAGE;
                    const uint64_t da = make_desc(a, 16, 1024), db = make_desc(a + 16384, 8192, 1024);
                    wg_fence();
                    #pragma unroll
                    for (int ks = 0; ks < 4; ks++) wgmma_n192_tB<0>(acc, da + ks * 2, db + ks * 128);
                    wg_commit();
                    asm volatile("wgmma.wait_group.sync.aligned 1;" ::: "memory");
                    if (kc > 0 && (tid & 127) == 0) mbar_arrive(sb + AX_EMPTY + 8 * prev);
                    prev = st;
                    if (++st == NST_G) { st = 0; ph ^= 1; }
                }
                wg_wait0();
                if ((tid & 127) == 0) mbar_arrive(sb + AX_EMPTY + 8 * prev);
                #pragma unroll
                for (int q = 0; q < 24; q++) {
                    *reinterpret_cast<float2*>(base + q * 8) = make_float2(acc[4 * q], acc[4 * q + 1]);
                    *reinterpret_cast<float2*>(base + 8 * DM + q * 8) = make_float2(acc[4 * q + 2], acc[4 * q + 3]);
                }
            } else {
                float acc[160];
                #pragma unroll
                for (int i = 96; i < 160; i++) acc[i] = 0.f;
                uint32_t prev = 0;
                for (int kc = 0; kc < t.nch; kc++) {
                    mbar_wait(sb + AX_BAR + 16 + 8 * st, ph);
                    const uint32_t a = sb + AX_DATA + st * AX_STAGE;
                    const uint64_t da = make_desc(a, 16, 1024), db = make_desc(a + 16384, 8192, 1024);
                    wg_fence();
                    #pragma unroll
                    for (int ks = 0; ks < 4; ks++) wgmma_n128_tB<96>(acc, da + ks * 2, db + ks * 128 + 3 * 512);
                    wg_commit();
                    asm volatile("wgmma.wait_group.sync.aligned 1;" ::: "memory");
                    if (kc > 0 && (tid & 127) == 0) mbar_arrive(sb + AX_EMPTY + 8 * prev);
                    prev = st;
                    if (++st == NST_G) { st = 0; ph ^= 1; }
                }
                wg_wait0();
                if ((tid & 127) == 0) mbar_arrive(sb + AX_EMPTY + 8 * prev);
                #pragma unroll
                for (int q = 24; q < 40; q++) {
                    *reinterpret_cast<float2*>(base + q * 8) = make_float2(acc[4 * q], acc[4 * q + 1]);
                    *reinterpret_cast<float2*>(base + 8 * DM + q * 8) = make_float2(acc[4 * q + 2], acc[4 * q + 3]);
                }
            }
        }
        if (tid == 0) s_done[ndone & 7] = s_tasks[n & 7];
        ndone++;
        nbar_arrive(2, 288);
        if (n < 56) ATRID(6 + n, s_tasks[n & 7]);
    }
    if (tid == 0) s_done[ndone & 7] = -1;
    nbar_arrive(2, 288);
}

__global__ void __launch_bounds__(384, 1)
k_aux(const __grid_constant__ CUtensorMap womap, const bf16* __restrict__ x, const bf16* __restrict__ A_re, const bf16* __restrict__ A_im,
      const bf16* __restrict__ B_re, const bf16* __restrict__ B_im, const bf16* __restrict__ C_re, const bf16* __restrict__ C_im,
      const bf16* __restrict__ log_dt, const bf16* __restrict__ Dskip, const bf16* __restrict__ gw, bf16* __restrict__ out) {
    extern __shared__ __align__(1024) unsigned char smem[];
    const uint32_t sb = smem_u32(smem);
    const int tid = threadIdx.x, warp = tid >> 5, lane = tid & 31;
    __shared__ unsigned s_epoch;
    __shared__ int s_task, s_tasks[8], s_done[8];
    if (tid == 0) {
        for (int i = 0; i < 2 + NST_G; i++) mbar_init(sb + AX_BAR + 8 * i, 1);
        for (int i = 0; i < NST_G; i++) mbar_init(sb + AX_EMPTY + 8 * i, blockIdx.x < NATT ? 8 : 2);
        asm volatile("fence.mbarrier_init.release.cluster;" ::: "memory");
        s_epoch = *reinterpret_cast<volatile unsigned*>(&g_epoch);
    }
    __syncthreads();
    const unsigned epoch = s_epoch;
    ATR(0);
    const int wg = __shfl_sync(~0u, tid >> 7, 0);
    if (wg == 2) {
        asm volatile("setmaxnreg.dec.sync.aligned.u32 40;");
        if (blockIdx.x < NATT) { if (warp == 8) attn_producer(smem, blockIdx.x, epoch); else if (warp == 9) attn_storer(smem, blockIdx.x); __syncwarp(); }
        nbar_sync(3, 384);
        nbar_sync(3, 384);
        if (warp == 8) { if (lane == 0) gemm_producer(smem, &womap, epoch, s_tasks); }
        else if (warp == 9) gemm_signaller(s_done);
        __syncwarp();
        nbar_sync(4, 384);
    } else {
        asm volatile("setmaxnreg.inc.sync.aligned.u32 232;");
        if (blockIdx.x < NATT) attn_loop(smem, blockIdx.x, epoch);
        else {
            int ntask = 0;
            for (;;) {
                nbar_sync(1, 256);
                if (tid == 0) s_task = (int)(atomicAdd(&g_taskctr, 1u) - epoch * (unsigned)(80 + NAUX - NATT));
                nbar_sync(1, 256);
                const int task = s_task;
                if (task >= 80) break;
                for (int r = task * 26 + warp; r < min(SEQ, task * 26 + 26); r += 8) {
                    float sum = 0.f;
                    for (int i = lane * 2; i < DM; i += 64) {
                        __nv_bfloat162 xv = *reinterpret_cast<const __nv_bfloat162*>(x + (size_t)r * DM + i), wv = *reinterpret_cast<const __nv_bfloat162*>(gw + i);
                        sum += bf2f(xv.x) * bf2f(wv.x) + bf2f(xv.y) * bf2f(wv.y);
                    }
                    #pragma unroll
                    for (int o = 16; o; o >>= 1) sum += __shfl_xor_sync(~0u, sum, o);
                    if (lane == 0) g_g[r] = 1.f / (1.f + expf(-sum));
                }
                ssm_group(smem + AX_DATA, task, x, A_re, A_im, B_re, B_im, C_re, C_im, log_dt, Dskip);
                nbar_sync(1, 256);
                if (tid == 0) { __threadfence(); atomicAdd(&g_ssmcnt, 1u); }
                if (ntask < 4) ATR(2 + ntask);
                ntask++;
            }
        }
        fence_async();
        nbar_sync(3, 384);
        if (tid == 0) {
            for (int i = 0; i < NST_G; i++) {
                asm volatile("mbarrier.inval.shared::cta.b64 [%0];" :: "r"(sb + AX_BAR + 16 + 8 * i) : "memory");
                asm volatile("mbarrier.inval.shared::cta.b64 [%0];" :: "r"(sb + AX_EMPTY + 8 * i) : "memory");
                mbar_init(sb + AX_BAR + 16 + 8 * i, 1); mbar_init(sb + AX_EMPTY + 8 * i, 2);
            }
            asm volatile("fence.mbarrier_init.release.cluster;" ::: "memory");
        }
        nbar_sync(3, 384);
        gemm_consumer(smem, out, s_tasks, s_done);
        nbar_sync(4, 384);
        if (tid == 0) {
            __threadfence();
            unsigned old = atomicAdd(&g_auxdone, 1u);
            if (old == NAUX - 1) { g_auxdone = 0; __threadfence(); atomicAdd(&g_epoch, 1u); }
        }
    }
    asm volatile("griddepcontrol.wait;" ::: "memory");
}

extern "C" void kernel_launch(void* const* d_in, const int* in_sizes, int n_in, void* d_out, int out_size) {
    const bf16* x = (const bf16*)d_in[0];
    const bf16* mem0 = (const bf16*)d_in[1];
    const bf16* Wq = (const bf16*)d_in[2];
    const bf16* Wk = (const bf16*)d_in[3];
    const bf16* Wv = (const bf16*)d_in[4];
    const bf16* Wo = (const bf16*)d_in[5];
    const bf16 *A_re = (const bf16*)d_in[8], *A_im = (const bf16*)d_in[9], *B_re = (const bf16*)d_in[10], *B_im = (const bf16*)d_in[11];
    const bf16 *C_re = (const bf16*)d_in[12], *C_im = (const bf16*)d_in[13], *log_dt = (const bf16*)d_in[14], *Dskip = (const bf16*)d_in[15];
    const bf16* gw = (const bf16*)d_in[16];
    bf16* out = (bf16*)d_out;
    cudaStream_t st = cudaStreamPerThread;
    static bool init = false;
    static CUtensorMap xmap, womap, wqmap, wkmap, wvmap;
    static const void* xmap_ptr = nullptr; static const void* womap_ptr = nullptr; static const void* w_ptr[3] = {nullptr, nullptr, nullptr};
    if (!init) {
        cudaFuncSetAttribute(k_chain, cudaFuncAttributeMaxDynamicSharedMemorySize, SM_TOTAL);
        cudaFuncSetAttribute(k_aux, cudaFuncAttributeMaxDynamicSharedMemorySize, AX_TOTAL);
        init = true;
    }
    if (xmap_ptr != (const void*)x || womap_ptr != (const void*)Wo || w_ptr[0] != Wq || w_ptr[1] != Wk || w_ptr[2] != Wv) {
        void* fn = nullptr; cudaDriverEntryPointQueryResult qres;
        cudaGetDriverEntryPoint("cuTensorMapEncodeTiled", &fn, cudaEnableDefault, &qres);
        typedef CUresult (*EncFn)(CUtensorMap*, CUtensorMapDataType, cuuint32_t, void*, const cuuint64_t*, const cuuint64_t*, const cuuint32_t*, const cuuint32_t*,
                                  CUtensorMapInterleave, CUtensorMapSwizzle, CUtensorMapL2promotion, CUtensorMapFloatOOBfill);
        cuuint32_t es[2] = {1, 1};
        {
          cuuint64_t dims[3] = {64, SEQ, 10}; cuuint64_t strides[2] = {DM * 2, 128}; cuuint32_t box[3] = {64, 32, 10}; cuuint32_t es3[3] = {1, 1, 1};
          ((EncFn)fn)(&xmap, CU_TENSOR_MAP_DATA_TYPE_BFLOAT16, 3, (void*)x, dims, strides, box, es3, CU_TENSOR_MAP_INTERLEAVE_NONE, CU_TENSOR_MAP_SWIZZLE_128B,
                      CU_TENSOR_MAP_L2_PROMOTION_L2_128B, CU_TENSOR_MAP_FLOAT_OOB_FILL_NONE); }
        { cuuint64_t dims[2] = {DM, HD}; cuuint64_t strides[1] = {DM * 2}; cuuint32_t box[2] = {64, 64};
          ((EncFn)fn)(&womap, CU_TENSOR_MAP_DATA_TYPE_BFLOAT16, 2, (void*)Wo, dims, strides, box, es, CU_TENSOR_MAP_INTERLEAVE_NONE, CU_TENSOR_MAP_SWIZZLE_128B,
                      CU_TENSOR_MAP_L2_PROMOTION_L2_128B, CU_TENSOR_MAP_FLOAT_OOB_FILL_NONE); }
        { cuuint64_t dims[2] = {HD, DM}; cuuint64_t strides[1] = {HD * 2}; cuuint32_t box[2] = {64, 128};
          const bf16* ws[3] = {Wq, Wk, Wv}; CUtensorMap* ms[3] = {&wqmap, &wkmap, &wvmap};
          for (int i = 0; i < 3; i++)
              ((EncFn)fn)(ms[i], CU_TENSOR_MAP_DATA_TYPE_BFLOAT16, 2, (void*)ws[i], dims, strides, box, es, CU_TENSOR_MAP_INTERLEAVE_NONE, CU_TENSOR_MAP_SWIZZLE_128B,
                          CU_TENSOR_MAP_L2_PROMOTION_L2_128B, CU_TENSOR_MAP_FLOAT_OOB_FILL_NONE); }
        xmap_ptr = (const void*)x; womap_ptr = (const void*)Wo; w_ptr[0] = Wq; w_ptr[1] = Wk; w_ptr[2] = Wv;
    }
    k_chain<<<96, 384, SM_TOTAL, st>>>(xmap, wqmap, wkmap, wvmap, womap, x, mem0);
    {
        cudaLaunchConfig_t cfg = {};
        cfg.gridDim = dim3(NAUX); cfg.blockDim = dim3(384); cfg.dynamicSmemBytes = AX_TOTAL; cfg.stream = st;
        cudaLaunchAttribute at[1];
        at[0].id = cudaLaunchAttributeProgrammaticStreamSerialization; at[0].val.programmaticStreamSerializationAllowed = 1;
        cfg.attrs = at; cfg.numAttrs = 1;
        cudaLaunchKernelEx(&cfg, k_aux, womap, x, A_re, A_im, B_re, B_im, C_re, C_im, log_dt, Dskip, gw, out);
    }
}
```

```cpp
#include <cuda_runtime.h>
#include <cuda_bf16.h>
#include <stdint.h>
#include <cuda.h>

typedef __nv_bfloat16 bf16;

#define SEQ 2048
#define DM 640
#define NH 32
#define DH 128
#define NM 8
#define SEG 32
#define NSEG 64
#define NST 128
#define HD 4096

__device__ bf16  g_b[SEQ * DM];
__device__ float g_g[SEQ];

__device__ __forceinline__ float bf2f(bf16 v) { return __bfloat162float(v); }
__device__ __forceinline__ uint32_t pack_bf16(float lo, float hi) {
    uint32_t r; asm("cvt.rn.bf16x2.f32 %0, %1, %2;" : "=r"(r) : "f"(hi), "f"(lo)); return r;
}
__device__ __forceinline__ uint32_t f2tf32(float x) { uint32_t r; asm("cvt.rna.tf32.f32 %0, %1;" : "=r"(r) : "f"(x)); return r; }
__device__ __forceinline__ void mma_tf32(float (&d)[4], uint32_t a0, uint32_t a1, uint32_t a2, uint32_t a3, uint32_t b0, uint32_t b1) {
    asm volatile("mma.sync.aligned.m16n8k8.row.col.f32.tf32.tf32.f32 {%0,%1,%2,%3}, {%4,%5,%6,%7}, {%8,%9}, {%0,%1,%2,%3};\n"
        : "+f"(d[0]), "+f"(d[1]), "+f"(d[2]), "+f"(d[3]) : "r"(a0), "r"(a1), "r"(a2), "r"(a3), "r"(b0), "r"(b1));
}
__device__ __forceinline__ void mma_bf16(float (&d)[4], uint32_t a0, uint32_t a1, uint32_t a2, uint32_t a3, uint32_t b0, uint32_t b1) {
    asm volatile("mma.sync.aligned.m16n8k16.row.col.f32.bf16.bf16.f32 {%0,%1,%2,%3}, {%4,%5,%6,%7}, {%8,%9}, {%0,%1,%2,%3};\n"
        : "+f"(d[0]), "+f"(d[1]), "+f"(d[2]), "+f"(d[3]) : "r"(a0), "r"(a1), "r"(a2), "r"(a3), "r"(b0), "r"(b1));
}
struct cf { float re, im; };
__device__ __forceinline__ cf cmul(cf a, cf b) { cf r; r.re = a.re * b.re - a.im * b.im; r.im = a.re * b.im + a.im * b.re; return r; }
__device__ __forceinline__ cf csq(cf a) { cf r; r.re = a.re * a.re - a.im * a.im; r.im = 2.f * a.re * a.im; return r; }
__device__ __forceinline__ cf cexpL(float zr, float zi, float L) {
    float e = __expf(zr * L);
    float ang = zi * L;
    float k = rintf(ang * 0.15915494309189535f);
    ang = fmaf(-k, 6.2831854820251465f, ang);
    ang = fmaf(-k, -1.7484555314695172e-07f, ang);
    cf r; r.re = e * __cosf(ang); r.im = e * __sinf(ang); return r;
}

#define SSM_CH 8
#define KC_PITCH 648
#define XS_PAD 128
#define XS_PITCH (XS_PAD + 2048 + 8)
#define YS_PITCH (2048 + 8)
#define KT_LEN (2048 + 48)
struct SsmSmem {
    float Kc[SSM_CH][KC_PITCH];
    bf16  xs[SSM_CH][XS_PITCH];
    union {
        bf16  KT[SSM_CH][2][KT_LEN];
        float st[SSM_CH][NST][8];
    } u;
    bf16  ys[SSM_CH][YS_PITCH];
    uint16_t kidx[2048];
};

__device__ __forceinline__ int kc_index(int l) {
    return l < 256 ? l : (l < 512 ? 256 + ((l - 256) >> 1) : (l < 1024 ? 384 + ((l - 512) >> 2) : 512 + ((l - 1024) >> 3)));
}

__device__ __forceinline__ void ssm_group(unsigned char* smem_raw, int grp, const bf16* __restrict__ x, const bf16* __restrict__ A_re, const bf16* __restrict__ A_im,
        const bf16* __restrict__ B_re, const bf16* __restrict__ B_im, const bf16* __restrict__ C_re, const bf16* __restrict__ C_im,
        const bf16* __restrict__ log_dt, const bf16* __restrict__ Dskip) {
    SsmSmem& S = *reinterpret_cast<SsmSmem*>(smem_raw);
    const int tid = threadIdx.x, w = tid >> 5, lane = tid & 31, g = lane >> 2, t = lane & 3;
    const int d0 = grp * SSM_CH;
    asm volatile("bar.sync 1, 256;" ::: "memory");
    #pragma unroll
    for (int it = 0; it < 8; it++) {
        const int l = tid + 256 * it;
        uint4 v = *reinterpret_cast<const uint4*>(x + (size_t)l * DM + d0);
        const bf16* p = reinterpret_cast<const bf16*>(&v);
        const int lr = (l & ~15) | (15 - (l & 15));
        #pragma unroll
        for (int c = 0; c < 8; c++) S.xs[c][XS_PAD + lr] = p[c];
        S.kidx[l] = (uint16_t)((int)bf2f(__float2bfloat16_rn((float)l)) == 2048 ? 640 : kc_index((int)bf2f(__float2bfloat16_rn((float)l))));
    }
    for (int i = tid; i < SSM_CH * XS_PAD / 2; i += 256) reinterpret_cast<uint32_t*>(&S.xs[i / (XS_PAD / 2)][0])[i % (XS_PAD / 2)] = 0u;
    {
        const int d = d0 + w;
        const float dt = bf2f(__float2bfloat16_rn(expf(bf2f(log_dt[d]))));
        #pragma unroll
        for (int i = 0; i < 4; i++) {
            const int n = lane + 32 * i;
            float zr = dt * bf2f(A_re[d * NST + n]), zi = dt * bf2f(A_im[d * NST + n]);
            cf dB; dB.re = dt * bf2f(B_re[d * NST + n]); dB.im = dt * bf2f(B_im[d * NST + n]);
            cf C; C.re = bf2f(C_re[d * NST + n]); C.im = bf2f(C_im[d * NST + n]);
            cf wv = cmul(C, dB);
            cf u8 = cexpL(zr, zi, 8.f), u128 = cexpL(zr, zi, 128.f);
            float* st = S.u.st[w][n];
            *reinterpret_cast<float4*>(st) = make_float4(zr, zi, wv.re, wv.im);
            *reinterpret_cast<float4*>(st + 4) = make_float4(u8.re, u8.im, u128.re, u128.im);
        }
        __syncwarp();
        float a0a[4] = {0, 0, 0, 0}, a0b[4] = {0, 0, 0, 0}, a1[4] = {0, 0, 0, 0}, a2a[4] = {0, 0, 0, 0}, a2b[4] = {0, 0, 0, 0};
        float k2048 = 0.f;
        const float Lg = (g < 4) ? (512.f + 4.f * g) : (g < 6 ? 1024.f + 8.f * (g - 4) : 1536.f + 8.f * (g - 6));
        #pragma unroll 4
        for (int kk = 0; kk < 32; kk++) {
            const float* st = S.u.st[w][4 * kk + t];
            float4 s0 = *reinterpret_cast<const float4*>(st), s1 = *reinterpret_cast<const float4*>(st + 4);
            cf wv; wv.re = s0.z; wv.im = s0.w;
            cf u8; u8.re = s1.x; u8.im = s1.y;
            cf u128; u128.re = s1.z; u128.im = s1.w;
            cf e1 = cexpL(s0.x, s0.y, (float)g);
            cf e23 = cexpL(s0.x, s0.y, Lg);
            cf e1b = cmul(e1, u8);
            cf e2 = csq(e1);
            cf p = csq(csq(csq(e2)));
            cf f0 = cmul(wv, p), f1 = cmul(f0, u128), f2 = cmul(f1, u128), f3 = cmul(f2, u128);
            uint32_t A00 = f2tf32(f0.re), A01 = f2tf32(f1.re), A02 = f2tf32(-f0.im), A03 = f2tf32(-f1.im);
            uint32_t A10 = f2tf32(f2.re), A11 = f2tf32(f3.re), A12 = f2tf32(-f2.im), A13 = f2tf32(-f3.im);
            mma_tf32(a0a, A00, A01, A02, A03, f2tf32(e1.re), f2tf32(e1.im));
            mma_tf32(a0b, A00, A01, A02, A03, f2tf32(e1b.re), f2tf32(e1b.im));
            mma_tf32(a1, A10, A11, A12, A13, f2tf32(e2.re), f2tf32(e2.im));
            uint32_t E0 = f2tf32(e23.re), E1 = f2tf32(e23.im);
            mma_tf32(a2a, A00, A01, A02, A03, E0, E1);
            mma_tf32(a2b, A10, A11, A12, A13, E0, E1);
            cf e2048 = csq(e23);
            k2048 += wv.re * e2048.re - wv.im * e2048.im;
        }
        k2048 += __shfl_xor_sync(~0u, k2048, 1);
        k2048 += __shfl_xor_sync(~0u, k2048, 2);
        float* Kc = S.Kc[w];
        Kc[16 * g + 2 * t] = a0a[0]; Kc[16 * g + 2 * t + 1] = a0a[1]; Kc[16 * (g + 8) + 2 * t] = a0a[2]; Kc[16 * (g + 8) + 2 * t + 1] = a0a[3];
        Kc[16 * g + 8 + 2 * t] = a0b[0]; Kc[16 * g + 8 + 2 * t + 1] = a0b[1]; Kc[16 * (g + 8) + 8 + 2 * t] = a0b[2]; Kc[16 * (g + 8) + 8 + 2 * t + 1] = a0b[3];
        Kc[256 + 8 * g + 2 * t] = a1[0]; Kc[256 + 8 * g + 2 * t + 1] = a1[1]; Kc[256 + 8 * (g + 8) + 2 * t] = a1[2]; Kc[256 + 8 * (g + 8) + 2 * t + 1] = a1[3];
        #pragma unroll
        for (int mt = 0; mt < 2; mt++) {
            #pragma unroll
            for (int e = 0; e < 4; e++) {
                int A = mt * 16 + g + (e >> 1) * 8, j = 2 * t + (e & 1);
                int Lj = (j < 4) ? 512 + 4 * j : (j < 6 ? 1024 + 8 * (j - 4) : 1536 + 8 * (j - 6));
                Kc[kc_index(Lj + 16 * A)] = mt ? a2b[e] : a2a[e];
            }
        }
        if (lane == 16) Kc[640] = k2048;
    }
    __syncwarp();
    {
        asm volatile("bar.sync 1, 256;" ::: "memory");
        bf16* k0 = S.u.KT[w][0];
        bf16* k1 = S.u.KT[w][1];
        const float* Kc = S.Kc[w];
        #pragma unroll 8
        for (int j = lane; j < 2048; j += 32) {
            const bf16 v = __float2bfloat16_rn(Kc[S.kidx[j]]);
            k0[16 + j] = v;
            k1[15 + j] = v;
        }
        if (lane < 16) { k0[lane] = __float2bfloat16_rn(0.f); if (lane < 15) k1[lane] = __float2bfloat16_rn(0.f); }
        k0[2064 + lane] = __float2bfloat16_rn(0.f); k1[2063 + lane] = __float2bfloat16_rn(0.f);
        __syncwarp();
    }
    {
        float acc[16][4];
        #pragma unroll
        for (int v = 0; v < 16; v++) { acc[v][0] = acc[v][1] = acc[v][2] = acc[v][3] = 0.f; }
        const bf16* kt = (g & 1) ? &S.u.KT[w][0][0] : &S.u.KT[w][1][0];
        const int ibase0 = g + 1 + 2 * t - ((g & 1) ? 0 : 1);
        #pragma unroll 1
        for (int r = 0; r < 8; r++) {
            uint32_t B[16][2];
            #pragma unroll
            for (int v = 0; v < 16; v++) {
                const bf16* p = &S.xs[w][XS_PAD + 16 * (8 * v + g - r) + 2 * t];
                B[v][0] = *reinterpret_cast<const uint32_t*>(p);
                B[v][1] = *reinterpret_cast<const uint32_t*>(p + 8);
            }
            #pragma unroll
            for (int q = 0; q < 16; q++) {
                const int i0 = ibase0 + 16 * r + 128 * q;
                const uint32_t A0 = *reinterpret_cast<const uint32_t*>(kt + i0);
                const uint32_t A1 = *reinterpret_cast<const uint32_t*>(kt + i0 + 8);
                const uint32_t A3 = *reinterpret_cast<const uint32_t*>(kt + i0 + 16);
                #pragma unroll
                for (int v = q; v < 16; v++) mma_bf16(acc[v], A0, A1, A1, A3, B[v - q][0], B[v - q][1]);
            }
        }
        bf16* ys = S.ys[w];
        #pragma unroll
        for (int v = 0; v < 16; v++) {
            const int a = 8 * v + 2 * t;
            ys[16 * a + g] = __float2bfloat16_rn(acc[v][0]); ys[16 * (a + 1) + g] = __float2bfloat16_rn(acc[v][1]);
            ys[16 * a + g + 8] = __float2bfloat16_rn(acc[v][2]); ys[16 * (a + 1) + g + 8] = __float2bfloat16_rn(acc[v][3]);
        }
    }
    asm volatile("bar.sync 1, 256;" ::: "memory");
    {
        float dsk[8];
        #pragma unroll
        for (int c = 0; c < 8; c++) dsk[c] = bf2f(Dskip[d0 + c]);
        #pragma unroll 2
        for (int it = 0; it < 8; it++) {
            const int l = tid + 256 * it;
            const int lr = XS_PAD + ((l & ~15) | (15 - (l & 15)));
            float o[8];
            #pragma unroll
            for (int c = 0; c < 8; c++) o[c] = bf2f(S.ys[c][l]) + bf2f(__float2bfloat16_rn(bf2f(S.xs[c][lr]) * dsk[c]));
            *reinterpret_cast<uint4*>(g_b + (size_t)l * DM + d0) = make_uint4(pack_bf16(o[0], o[1]), pack_bf16(o[2], o[3]), pack_bf16(o[4], o[5]), pack_bf16(o[6], o[7]));
        }
    }
}

__device__ __forceinline__ uint32_t smem_u32(const void* p) { return (uint32_t)__cvta_generic_to_shared(p); }
__device__ __forceinline__ void mbar_init(uint32_t bar, uint32_t cnt) { asm volatile("mbarrier.init.shared::cta.b64 [%0], %1;" :: "r"(bar), "r"(cnt) : "memory"); }
__device__ __forceinline__ void mbar_expect_tx(uint32_t bar, uint32_t bytes) { asm volatile("mbarrier.arrive.expect_tx.shared::cta.b64 _, [%0], %1;" :: "r"(bar), "r"(bytes) : "memory"); }
__device__ __forceinline__ void mbar_arrive(uint32_t bar) { asm volatile("mbarrier.arrive.shared::cta.b64 _, [%0];" :: "r"(bar) : "memory"); }
__device__ __forceinline__ void mbar_wait(uint32_t bar, uint32_t parity) {
    uint32_t ok; int guard = 0;
    do {
        asm volatile("{\n.reg .pred P1;\nmbarrier.test_wait.parity.shared::cta.b64 P1, [%1], %2;\nselp.u32 %0,1,0,P1;\n}" : "=r"(ok) : "r"(bar), "r"(parity) : "memory");
    } while (!ok && ++guard < (1 << 26));
}
__device__ __forceinline__ void mbar_wait_sleep(uint32_t bar, uint32_t parity) {
    uint32_t ok; int guard = 0;
    do {
        asm volatile("{\n.reg .pred P1;\nmbarrier.try_wait.parity.shared::cta.b64 P1, [%1], %2;\nselp.u32 %0,1,0,P1;\n}" : "=r"(ok) : "r"(bar), "r"(parity) : "memory");
    } while (!ok && ++guard < (1 << 22));
}
__device__ __forceinline__ uint32_t mapa(uint32_t addr, uint32_t rank) { uint32_t r; asm volatile("mapa.shared::cluster.u32 %0, %1, %2;" : "=r"(r) : "r"(addr), "r"(rank)); return r; }
__device__ __forceinline__ void st_async4(uint32_t addr, float a, float b, float c, float d, uint32_t bar) {
    asm volatile("st.async.weak.shared::cluster.mbarrier::complete_tx::bytes.v4.f32 [%0], {%1,%2,%3,%4}, [%5];" :: "r"(addr), "f"(a), "f"(b), "f"(c), "f"(d), "r"(bar) : "memory");
}
__device__ __forceinline__ void bulk_s2c(uint32_t dst, uint32_t src, uint32_t bytes, uint32_t bar) {
    asm volatile("cp.async.bulk.shared::cluster.shared::cta.mbarrier::complete_tx::bytes [%0], [%1], %2, [%3];" :: "r"(dst), "r"(src), "r"(bytes), "r"(bar) : "memory");
}
__device__ __forceinline__ void bulk_g2s(uint32_t dst, const void* src, uint32_t bytes, uint32_t bar) {
    asm volatile("cp.async.bulk.shared::cluster.global.mbarrier::complete_tx::bytes [%0], [%1], %2, [%3];" :: "r"(dst), "l"(src), "r"(bytes), "r"(bar) : "memory");
}
__device__ __forceinline__ void bulk_s2g(void* dst, uint32_t src, uint32_t bytes) {
    asm volatile("cp.async.bulk.global.shared::cta.bulk_group [%0], [%1], %2;" :: "l"(dst), "r"(src), "r"(bytes) : "memory");
}
__device__ __forceinline__ void bulk_commit() { asm volatile("cp.async.bulk.commit_group;" ::: "memory"); }
__device__ __forceinline__ void bulk_wait_read0() { asm volatile("cp.async.bulk.wait_group.read 0;" ::: "memory"); }
__device__ __forceinline__ void bulk_wait0() { asm volatile("cp.async.bulk.wait_group 0;" ::: "memory"); }
__device__ __forceinline__ void fence_async() { asm volatile("fence.proxy.async.shared::cta;" ::: "memory"); }
__device__ __forceinline__ void nbar_sync(int id, int n) { asm volatile("bar.sync %0, %1;" :: "r"(id), "r"(n) : "memory"); }
__device__ __forceinline__ void nbar_arrive(int id, int n) { asm volatile("bar.arrive %0, %1;" :: "r"(id), "r"(n) : "memory"); }
__device__ __forceinline__ void cp_async16(uint32_t dst, const void* src) { asm volatile("cp.async.cg.shared.global [%0], [%1], 16;" :: "r"(dst), "l"(src) : "memory"); }
__device__ __forceinline__ void cp_async_wait_all() { asm volatile("cp.async.wait_all;" ::: "memory"); }
__device__ __forceinline__ void ldsm4(uint32_t (&r)[4], uint32_t addr) {
    asm volatile("ldmatrix.sync.aligned.m8n8.x4.shared.b16 {%0,%1,%2,%3}, [%4];" : "=r"(r[0]), "=r"(r[1]), "=r"(r[2]), "=r"(r[3]) : "r"(addr) : "memory");
}
__device__ __forceinline__ void ldsm4t(uint32_t (&r)[4], uint32_t addr) {
    asm volatile("ldmatrix.sync.aligned.m8n8.x4.trans.shared.b16 {%0,%1,%2,%3}, [%4];" : "=r"(r[0]), "=r"(r[1]), "=r"(r[2]), "=r"(r[3]) : "r"(addr) : "memory");
}
__device__ __forceinline__ void stsm2t(uint32_t addr, uint32_t r0, uint32_t r1) {
    asm volatile("stmatrix.sync.aligned.m8n8.x2.trans.shared.b16 [%0], {%1,%2};" :: "r"(addr), "r"(r0), "r"(r1) : "memory");
}
__device__ __forceinline__ uint4 ld_relaxed4(const void* p) { uint4 v; asm volatile("ld.relaxed.gpu.global.v4.u32 {%0,%1,%2,%3}, [%4];" : "=r"(v.x), "=r"(v.y), "=r"(v.z), "=r"(v.w) : "l"(p) : "memory"); return v; }
__device__ __forceinline__ void st_relaxed2(void* p, uint32_t a, uint32_t b) { asm volatile("st.relaxed.gpu.global.v2.u32 [%0], {%1,%2};" :: "l"(p), "r"(a), "r"(b) : "memory"); }
__device__ __forceinline__ void st_relaxed1(void* p, uint32_t a) { asm volatile("st.relaxed.gpu.global.u32 [%0], %1;" :: "l"(p), "r"(a) : "memory"); }
__device__ __forceinline__ unsigned ld_acquire(const unsigned* p) { unsigned v; asm volatile("ld.acquire.gpu.global.u32 %0, [%1];" : "=r"(v) : "l"(p) : "memory"); return v; }
__device__ __forceinline__ float ex2_approx(float x) { float r; asm("ex2.approx.ftz.f32 %0, %1;" : "=f"(r) : "f"(x)); return r; }
__device__ __forceinline__ uint64_t make_desc(uint32_t saddr, uint32_t lbo, uint32_t sbo) {
    return (uint64_t)((saddr & 0x3FFFF) >> 4) | ((uint64_t)((lbo & 0x3FFFF) >> 4) << 16) | ((uint64_t)((sbo & 0x3FFFF) >> 4) << 32) | (1ull << 62);
}
__device__ __forceinline__ void wg_fence() { asm volatile("wgmma.fence.sync.aligned;" ::: "memory"); }
__device__ __forceinline__ void wg_commit() { asm volatile("wgmma.commit_group.sync.aligned;" ::: "memory"); }
__device__ __forceinline__ void wg_wait0() { asm volatile("wgmma.wait_group.sync.aligned 0;" ::: "memory"); }
__device__ __forceinline__ void wgmma_n40_tA(float (&d)[20], uint64_t da, uint64_t db, int scale_d) {
    asm volatile("{\n.reg .pred p;\nsetp.ne.b32 p, %22, 0;\n"
        "wgmma.mma_async.sync.aligned.m64n40k16.f32.bf16.bf16 {%0,%1,%2,%3,%4,%5,%6,%7,%8,%9,%10,%11,%12,%13,%14,%15,%16,%17,%18,%19}, %20, %21, p, 1, 1, 1, 0;\n}\n"
        : "+f"(d[0]), "+f"(d[1]), "+f"(d[2]), "+f"(d[3]), "+f"(d[4]), "+f"(d[5]), "+f"(d[6]), "+f"(d[7]), "+f"(d[8]), "+f"(d[9]),
          "+f"(d[10]), "+f"(d[11]), "+f"(d[12]), "+f"(d[13]), "+f"(d[14]), "+f"(d[15]), "+f"(d[16]), "+f"(d[17]), "+f"(d[18]), "+f"(d[19])
        : "l"(da), "l"(db), "r"(scale_d));
}

#define NRED 80
#define CAL_THR 410u
#define COMM_REGS "40"
#define NPOOL 576
#define RPS 1
__device__ __align__(4096) uint32_t g_pool[(NPOOL + 1) * 1024];
__device__ unsigned g_cls[NPOOL];
__device__ unsigned g_side[96];
__device__ unsigned g_calcnt;
__device__ unsigned g_epoch;
__device__ unsigned g_flag[NSEG][NH];
__device__ __align__(1024) bf16 g_Qimg[NSEG * NH * 2 * 32 * 64];
__device__ __align__(1024) bf16 g_Kimg[NSEG * NH * 2 * 40 * 64];
__device__ __align__(1024) bf16 g_Vimg[NSEG * NH * 2 * 40 * 64];

#define SM_XB    0
#define SM_VT    81920
#define SM_KT    (SM_VT + 20480)
#define SM_QT    (SM_KT + 10240)
#define SM_QS    (SM_QT + 4096)
#define SM_MEMB  (SM_QS + 1024)
#define SM_RED   (SM_MEMB + 10240)
#define SM_SC    (SM_RED + 16384)
#define SM_CRED  (SM_SC + 5120)
#define SM_PB    (SM_CRED + 1024)
#define SM_TRACE (SM_PB + 1024)
#define SM_WO    163840
#define SM_BAR   (SM_WO + 65536)
#define SM_TPM   (SM_BAR + 256)
#define SM_TRD   (SM_TPM + 256)
#define SM_TPUB  (SM_TRD + 16)
#define SM_TGAT  (SM_TPUB + 128)
#define SM_CAL   (SM_TGAT + 64)
#define SM_TOTAL (SM_CAL + 128)
#define B_SC   (SM_BAR + 0)
#define B_V    (SM_BAR + 16)
#define B_P    (SM_BAR + 48)
#define B_X    (SM_BAR + 56)
#define B_EXP  (SM_BAR + 72)

#define TR(ev) do {} while (0)
__device__ __forceinline__ uint32_t tag_of(int s) { return (uint32_t)(((s >> 1) & 1) + 1); }
__device__ __forceinline__ unsigned probe_latency(uint32_t* p, uint32_t zero) {
    uint32_t v, best = 0xffffffffu;
    asm volatile("atom.relaxed.gpu.global.add.u32 %0, [%1], 0;" : "=r"(v) : "l"(p) : "memory");
    #pragma unroll 1
    for (int r = 0; r < 4; r++) {
        uint32_t c0, c1;
        asm volatile("mov.u32 %0, %%clock;" : "=r"(c0) : "r"(v) : "memory");
        asm volatile("atom.relaxed.gpu.global.add.u32 %0, [%1], 0;" : "=r"(v) : "l"(p + ((v + c0) & zero)) : "memory");
        asm volatile("{\n.reg .u32 t;\nand.b32 t, %1, %2;\nmov.u32 %0, %%clock;\nadd.u32 %0, %0, t;\n}" : "=r"(c1) : "r"(v), "r"(zero) : "memory");
        best = min(best, c1 - c0);
    }
    return best;
}
__device__ __forceinline__ void cluster_sync_all() { asm volatile("barrier.cluster.arrive.release.aligned;\nbarrier.cluster.wait.acquire.aligned;" ::: "memory"); }
__device__ __forceinline__ void tma_load_2d(uint32_t dst, const void* map, int c0, int c1, uint32_t bar) {
    asm volatile("cp.async.bulk.tensor.2d.shared::cluster.global.mbarrier::complete_tx::bytes [%0], [%1, {%3, %4}], [%2];"
        :: "r"(dst), "l"(map), "r"(bar), "r"(c0), "r"(c1) : "memory");
}
__device__ __forceinline__ void tma_load_3d(uint32_t dst, const void* map, int c0, int c1, int c2, uint32_t bar) {
    asm volatile("cp.async.bulk.tensor.3d.shared::cluster.global.mbarrier::complete_tx::bytes [%0], [%1, {%3, %4, %5}], [%2];"
        :: "r"(dst), "l"(map), "r"(bar), "r"(c0), "r"(c1), "r"(c2) : "memory");
}
__device__ __forceinline__ void stsm4t(uint32_t addr, uint32_t r0, uint32_t r1, uint32_t r2, uint32_t r3) {
    asm volatile("stmatrix.sync.aligned.m8n8.x4.trans.shared.b16 [%0], {%1,%2,%3,%4};" :: "r"(addr), "r"(r0), "r"(r1), "r"(r2), "r"(r3) : "memory");
}
__device__ __forceinline__ void wgmma_n32_rs(float (&d)[16], const uint32_t (&a)[4], uint64_t db, int scale_d) {
    asm volatile("{\n.reg .pred p;\nsetp.ne.b32 p, %21, 0;\n"
        "wgmma.mma_async.sync.aligned.m64n32k16.f32.bf16.bf16 {%0,%1,%2,%3,%4,%5,%6,%7,%8,%9,%10,%11,%12,%13,%14,%15}, {%16,%17,%18,%19}, %20, p, 1, 1, 0;\n}\n"
        : "+f"(d[0]), "+f"(d[1]), "+f"(d[2]), "+f"(d[3]), "+f"(d[4]), "+f"(d[5]), "+f"(d[6]), "+f"(d[7]),
          "+f"(d[8]), "+f"(d[9]), "+f"(d[10]), "+f"(d[11]), "+f"(d[12]), "+f"(d[13]), "+f"(d[14]), "+f"(d[15])
        : "r"(a[0]), "r"(a[1]), "r"(a[2]), "r"(a[3]), "l"(db), "r"(scale_d));
}

__device__ __forceinline__ void st_async4u(uint32_t addr, uint4 v, uint32_t bar) {
    asm volatile("st.async.weak.shared::cluster.mbarrier::complete_tx::bytes.v4.u32 [%0], {%1,%2,%3,%4}, [%5];" :: "r"(addr), "r"(v.x), "r"(v.y), "r"(v.z), "r"(v.w), "r"(bar) : "memory");
}
__device__ __forceinline__ void export_issue(uint32_t sb, int s, int h, uint32_t rank) {
    const size_t img = (size_t)(s * NH + h) * 2;
    const int sl = s & 1;
    if (rank == 2) {
        bulk_s2g(g_Vimg + img * 2560, sb + SM_VT + sl * 10240, 5120);
        bulk_s2g(g_Vimg + (img + 1) * 2560, sb + SM_VT + sl * 10240 + 5120, 5120);
    } else {
        bulk_s2g(g_Qimg + (img + rank) * 2048, sb + SM_QT, 4096);
        bulk_s2g(g_Kimg + (img + rank) * 2560, sb + SM_KT + sl * 5120, 5120);
    }
    bulk_commit();
    bulk_wait_read0();
    mbar_arrive(sb + B_EXP);
}
__device__ __forceinline__ void export_signal(int s, int h) {
    bulk_wait0();
    asm volatile("fence.proxy.async;" ::: "memory");
    __threadfence();
    atomicAdd(&g_flag[s][h], 1u);
}

__device__ __forceinline__ void score_tile(uint32_t sb, int sl, int nt, int lane, uint32_t rank) {
    float sc[4] = {0, 0, 0, 0}, sd[4] = {0, 0, 0, 0};
    const int r = lane & 7;
    uint32_t qa[2][4], kb[2][4];
    #pragma unroll
    for (int j = 0; j < 2; j++) {
        const int chunk = (lane >> 3) + 4 * j;
        ldsm4(kb[j], sb + SM_KT + sl * 5120 + (8 * nt + r) * 128 + ((chunk ^ r) << 4));
        ldsm4(qa[j], sb + SM_QS + r * 128 + ((chunk ^ r) << 4));
    }
    mma_bf16(sc, qa[0][0], 0u, qa[0][1], 0u, kb[0][0], kb[0][1]);
    mma_bf16(sd, qa[1][0], 0u, qa[1][1], 0u, kb[1][0], kb[1][1]);
    mma_bf16(sc, qa[0][2], 0u, qa[0][3], 0u, kb[0][2], kb[0][3]);
    mma_bf16(sd, qa[1][2], 0u, qa[1][3], 0u, kb[1][2], kb[1][3]);
    sc[0] += sd[0]; sc[1] += sd[1];
    const float o0 = __shfl_down_sync(~0u, sc[0], 1), o1 = __shfl_down_sync(~0u, sc[1], 1);
    if ((lane & 1) == 0) {
        const uint32_t a = SM_SC + sl * 2560 + rank * 1280 + ((lane >> 2) * 40 + 8 * nt + 2 * (lane & 3)) * 4;
        const uint32_t bo = B_SC + 8 * sl;
        { const uint32_t rb = mapa(sb, 2); st_async4(rb + a, sc[0], sc[1], o0, o1, rb + bo); }
        { const uint32_t rb = mapa(sb, rank ^ 1); st_async4(rb + a, sc[0], sc[1], o0, o1, rb + bo); }
        asm volatile("st.shared.v4.f32 [%0], {%1,%2,%3,%4};" :: "r"(sb + a), "f"(sc[0]), "f"(sc[1]), "f"(o0), "f"(o1) : "memory");
    }
    __syncwarp();
    if (lane == 0) mbar_arrive(sb + B_SC + 8 * sl);
}
__device__ __forceinline__ void wgmma_n40_rs(float (&d)[20], const uint32_t (&a)[4], uint64_t db, int scale_d) {
    asm volatile("{\n.reg .pred p;\nsetp.ne.b32 p, %25, 0;\n"
        "wgmma.mma_async.sync.aligned.m64n40k16.f32.bf16.bf16 {%0,%1,%2,%3,%4,%5,%6,%7,%8,%9,%10,%11,%12,%13,%14,%15,%16,%17,%18,%19}, {%20,%21,%22,%23}, %24, p, 1, 1, 0;\n}\n"
        : "+f"(d[0]), "+f"(d[1]), "+f"(d[2]), "+f"(d[3]), "+f"(d[4]), "+f"(d[5]), "+f"(d[6]), "+f"(d[7]), "+f"(d[8]), "+f"(d[9]),
          "+f"(d[10]), "+f"(d[11]), "+f"(d[12]), "+f"(d[13]), "+f"(d[14]), "+f"(d[15]), "+f"(d[16]), "+f"(d[17]), "+f"(d[18]), "+f"(d[19])
        : "r"(a[0]), "r"(a[1]), "r"(a[2]), "r"(a[3]), "l"(db), "r"(scale_d));
}
__device__ __forceinline__ void pu_mma(float (&o)[4], const float (&u)[20], const uint32_t (&pb)[5]) {
    float o2[4] = {0, 0, 0, 0};
    o[0] = o[1] = o[2] = o[3] = 0.f;
    mma_bf16(o, pack_bf16(u[0], u[1]), pack_bf16(u[2], u[3]), pack_bf16(u[4], u[5]), pack_bf16(u[6], u[7]), pb[0], pb[1]);
    mma_bf16(o2, pack_bf16(u[8], u[9]), pack_bf16(u[10], u[11]), pack_bf16(u[12], u[13]), pack_bf16(u[14], u[15]), pb[2], pb[3]);
    mma_bf16(o, pack_bf16(u[16], u[17]), pack_bf16(u[18], u[19]), 0u, 0u, pb[4], 0u);
    o[0] += o2[0]; o[1] += o2[1]; o[2] += o2[2]; o[3] += o2[3];
}
__device__ __forceinline__ void pu_store(const float (&o)[4], float2 inv, uint2 off, int lane, uint32_t tg) {
    unsigned char* pool = reinterpret_cast<unsigned char*>(g_pool) + lane * 8;
    st_relaxed2(pool + off.x, (__float_as_uint(o[0] * inv.x) & ~3u) | tg, (__float_as_uint(o[1] * inv.y) & ~3u) | tg);
    st_relaxed2(pool + off.y, (__float_as_uint(o[2] * inv.x) & ~3u) | tg, (__float_as_uint(o[3] * inv.y) & ~3u) | tg);
}
__device__ __forceinline__ float rcp_approx(float x) { float r; asm("rcp.approx.ftz.f32 %0, %1;" : "=f"(r) : "f"(x)); return r; }
template <int NT>
__device__ __forceinline__ void u_pass(unsigned char* smem, uint32_t sb, int s, uint32_t rank, int wg, int warp, int lane) {
    const int sl = s & 1;
#define NRS_V 6
    constexpr int NRS = NRS_V;
    uint32_t wa[NRS][4];
    {
        const int mi = lane >> 3, chunk = 2 * warp + (mi & 1);
        #pragma unroll
        for (int ks = 0; ks < NRS; ks++) {
            const int row = 16 * ks + (mi >> 1) * 8 + (lane & 7);
            ldsm4t(wa[ks], sb + SM_WO + (2 * wg) * 16384 + row * 128 + ((chunk ^ (row & 7)) << 4));
        }
    }
    if (rank < 2) { mbar_wait(sb + B_V + 8 * sl, (s >> 1) & 1); fence_async(); }
    if (wg == 0 && warp == 0) TR(4);
    float U0[20];
    wg_fence();
    #pragma unroll
    for (int ks = 0; ks < NRS; ks++)
        wgmma_n40_rs(U0, wa[ks], make_desc(sb + SM_VT + sl * 10240 + (ks >> 2) * 5120 + (ks & 3) * 32, 16, 1024), ks > 0);
    #pragma unroll
    for (int ks = NRS; ks < 8; ks++)
        wgmma_n40_tA(U0, make_desc(sb + SM_WO + (2 * wg) * 16384 + ks * 2048, 1024, 1024),
                     make_desc(sb + SM_VT + sl * 10240 + (ks >> 2) * 5120 + (ks & 3) * 32, 16, 1024), 1);
    wg_commit();
    const uint32_t tg = tag_of(s);
    uint32_t pb[5];
    float sm[4], sm2[4];
    auto get_p = [&]() {
        nbar_sync(9, 288);
        const uint32_t* pbs = reinterpret_cast<const uint32_t*>(smem + SM_PB);
        #pragma unroll
        for (int q = 0; q < 5; q++) pb[q] = pbs[q * 32 + lane];
        sm[0] = sm[1] = sm[2] = sm[3] = 0.f; sm2[0] = sm2[1] = sm2[2] = sm2[3] = 0.f;
        const uint32_t one = 0x3f803f80u;
        mma_bf16(sm, one, one, one, one, pb[0], pb[1]);
        mma_bf16(sm2, one, one, one, one, pb[2], pb[3]);
        mma_bf16(sm, one, one, 0u, 0u, pb[4], 0u);
    };
    const uint2* tpm = reinterpret_cast<const uint2*>(smem + SM_TPM) + (sl * 4 + 2 * wg) * 4 + warp;
    if (NT == 2) {
        wg_wait0();
        float U1[20];
        wg_fence();
        #pragma unroll
        for (int ks = 0; ks < 8; ks++)
            wgmma_n40_tA(U1, make_desc(sb + SM_WO + (2 * wg + 1) * 16384 + ks * 2048, 1024, 1024),
                         make_desc(sb + SM_VT + sl * 10240 + (ks >> 2) * 5120 + (ks & 3) * 32, 16, 1024), ks > 0);
        wg_commit();
        const uint2 off0 = tpm[0], off1 = tpm[4];
        get_p();
        float o0[4], o1[4];
        pu_mma(o0, U0, pb);
        wg_wait0();
        pu_mma(o1, U1, pb);
        const float2 inv = make_float2(rcp_approx(sm[0] + sm2[0]), rcp_approx(sm[1] + sm2[1]));
        if (wg == 0 && warp == 0) TR(8);
        pu_store(o0, inv, off0, lane, tg);
        pu_store(o1, inv, off1, lane, tg);
        if (wg == 0 && warp == 0) TR(6);
    } else {
        const uint2 off0 = tpm[0];
        wg_wait0();
        get_p();
        float o0[4];
        pu_mma(o0, U0, pb);
        const float2 inv = make_float2(rcp_approx(sm[0] + sm2[0]), rcp_approx(sm[1] + sm2[1]));
        pu_store(o0, inv, off0, lane, tg);
    }
}

__global__ void __cluster_dims__(3, 1, 1) __launch_bounds__(384, 1)
k_chain(const __grid_constant__ CUtensorMap xmap, const __grid_constant__ CUtensorMap wqmap, const __grid_constant__ CUtensorMap wkmap,
        const __grid_constant__ CUtensorMap wvmap, const __grid_constant__ CUtensorMap womap, const bf16* __restrict__ xptr, const bf16* __restrict__ mem0) {
    extern __shared__ __align__(1024) unsigned char smem[];
    const uint32_t sb = smem_u32(smem);
    const int tid = threadIdx.x, lane = tid & 31;
    const int wg = __shfl_sync(~0u, tid >> 7, 0), warp = __shfl_sync(~0u, (tid >> 5) & 3, 0);
    uint32_t rank; asm volatile("mov.u32 %0, %%cluster_ctarank;" : "=r"(rank));
    const int cta = blockIdx.x, h = cta / 3;
    asm volatile("griddepcontrol.launch_dependents;");
    if (tid == 0) {
        for (int i = 0; i < 2; i++) { mbar_init(sb + B_SC + 8 * i, rank < 2 ? 6 : 1); mbar_init(sb + B_V + 8 * i, 1); mbar_init(sb + B_X + 8 * i, 1); }
        mbar_init(sb + B_P, 1); mbar_init(sb + B_EXP, 1);
        asm volatile("fence.mbarrier_init.release.cluster;" ::: "memory");
    }
    if (tid < 80) asm volatile("prefetch.global.L2 [%0];" :: "l"(mem0 + tid * 64));
    if (h < 2) { for (int i = tid; i < 320; i += 384) asm volatile("prefetch.global.L2 [%0];" :: "l"(xptr + (size_t)h * 32 * DM + i * 64)); }
    {
        uint4* z = reinterpret_cast<uint4*>(g_pool + (size_t)cta * 6 * 1024);
        #pragma unroll
        for (int q = 0; q < 4; q++) z[tid + 384 * q] = make_uint4(0, 0, 0, 0);
        __threadfence();
    }
    __syncthreads();
    if (tid == 0) {
        const int ntile = (rank == 2) ? 4 : 3;
        const int tile0 = (rank == 2) ? 0 : (rank == 0 ? 4 : 7);
        mbar_expect_tx(sb + B_P, 163840 + ntile * 16384);
        const void* m0 = (rank == 2) ? &wvmap : &wqmap;
        const void* m1 = (rank == 2) ? &wvmap : &wkmap;
        const int c0 = h * DH + (rank == 1 ? 64 : 0), c1 = h * DH + (rank == 0 ? 0 : 64);
        for (int b = 0; b < 5; b++) {
            tma_load_2d(sb + b * 16384, m0, c0, b * 128, sb + B_P);
            tma_load_2d(sb + 81920 + b * 16384, m1, c1, b * 128, sb + B_P);
        }
        for (int lt = 0; lt < ntile; lt++) {
            tma_load_2d(sb + SM_WO + lt * 16384, &womap, (tile0 + lt) * 64, h * DH, sb + B_P);
            tma_load_2d(sb + SM_WO + lt * 16384 + 8192, &womap, (tile0 + lt) * 64, h * DH + 64, sb + B_P);
        }
    }
    {
        const int w12 = tid >> 5;
        if (lane == 0 && w12 >= 1 && w12 < 8) {
            const int i = w12 - 1;
            uint32_t* pp = (i < 6) ? g_pool + (size_t)(cta * 6 + i) * 1024 + 512 : g_pool + (size_t)NPOOL * 1024 + (cta & 31) * 32 + (cta >> 5) * 8;
            const unsigned lat = probe_latency(pp, blockIdx.y);
            if (i < 6) g_cls[cta * 6 + i] = lat > CAL_THR ? 1u : 0u; else g_side[cta] = lat > CAL_THR ? 1u : 0u;
            __threadfence();
            atomicAdd(&g_calcnt, 1u);
        }
        __syncwarp();
    }
    {
        const int tile0 = (rank == 2) ? 0 : (rank == 0 ? 4 : 7);
        if (wg == 2) {
            const int ct = tid & 127;
            if (ct == 0) {
                const unsigned target = (*reinterpret_cast<volatile unsigned*>(&g_epoch) + 1u) * (96u * 7u);
                int guard = 0;
                while ((int)(ld_acquire(&g_calcnt) - target) < 0 && ++guard < (1 << 22)) {}
            }
            nbar_sync(4, 128);
            uint32_t* bm = reinterpret_cast<uint32_t*>(smem + SM_CAL);
            {
                unsigned v[5];
                #pragma unroll
                for (int q = 0; q < 5; q++) { const int b = ct + 128 * q; v[q] = (b < NPOOL) ? (__ldcg(&g_cls[b]) ^ __ldcg(&g_side[b / 6])) : 0u; }
                const unsigned sv = (ct < 96) ? __ldcg(&g_side[ct]) : 0u;
                #pragma unroll
                for (int q = 0; q < 5; q++) { const unsigned m = __ballot_sync(~0u, v[q] & 1u); if (lane == 0 && q * 4 + warp < 18) bm[q * 4 + warp] = m; }
                const unsigned m = __ballot_sync(~0u, sv & 1u);
                if (lane == 0 && warp < 3) bm[18 + warp] = m;
            }
            nbar_sync(4, 128);
            int nblk1 = 0;
            for (int i = 0; i < 18; i++) nblk1 += __popc(bm[i]);
            const unsigned red_last = (1u << (NRED - 64)) - 1u;
            const int nred1 = __popc(bm[18]) + __popc(bm[19]) + __popc(bm[20] & red_last);
            auto side_of = [&](int c) -> int { return (bm[18 + (c >> 5)] >> (c & 31)) & 1; };
            auto rank_of = [&](int c) -> int {
                int ones = 0;
                for (int i = 0; i < (c >> 5); i++) ones += __popc(bm[18 + i]);
                ones += __popc(bm[18 + (c >> 5)] & ((1u << (c & 31)) - 1u));
                return side_of(c) ? ones : c - ones;
            };
            auto nth = [&](int side, int idx) -> uint32_t {
                for (int i = 0; i < 18; i++) {
                    const unsigned m = side ? bm[i] : ~bm[i];
                    const int n = __popc(m);
                    if (idx < n) return (uint32_t)(i * 32 + __fns(m, 0, idx + 1));
                    idx -= n;
                }
                return 0u;
            };
            auto phys = [&](int side, int idx) -> uint32_t {
                const int c = side ? nblk1 : NPOOL - nblk1;
                return (idx < c) ? nth(side, idx) : nth(side ^ 1, (NPOOL - c) - 1 - (idx - c));
            };
            const int e = ct;
            if (e < 64) {
                const int slot = e >> 5, lt = (e >> 3) & 3, w = (e >> 1) & 3, hf = e & 1;
                const int tile = min(tile0 + lt, 9);
                const int r = 2 * (4 * tile + w) + hf;
                reinterpret_cast<uint32_t*>(smem + SM_TPM)[e] = phys(side_of(r), 4 * rank_of(r) + slot * 2 + (h >> 4)) * 4096u + (h & 15) * 256u;
            } else if (e < 68) {
                const int i = e - 64;
                reinterpret_cast<uint32_t*>(smem + SM_TRD)[i] = (cta < NRED) ? phys(side_of(cta), 4 * rank_of(cta) + i) * 4096u : 0u;
            } else if (e < 100) {
                const int i = e - 68, slot = i >> 3, rep = i & 7, side = (rep / RPS) & 1;
                reinterpret_cast<uint32_t*>(smem + SM_TPUB)[i] = phys(side, 4 * (side ? nred1 : NRED - nred1) + (slot * RPS + (rep % RPS)) * 3 + (cta >> 5)) * 4096u + (cta & 31) * 128u;
            } else if (e < 112) {
                const int i = e - 100, slot = i / 3, b = i % 3, side = side_of(cta);
                reinterpret_cast<uint32_t*>(smem + SM_TGAT)[slot * 4 + b] = phys(side, 4 * (side ? nred1 : NRED - nred1) + (slot * RPS + (h % RPS)) * 3 + b) * 4096u;
            }
        }
    }
    __syncthreads();
    mbar_wait_sleep(sb + B_P, 0);

    if (wg == 2) {
        asm volatile("setmaxnreg.dec.sync.aligned.u32 " COMM_REGS ";");
        const int ct = tid & 127;
        nbar_sync(5, 384);
        for (int c = ct; c < 640; c += 128) {
            int ks = c >> 4, hf = (c >> 3) & 1, r = c & 7;
            *reinterpret_cast<uint4*>(smem + SM_MEMB + c * 16) = *reinterpret_cast<const uint4*>(mem0 + r * DM + ks * 16 + hf * 8);
        }
        if (ct == 0) {
            for (int sg = 0; sg < 2; sg++) {
                mbar_expect_tx(sb + B_X + 8 * sg, 40960);
                tma_load_3d(sb + SM_XB + sg * 40960, &xmap, 0, sg * 32, 0, sb + B_X + 8 * sg);
            }
            mbar_expect_tx(sb + B_SC, rank < 2 ? 1280 : 2560);
            if (rank < 2) mbar_expect_tx(sb + B_V, 8192 + 2048);
        }
        nbar_sync(5, 384);
        cluster_sync_all();
        unsigned char* const pool = reinterpret_cast<unsigned char*>(g_pool);
        for (int s = 0; s < NSEG - 1; s++) {
            if (warp == 1) nbar_sync(12, 288);
            if (warp == 0) {
                const int g = lane >> 2, t = lane & 3;
                mbar_wait(sb + B_SC + 8 * (s & 1), (s >> 1) & 1);
                TR(5);
                const uint32_t sa = sb + SM_SC + (s & 1) * 2560 + (g * 40 + 2 * t) * 4;
                float v[5][2], u[5][2];
                #pragma unroll
                for (int q = 0; q < 5; q++) {
                    asm volatile("ld.shared.v2.f32 {%0,%1}, [%2];" : "=f"(v[q][0]), "=f"(v[q][1]) : "r"(sa + 32 * q) : "memory");
                    asm volatile("ld.shared.v2.f32 {%0,%1}, [%2];" : "=f"(u[q][0]), "=f"(u[q][1]) : "r"(sa + 1280 + 32 * q) : "memory");
                }
                float mx = -3.0e38f;
                #pragma unroll
                for (int q = 0; q < 5; q++) {
                    v[q][0] += u[q][0]; v[q][1] += u[q][1];
                    mx = fmaxf(mx, fmaxf(v[q][0], v[q][1]));
                }
                mx = fmaxf(mx, __shfl_xor_sync(~0u, mx, 1));
                mx = fmaxf(mx, __shfl_xor_sync(~0u, mx, 2));
                const float sc2 = 0.08838834764831845f * 1.4426950408889634f;
                const float mxs = mx * sc2;
                uint32_t* pbs = reinterpret_cast<uint32_t*>(smem + SM_PB);
                #pragma unroll
                for (int q = 0; q < 5; q++) {
                    const float e0 = ex2_approx(fmaf(v[q][0], sc2, -mxs)), e1 = ex2_approx(fmaf(v[q][1], sc2, -mxs));
                    pbs[q * 32 + lane] = pack_bf16(e0, e1);
                }
                __syncwarp();
                TR(0);
                nbar_arrive(9, 288);
            } else if (warp == 1 && lane == 0) {
                if (s + 1 < NSEG - 1) {
                    mbar_expect_tx(sb + B_SC + 8 * ((s + 1) & 1), rank < 2 ? 1280 : 2560);
                    if (rank < 2) mbar_expect_tx(sb + B_V + 8 * ((s + 1) & 1), 8192 + 2048);
                }
                if (s + 2 < NSEG) {
                    mbar_expect_tx(sb + B_X + 8 * (s & 1), 40960);
                    tma_load_3d(sb + SM_XB + (s & 1) * 40960, &xmap, 0, (s + 2) * 32, 0, sb + B_X + 8 * (s & 1));
                }
                export_issue(sb, s, h, rank);
                if (s >= NSEG - 4) export_signal(s, h);
            }
            __syncwarp();
            nbar_sync(3, 384);
            const uint32_t tg = tag_of(s);
            if (cta < NRED) {
                const unsigned char* base = pool + reinterpret_cast<const uint32_t*>(smem + SM_TRD)[(s & 1) * 2 + (warp >> 1)] + (warp & 1) * 2048 + lane * 16;
                uint4 v[4]; int guard = 0;
                #pragma unroll
                for (int j = 0; j < 4; j++) v[j] = make_uint4(0, 0, 0, 0);
                uint32_t pend = 0xF;
                do {
                    #pragma unroll
                    for (int j = 0; j < 4; j++) if (pend & (1u << j)) v[j] = ld_relaxed4(base + j * 512);
                    #pragma unroll
                    for (int j = 0; j < 4; j++)
                        if (((v[j].x & 3) == tg) && ((v[j].y & 3) == tg) && ((v[j].z & 3) == tg) && ((v[j].w & 3) == tg)) pend &= ~(1u << j);
                } while (__any_sync(~0u, pend != 0) && ++guard < (1 << 20));
                if (warp == 0) TR(9);
                float a0 = 0, a1 = 0, a2 = 0, a3 = 0;
                #pragma unroll
                for (int j = 0; j < 4; j++) { a0 += __uint_as_float(v[j].x); a1 += __uint_as_float(v[j].y); a2 += __uint_as_float(v[j].z); a3 += __uint_as_float(v[j].w); }
                a0 += __shfl_xor_sync(~0u, a0, 16); a1 += __shfl_xor_sync(~0u, a1, 16); a2 += __shfl_xor_sync(~0u, a2, 16); a3 += __shfl_xor_sync(~0u, a3, 16);
                float* cr = reinterpret_cast<float*>(smem + SM_CRED);
                if (lane < 16) *reinterpret_cast<float4*>(cr + warp * 64 + lane * 4) = make_float4(a0, a1, a2, a3);
                nbar_sync(4, 128);
                {
                    int rho = lane >> 2, pp = lane & 3;
                    int i0 = ((2 * pp) * 4 + (rho >> 1)) * 2 + (rho & 1), i1 = i0 + 8;
                    uint32_t wv = pack_bf16((cr[i0] + cr[64 + i0]) + (cr[128 + i0] + cr[192 + i0]), (cr[i1] + cr[64 + i1]) + (cr[128 + i1] + cr[192 + i1]));
                    if (wv == 0) wv = 0x8000u;
                    if (warp == 0) TR(10);
                    const uint32_t* tp = reinterpret_cast<const uint32_t*>(smem + SM_TPUB) + warp;
                    if (warp < 2 * RPS) st_relaxed1(pool + tp[((s + 1) & 3) * 8] + lane * 4, wv);
                    if (RPS == 4) st_relaxed1(pool + tp[((s + 1) & 3) * 8 + 4] + lane * 4, wv);
                    if (warp < 2 * RPS) st_relaxed1(pool + tp[(s & 3) * 8] + lane * 4, 0u);
                    if (RPS == 4) st_relaxed1(pool + tp[(s & 3) * 8 + 4] + lane * 4, 0u);
                }
            }
            {
                const int c0 = warp * 160 + lane;
                const uint32_t* tg3 = reinterpret_cast<const uint32_t*>(smem + SM_TGAT) + ((s + 1) & 3) * 4;
                const uint32_t g0 = tg3[0], g1 = tg3[1], g2 = tg3[2];
                uint4 v[5]; int guard = 0;
                #pragma unroll
                for (int j = 0; j < 5; j++) v[j] = make_uint4(0, 0, 0, 0);
                uint32_t pend = 0x1F;
                do {
                    #pragma unroll
                    for (int j = 0; j < 5; j++) {
                        const int c = c0 + 32 * j;
                        if (pend & (1u << j)) v[j] = ld_relaxed4(pool + ((c >> 8) == 0 ? g0 : ((c >> 8) == 1 ? g1 : g2)) + (c & 255) * 16);
                    }
                    #pragma unroll
                    for (int j = 0; j < 5; j++) if (v[j].x && v[j].y && v[j].z && v[j].w) pend &= ~(1u << j);
                } while (__any_sync(~0u, pend != 0) && ++guard < (1 << 20));
                #pragma unroll
                for (int j = 0; j < 5; j++) *reinterpret_cast<uint4*>(smem + SM_MEMB + (c0 + 32 * j) * 16) = v[j];
                if (warp == 0) TR(11);
                if (warp == 3) TR(12);
                nbar_arrive(warp < 2 ? 7 + warp : 8 + warp, 160);
            }
            if (warp == 1 && lane == 0 && s < NSEG - 4) export_signal(s, h);
            __syncwarp();
        }
        if (warp == 1) { nbar_sync(12, 288); if (lane == 0) { export_issue(sb, NSEG - 1, h, rank); export_signal(NSEG - 1, h); } }
        __syncwarp();
        nbar_sync(3, 384);
        __syncwarp();
        cluster_sync_all();
    } else {
        asm volatile("setmaxnreg.inc.sync.aligned.u32 232;");
        const int wtid = tid & 127;
        const int cw = wg * 4 + warp;
        uint32_t areg[2][20][4];
        #pragma unroll
        for (int mt = 0; mt < 2; mt++)
            #pragma unroll
            for (int kk = 0; kk < 20; kk++) {
                int mi = lane >> 3;
                int row = 16 * (20 * wg + kk) + (mi >> 1) * 8 + (lane & 7);
                int chunk = 2 * warp + (mi & 1);
                ldsm4t(areg[mt][kk], sb + mt * 81920 + row * 128 + ((chunk ^ (row & 7)) << 4));
            }
        nbar_sync(5, 384);
        nbar_sync(5, 384);
        cluster_sync_all();

        for (int s = -1; s < NSEG; s++) {
            const int sl = s & 1;
            if (s >= 0) {
            if (s > 0) nbar_sync(7 + 3 * wg, 160);
            float fin[4];
            {
                float acc[2][2][4];
                #pragma unroll
                for (int i = 0; i < 2; i++)
                    #pragma unroll
                    for (int j = 0; j < 2; j++) { acc[i][j][0] = acc[i][j][1] = acc[i][j][2] = acc[i][j][3] = 0.f; }
                uint32_t b[3][4];
                const uint32_t mb = sb + SM_MEMB + (20 * wg) * 256 + lane * 16;
                ldsm4(b[0], mb); ldsm4(b[1], mb + 512);
                #pragma unroll
                for (int kp = 0; kp < 10; kp++) {
                    if (kp == 3 && s > 0) nbar_sync(8 + 3 * wg, 160);
                    if (kp + 2 < 10) ldsm4(b[(kp + 2) % 3], mb + (kp + 2) * 512);
                    const uint32_t (&bb)[4] = b[kp % 3];
                    mma_bf16(acc[0][0], areg[0][2 * kp][0], areg[0][2 * kp][1], areg[0][2 * kp][2], areg[0][2 * kp][3], bb[0], bb[1]);
                    mma_bf16(acc[1][0], areg[1][2 * kp][0], areg[1][2 * kp][1], areg[1][2 * kp][2], areg[1][2 * kp][3], bb[0], bb[1]);
                    mma_bf16(acc[0][1], areg[0][2 * kp + 1][0], areg[0][2 * kp + 1][1], areg[0][2 * kp + 1][2], areg[0][2 * kp + 1][3], bb[2], bb[3]);
                    mma_bf16(acc[1][1], areg[1][2 * kp + 1][0], areg[1][2 * kp + 1][1], areg[1][2 * kp + 1][2], areg[1][2 * kp + 1][3], bb[2], bb[3]);
                }
                float4* red = reinterpret_cast<float4*>(smem + SM_RED);
                float m0[4], m1[4];
                #pragma unroll
                for (int i = 0; i < 4; i++) { m0[i] = acc[0][0][i] + acc[0][1][i]; m1[i] = acc[1][0][i] + acc[1][1][i]; }
                red[(wg ^ 1) * 128 + wtid] = wg == 0 ? make_float4(m1[0], m1[1], m1[2], m1[3]) : make_float4(m0[0], m0[1], m0[2], m0[3]);
                nbar_sync(1, 256);
                float4 r = red[wg * 128 + wtid];
                fin[0] = (wg == 0 ? m0[0] : m1[0]) + r.x; fin[1] = (wg == 0 ? m0[1] : m1[1]) + r.y;
                fin[2] = (wg == 0 ? m0[2] : m1[2]) + r.z; fin[3] = (wg == 0 ? m0[3] : m1[3]) + r.w;
            }
            if (cw == 0) TR(1);
            {
                uint32_t p0 = pack_bf16(fin[0], fin[1]), p1 = pack_bf16(fin[2], fin[3]);
                const uint32_t doff = (rank == 2) ? SM_VT + sl * 10240 + wg * 5120 : (wg == 0 ? SM_QS : SM_KT + sl * 5120);
                const int r = lane & 7, chunk = 2 * warp + ((lane >> 3) & 1);
                const uint32_t coff = doff + r * 128 + ((chunk ^ r) << 4);
                stsm2t(sb + coff, p0, p1);
                if (rank == 2 && s < NSEG - 1) {
                    __syncwarp();
                    const uint4 v = *reinterpret_cast<const uint4*>(smem + coff);
                    const uint32_t rb = mapa(sb, lane >> 4);
                    st_async4u(rb + coff, v, rb + B_V + 8 * sl);
                }
            }
            fence_async();
            nbar_sync(1, 256);
            nbar_arrive(12, 288);
            if (cw == 0) TR(2);
            if (rank < 2 && s < NSEG - 1) {
                if (wg == 1) score_tile(sb, sl, 1 + warp, lane, rank);
                else if (warp == 0) score_tile(sb, sl, 0, lane, rank);
            }
            if (s == NSEG - 1) break;
            if (cw == 0) TR(3);
            if (wg == 0 || rank == 2) u_pass<2>(smem, sb, s, rank, wg, warp, lane);
            else                      u_pass<1>(smem, sb, s, rank, wg, warp, lane);
            if (cw == 0) TR(7);
            nbar_arrive(3, 384);
            }
            {
                const int sn = s + 1, sln = sn & 1;
                mbar_wait(sb + B_X + 8 * sln, (sn >> 1) & 1);
                float acc[2][16];
                wg_fence();
                #pragma unroll
                for (int mt = 0; mt < 2; mt++)
                    #pragma unroll
                    for (int kk = 0; kk < 20; kk++) {
                        uint64_t db = make_desc(sb + SM_XB + sln * 40960 + (5 * wg + (kk >> 2)) * 4096 + (kk & 3) * 32, 16, 1024);
                        wgmma_n32_rs(acc[mt], areg[mt][kk], db, kk > 0);
                    }
                wg_commit();
                if (cw == 0 && s >= 0) TR(14);
                wg_wait0();
                if (cw == 0 && s >= 0) TR(15);
                float4* red = reinterpret_cast<float4*>(smem + SM_RED);
                #pragma unroll
                for (int j = 0; j < 4; j++) {
                    red[((wg ^ 1) * 4 + j) * 128 + wtid] = make_float4(wg == 0 ? acc[1][4 * j] : acc[0][4 * j], wg == 0 ? acc[1][4 * j + 1] : acc[0][4 * j + 1],
                                                                       wg == 0 ? acc[1][4 * j + 2] : acc[0][4 * j + 2], wg == 0 ? acc[1][4 * j + 3] : acc[0][4 * j + 3]);
                }
                if (s >= 0) mbar_wait(sb + B_EXP, s & 1);
                nbar_sync(1, 256);
                uint32_t pk[8];
                #pragma unroll
                for (int j = 0; j < 4; j++) {
                    float4 r = red[(wg * 4 + j) * 128 + wtid];
                    pk[2 * j] = pack_bf16((wg == 0 ? acc[0][4 * j] : acc[1][4 * j]) + r.x, (wg == 0 ? acc[0][4 * j + 1] : acc[1][4 * j + 1]) + r.y);
                    pk[2 * j + 1] = pack_bf16((wg == 0 ? acc[0][4 * j + 2] : acc[1][4 * j + 2]) + r.z, (wg == 0 ? acc[0][4 * j + 3] : acc[1][4 * j + 3]) + r.w);
                }
                const uint32_t dst = (rank == 2) ? sb + SM_VT + sln * 10240 + wg * 5120 + 1024 : (wg == 0 ? sb + SM_QT : sb + SM_KT + sln * 5120 + 1024);
                #pragma unroll
                for (int jj = 0; jj < 2; jj++) {
                    int mi = lane >> 3, tok = 8 * (2 * jj + (mi >> 1)) + (lane & 7), chunk = 2 * warp + (mi & 1);
                    stsm4t(dst + tok * 128 + ((chunk ^ (tok & 7)) << 4), pk[4 * jj], pk[4 * jj + 1], pk[4 * jj + 2], pk[4 * jj + 3]);
                }
                fence_async();
                nbar_sync(1, 256);
                if (rank == 2 && lane == 0 && cw < 4 && sn < NSEG - 1) {
                    const uint32_t off = SM_VT + sln * 10240 + (cw & 1) * 5120 + 1024;
                    const uint32_t rb = mapa(sb, cw >> 1);
                    bulk_s2c(rb + off, sb + off, 4096, rb + B_V + 8 * sln);
                }
                if (cw == 0 && s >= 0) TR(13);
            }
        }
        nbar_arrive(3, 384);
        __syncwarp();
        cluster_sync_all();
    }
}

#define NAUX 36
__device__ __align__(1024) bf16 g_Oimg[16 * 64 * 128 * 64];
__device__ float    g_part[4 * SEQ * DM];
__device__ float    g_part31[3 * 13 * 64 * DM];
__device__ unsigned g_ocnt[32];
__device__ unsigned g_gcnt[32][2];
__device__ unsigned g_ssmcnt, g_auxdone, g_taskctr, g_gemmctr;
#define NATT 8
#define ATR(i) do {} while (0)
#define ATRID(i, id) do {} while (0)

__device__ __forceinline__ void wait_counter(const unsigned* p, unsigned target) {
    int guard = 0;
    while ((int)(ld_acquire(p) - target) < 0 && ++guard < (1 << 22)) __nanosleep(64);
}
__device__ __forceinline__ void fence_async_all() { asm volatile("fence.proxy.async;" ::: "memory"); }
template <int OFF>
__device__ __forceinline__ void wgmma_n192_tB(float (&d)[160], uint64_t da, uint64_t db) {
    asm volatile("wgmma.mma_async.sync.aligned.m64n192k16.f32.bf16.bf16 {%0,%1,%2,%3,%4,%5,%6,%7,%8,%9,%10,%11,%12,%13,%14,%15,%16,%17,%18,%19,%20,%21,%22,%23,%24,%25,%26,%27,%28,%29,%30,%31,%32,%33,%34,%35,%36,%37,%38,%39,%40,%41,%42,%43,%44,%45,%46,%47,%48,%49,%50,%51,%52,%53,%54,%55,%56,%57,%58,%59,%60,%61,%62,%63,%64,%65,%66,%67,%68,%69,%70,%71,%72,%73,%74,%75,%76,%77,%78,%79,%80,%81,%82,%83,%84,%85,%86,%87,%88,%89,%90,%91,%92,%93,%94,%95}, %96, %97, 1, 1, 1, 0, 1;\n"
        : "+f"(d[OFF + 0]), "+f"(d[OFF + 1]), "+f"(d[OFF + 2]), "+f"(d[OFF + 3]), "+f"(d[OFF + 4]), "+f"(d[OFF + 5]), "+f"(d[OFF + 6]), "+f"(d[OFF + 7]), "+f"(d[OFF + 8]), "+f"(d[OFF + 9]), "+f"(d[OFF + 10]), "+f"(d[OFF + 11]), "+f"(d[OFF + 12]), "+f"(d[OFF + 13]), "+f"(d[OFF + 14]), "+f"(d[OFF + 15]), "+f"(d[OFF + 16]), "+f"(d[OFF + 17]), "+f"(d[OFF + 18]), "+f"(d[OFF + 19]), "+f"(d[OFF + 20]), "+f"(d[OFF + 21]), "+f"(d[OFF + 22]), "+f"(d[OFF + 23]), "+f"(d[OFF + 24]), "+f"(d[OFF + 25]), "+f"(d[OFF + 26]), "+f"(d[OFF + 27]), "+f"(d[OFF + 28]), "+f"(d[OFF + 29]), "+f"(d[OFF + 30]), "+f"(d[OFF + 31]), "+f"(d[OFF + 32]), "+f"(d[OFF + 33]), "+f"(d[OFF + 34]), "+f"(d[OFF + 35]), "+f"(d[OFF + 36]), "+f"(d[OFF + 37]), "+f"(d[OFF + 38]), "+f"(d[OFF + 39]), "+f"(d[OFF + 40]), "+f"(d[OFF + 41]), "+f"(d[OFF + 42]), "+f"(d[OFF + 43]), "+f"(d[OFF + 44]), "+f"(d[OFF + 45]), "+f"(d[OFF + 46]), "+f"(d[OFF + 47]), "+f"(d[OFF + 48]), "+f"(d[OFF + 49]), "+f"(d[OFF + 50]), "+f"(d[OFF + 51]), "+f"(d[OFF + 52]), "+f"(d[OFF + 53]), "+f"(d[OFF + 54]), "+f"(d[OFF + 55]), "+f"(d[OFF + 56]), "+f"(d[OFF + 57]), "+f"(d[OFF + 58]), "+f"(d[OFF + 59]), "+f"(d[OFF + 60]), "+f"(d[OFF + 61]), "+f"(d[OFF + 62]), "+f"(d[OFF + 63]), "+f"(d[OFF + 64]), "+f"(d[OFF + 65]), "+f"(d[OFF + 66]), "+f"(d[OFF + 67]), "+f"(d[OFF + 68]), "+f"(d[OFF + 69]), "+f"(d[OFF + 70]), "+f"(d[OFF + 71]), "+f"(d[OFF + 72]), "+f"(d[OFF + 73]), "+f"(d[OFF + 74]), "+f"(d[OFF + 75]), "+f"(d[OFF + 76]), "+f"(d[OFF + 77]), "+f"(d[OFF + 78]), "+f"(d[OFF + 79]), "+f"(d[OFF + 80]), "+f"(d[OFF + 81]), "+f"(d[OFF + 82]), "+f"(d[OFF + 83]), "+f"(d[OFF + 84]), "+f"(d[OFF + 85]), "+f"(d[OFF + 86]), "+f"(d[OFF + 87]), "+f"(d[OFF + 88]), "+f"(d[OFF + 89]), "+f"(d[OFF + 90]), "+f"(d[OFF + 91]), "+f"(d[OFF + 92]), "+f"(d[OFF + 93]), "+f"(d[OFF + 94]), "+f"(d[OFF + 95])
        : "l"(da), "l"(db));
}
template <int OFF>
__device__ __forceinline__ void wgmma_n128_tB(float (&d)[160], uint64_t da, uint64_t db) {
    asm volatile("wgmma.mma_async.sync.aligned.m64n128k16.f32.bf16.bf16 {%0,%1,%2,%3,%4,%5,%6,%7,%8,%9,%10,%11,%12,%13,%14,%15,%16,%17,%18,%19,%20,%21,%22,%23,%24,%25,%26,%27,%28,%29,%30,%31,%32,%33,%34,%35,%36,%37,%38,%39,%40,%41,%42,%43,%44,%45,%46,%47,%48,%49,%50,%51,%52,%53,%54,%55,%56,%57,%58,%59,%60,%61,%62,%63}, %64, %65, 1, 1, 1, 0, 1;\n"
        : "+f"(d[OFF + 0]), "+f"(d[OFF + 1]), "+f"(d[OFF + 2]), "+f"(d[OFF + 3]), "+f"(d[OFF + 4]), "+f"(d[OFF + 5]), "+f"(d[OFF + 6]), "+f"(d[OFF + 7]), "+f"(d[OFF + 8]), "+f"(d[OFF + 9]), "+f"(d[OFF + 10]), "+f"(d[OFF + 11]), "+f"(d[OFF + 12]), "+f"(d[OFF + 13]), "+f"(d[OFF + 14]), "+f"(d[OFF + 15]), "+f"(d[OFF + 16]), "+f"(d[OFF + 17]), "+f"(d[OFF + 18]), "+f"(d[OFF + 19]), "+f"(d[OFF + 20]), "+f"(d[OFF + 21]), "+f"(d[OFF + 22]), "+f"(d[OFF + 23]), "+f"(d[OFF + 24]), "+f"(d[OFF + 25]), "+f"(d[OFF + 26]), "+f"(d[OFF + 27]), "+f"(d[OFF + 28]), "+f"(d[OFF + 29]), "+f"(d[OFF + 30]), "+f"(d[OFF + 31]), "+f"(d[OFF + 32]), "+f"(d[OFF + 33]), "+f"(d[OFF + 34]), "+f"(d[OFF + 35]), "+f"(d[OFF + 36]), "+f"(d[OFF + 37]), "+f"(d[OFF + 38]), "+f"(d[OFF + 39]), "+f"(d[OFF + 40]), "+f"(d[OFF + 41]), "+f"(d[OFF + 42]), "+f"(d[OFF + 43]), "+f"(d[OFF + 44]), "+f"(d[OFF + 45]), "+f"(d[OFF + 46]), "+f"(d[OFF + 47]), "+f"(d[OFF + 48]), "+f"(d[OFF + 49]), "+f"(d[OFF + 50]), "+f"(d[OFF + 51]), "+f"(d[OFF + 52]), "+f"(d[OFF + 53]), "+f"(d[OFF + 54]), "+f"(d[OFF + 55]), "+f"(d[OFF + 56]), "+f"(d[OFF + 57]), "+f"(d[OFF + 58]), "+f"(d[OFF + 59]), "+f"(d[OFF + 60]), "+f"(d[OFF + 61]), "+f"(d[OFF + 62]), "+f"(d[OFF + 63])
        : "l"(da), "l"(db));
}
__device__ __forceinline__ void stsm4(uint32_t addr, uint32_t r0, uint32_t r1, uint32_t r2, uint32_t r3) {
    asm volatile("stmatrix.sync.aligned.m8n8.x4.shared.b16 [%0], {%1,%2,%3,%4};" :: "r"(addr), "r"(r0), "r"(r1), "r"(r2), "r"(r3) : "memory");
}

#define AX_BAR   0
#define NST_G 4
#define AX_EMPTY (AX_BAR + 16 + 8 * NST_G)
#define AX_DATA  1024
#define AX_UNIT  28672
#define AX_STAGE 57344
#define AX_TOTAL (AX_DATA + 8 * AX_UNIT)

__device__ __forceinline__ void attn_compute(unsigned char* smem, uint32_t sb, uint32_t buf, int warp, int lane);
__device__ __forceinline__ void attn_producer(unsigned char* smem, int hg, unsigned epoch) {
    const uint32_t sb = smem_u32(smem);
    const int lane = threadIdx.x & 31;
    {
        for (int s = 0; s < NSEG; s++) {
            const uint32_t buf = AX_DATA + (s & 1) * (4 * AX_UNIT), bar = sb + AX_BAR + 8 * (s & 1);
            if (lane < 4) wait_counter(&g_flag[s][4 * hg + lane], (epoch + 1) * 3u);
            if (lane == 4) mbar_wait_sleep(sb + AX_EMPTY + 8 * (s & 1), ((s >> 1) & 1) ^ 1);
            __syncwarp();
            if (lane == 0) mbar_expect_tx(bar, 4 * AX_UNIT);
            __syncwarp();
            if (lane < 24) {
                fence_async_all();
                const int u = lane / 6, r = lane % 6, hf = r & 1, kind = r >> 1;
                const uint32_t ub = sb + buf + u * AX_UNIT;
                const size_t img = ((size_t)(s * NH + 4 * hg + u) * 2) + hf;
                if (kind == 0) bulk_g2s(ub + hf * 4096, g_Qimg + img * 2048, 4096, bar);
                else if (kind == 1) bulk_g2s(ub + 8192 + hf * 5120, g_Kimg + img * 2560, 5120, bar);
                else bulk_g2s(ub + 18432 + hf * 5120, g_Vimg + img * 2560, 5120, bar);
            }
            __syncwarp();
        }
    }
}
__device__ __forceinline__ void attn_loop(unsigned char* smem, int hg, unsigned epoch) {
    const uint32_t sb = smem_u32(smem);
    const int tid = threadIdx.x, warp = tid >> 5, lane = tid & 31;
    for (int s = 0; s < NSEG; s++) {
        const uint32_t buf = AX_DATA + (s & 1) * (4 * AX_UNIT), bar = sb + AX_BAR + 8 * (s & 1);
        mbar_wait_sleep(bar, (s >> 1) & 1);
        if (s >= 36) ATR(2 + 2 * (s - 36));
        attn_compute(smem, sb, buf, warp, lane);
        if (s >= 36) ATR(3 + 2 * (s - 36));
        fence_async();
        __syncwarp();
        if (lane == 0) mbar_arrive(sb + AX_EMPTY + 16 + 8 * (s & 1));
    }
}
__device__ __forceinline__ void attn_storer(unsigned char* smem, int hg) {
    const uint32_t sb = smem_u32(smem);
    const int lane = threadIdx.x & 31;
    for (int s = 0; s < NSEG; s++) {
        const uint32_t buf = AX_DATA + (s & 1) * (4 * AX_UNIT);
        mbar_wait_sleep(sb + AX_EMPTY + 16 + 8 * (s & 1), (s >> 1) & 1);
        if (lane < 8) {
            const int uu = lane >> 1, hf = lane & 1, hh = 4 * hg + uu;
            bulk_s2g(g_Oimg + (((size_t)(s >> 2) * 64 + hh * 2 + hf) * 128 + (s & 3) * 32) * 64, sb + buf + uu * AX_UNIT + hf * 4096, 4096);
            bulk_commit();
            bulk_wait_read0();
            mbar_arrive(sb + AX_EMPTY + 8 * (s & 1));
            bulk_wait0();
            fence_async_all();
            __threadfence();
            atomicAdd(&g_ocnt[s >> 1], 1u);
        }
        __syncwarp();
    }
}
__device__ __forceinline__ void attn_compute(unsigned char* smem, uint32_t sb, uint32_t buf, int warp, int lane) {
    const int g = lane >> 2, t = lane & 3;
    const int u = warp >> 1, qh = warp & 1;
    const uint32_t ub = sb + buf + u * AX_UNIT;
    float sc[5][4];
    #pragma unroll
    for (int j = 0; j < 5; j++) { sc[j][0] = sc[j][1] = sc[j][2] = sc[j][3] = 0.f; }
    #pragma unroll
    for (int ks = 0; ks < 8; ks++) {
        const int hf = ks >> 2, c0 = (ks & 3) * 2;
        uint32_t a[4];
        { int mi = lane >> 3, row = 16 * qh + (mi & 1) * 8 + (lane & 7), chunk = c0 + (mi >> 1);
          ldsm4(a, ub + hf * 4096 + row * 128 + ((chunk ^ (row & 7)) << 4)); }
        #pragma unroll
        for (int jp = 0; jp < 3; jp++) {
            uint32_t b[4];
            int mi = lane >> 3, nt = 2 * jp + (mi >> 1); if (nt > 4) nt = 4;
            int row = 8 * nt + (lane & 7), chunk = c0 + (mi & 1);
            ldsm4(b, ub + 8192 + hf * 5120 + row * 128 + ((chunk ^ (row & 7)) << 4));
            mma_bf16(sc[2 * jp], a[0], a[1], a[2], a[3], b[0], b[1]);
            if (jp < 2) mma_bf16(sc[2 * jp + 1], a[0], a[1], a[2], a[3], b[2], b[3]);
        }
    }
    uint32_t pa[3][4];
    {
        const float sc2 = 0.08838834764831845f * 1.4426950408889634f;
        float mx0 = -3.0e38f, mx1 = -3.0e38f;
        const int q0 = 16 * qh + g, q1 = q0 + 8;
        #pragma unroll
        for (int j = 0; j < 5; j++)
            #pragma unroll
            for (int e = 0; e < 2; e++) {
                int key = 8 * j + 2 * t + e - 8;
                sc[j][e] = (key <= q0) ? sc[j][e] * sc2 : -3.0e38f;
                sc[j][2 + e] = (key <= q1) ? sc[j][2 + e] * sc2 : -3.0e38f;
                mx0 = fmaxf(mx0, sc[j][e]); mx1 = fmaxf(mx1, sc[j][2 + e]);
            }
        mx0 = fmaxf(mx0, __shfl_xor_sync(~0u, mx0, 1)); mx0 = fmaxf(mx0, __shfl_xor_sync(~0u, mx0, 2));
        mx1 = fmaxf(mx1, __shfl_xor_sync(~0u, mx1, 1)); mx1 = fmaxf(mx1, __shfl_xor_sync(~0u, mx1, 2));
        float s0 = 0.f, s1 = 0.f;
        #pragma unroll
        for (int j = 0; j < 5; j++)
            #pragma unroll
            for (int e = 0; e < 2; e++) {
                sc[j][e] = ex2_approx(sc[j][e] - mx0); sc[j][2 + e] = ex2_approx(sc[j][2 + e] - mx1);
                s0 += sc[j][e]; s1 += sc[j][2 + e];
            }
        s0 += __shfl_xor_sync(~0u, s0, 1); s0 += __shfl_xor_sync(~0u, s0, 2);
        s1 += __shfl_xor_sync(~0u, s1, 1); s1 += __shfl_xor_sync(~0u, s1, 2);
        const float i0 = __frcp_rn(s0), i1 = __frcp_rn(s1);
        #pragma unroll
        for (int k = 0; k < 3; k++) {
            pa[k][0] = pack_bf16(sc[2 * k][0] * i0, sc[2 * k][1] * i0);
            pa[k][1] = pack_bf16(sc[2 * k][2] * i1, sc[2 * k][3] * i1);
            if (k < 2) { pa[k][2] = pack_bf16(sc[2 * k + 1][0] * i0, sc[2 * k + 1][1] * i0); pa[k][3] = pack_bf16(sc[2 * k + 1][2] * i1, sc[2 * k + 1][3] * i1); }
            else { pa[k][2] = 0u; pa[k][3] = 0u; }
        }
    }
    __syncwarp();
    nbar_sync(5 + u, 64);
    #pragma unroll
    for (int np = 0; np < 8; np++) {
        const int hf = np >> 2, c0 = (np & 3) * 2;
        float o0[4] = {0, 0, 0, 0}, o1[4] = {0, 0, 0, 0};
        #pragma unroll
        for (int k = 0; k < 3; k++) {
            uint32_t b[4];
            int mi = lane >> 3;
            int row = 16 * k + (mi & 1) * 8 + (lane & 7); if (row > 39) row = 39 - 7 + (lane & 7);
            int chunk = c0 + (mi >> 1);
            ldsm4t(b, ub + 18432 + hf * 5120 + row * 128 + ((chunk ^ (row & 7)) << 4));
            mma_bf16(o0, pa[k][0], pa[k][1], pa[k][2], pa[k][3], b[0], k < 2 ? b[1] : 0u);
            mma_bf16(o1, pa[k][0], pa[k][1], pa[k][2], pa[k][3], b[2], k < 2 ? b[3] : 0u);
        }
        int mi = lane >> 3, row = 16 * qh + (mi & 1) * 8 + (lane & 7), chunk = c0 + (mi >> 1);
        stsm4(ub + hf * 4096 + row * 128 + ((chunk ^ (row & 7)) << 4), pack_bf16(o0[0], o0[1]), pack_bf16(o0[2], o0[3]), pack_bf16(o1[0], o1[1]), pack_bf16(o1[2], o1[3]));
    }
}

template <int V> struct IntC { static constexpr int value = V; };
struct Task { int type, rb, c, k0, nch, plane; };
#define NFINE 29
#define NGEMM (8 + 144 + 8 * 2 + 4 + 8 * 4 + 26 * 3 + 16 * 3)
__device__ __forceinline__ Task decode_task(int j) {
    Task t; t.type = 0; t.rb = 0; t.c = 0; t.k0 = 0; t.nch = 16; t.plane = 0;
    auto H = [&](int rb, int i) { t.type = 1; t.rb = rb; t.c = i & 1; t.plane = i >> 1; t.k0 = t.plane * 16; };
    auto CF = [&](int rb, int i) { t.type = 2; t.rb = rb; t.c = i & 1; t.k0 = rb * 64 + (i >> 1) * 16; t.nch = 16; };
    auto H13 = [&](int rb, int i) { t.type = 1; t.rb = rb; t.c = i & 1; t.plane = i >> 1; t.k0 = t.plane * 5; t.nch = (t.plane == 12) ? 4 : 5; };
    auto C13 = [&](int rb, int i) { t.type = 2; t.rb = rb; t.c = i & 1; t.k0 = rb * 64 + (i >> 1) * 8; t.nch = 8; };
    if (j >= NGEMM) { t.type = 3; return t; }
    if (j < 8) { t.c = j & 1; t.plane = j >> 1; t.k0 = t.plane * 16; return t; }
    j -= 8;
    if (j < 144) {
        const int q = j / 12, r = j % 12;
        if (r < 8) { t.rb = 2 * (q + 1); t.c = r & 1; t.plane = r >> 1; t.k0 = t.plane * 16; }
        else { t.type = 2; t.rb = 2 * q + ((r - 8) >> 1); t.c = r & 1; t.k0 = t.rb * 64; t.nch = 64; }
        return t;
    }
    j -= 144;
    if (j < 8) { H(26, j); return t; }
    j -= 8;
    if (j < 8) { H(27, j); return t; }
    j -= 8;
    if (j < 4) { t.type = 2; t.rb = 24 + (j >> 1); t.c = j & 1; t.k0 = t.rb * 64; t.nch = 64; return t; }
    j -= 4;
    if (j < 8) { H(28, j); return t; }
    j -= 8;
    if (j < 8) { CF(26, j); return t; }
    j -= 8;
    if (j < 8) { CF(27, j); return t; }
    j -= 8;
    if (j < 26) { H13(29, j); return t; }
    j -= 26;
    if (j < 8) { CF(28, j); return t; }
    j -= 8;
    if (j < 26) { H13(30, j); return t; }
    j -= 26;
    if (j < 16) { C13(29, j); return t; }
    j -= 16;
    if (j < 26) { H13(31, j); return t; }
    j -= 26;
    if (j < 16) { C13(30, j); return t; }
    j -= 16;
    C13(31, j);
    return t;
}
__device__ __forceinline__ void gemm_producer(unsigned char* smem, const CUtensorMap* womap, unsigned epoch, volatile int* s_tasks) {
    const uint32_t sb = smem_u32(smem);
    uint32_t st = 0, ph = 1;
    for (int n = 0;; n++) {
        const int j = (int)(atomicAdd(&g_gemmctr, 1u) - epoch * (unsigned)(NGEMM + NAUX));
        const Task t = decode_task(j);
        if (t.type <= 1) {
            wait_counter(&g_ocnt[t.rb], (epoch + 1) * 128u);
            if (t.type == 0) wait_counter(&g_ocnt[t.rb + 1], (epoch + 1) * 128u);
            fence_async_all();
        } else if (t.type == 2) {
            wait_counter(&g_gcnt[t.rb][t.c], (epoch + 1) * (t.rb >= NFINE ? 13u : 4u));
            wait_counter(&g_ssmcnt, (epoch + 1) * 80u);
        }
        const int nch = (t.type <= 1) ? t.nch : 1;
        for (int kc = 0; kc < nch; kc++) {
            mbar_wait_sleep(sb + AX_EMPTY + 8 * st, ph);
            const uint32_t a = sb + AX_DATA + st * AX_STAGE, bar = sb + AX_BAR + 16 + 8 * st;
            if (kc == 0) s_tasks[n & 7] = j;
            if (t.type > 1) mbar_arrive(bar);
            else {
                const bf16* asrc = g_Oimg + ((size_t)(t.rb >> 1) * 64 + t.k0 + kc) * 8192 + (t.rb & 1) * 4096;
                if (t.type == 0) { mbar_expect_tx(bar, AX_STAGE); bulk_g2s(a, asrc, 8192, bar); bulk_g2s(a + 8192, asrc + 4096, 8192, bar); }
                else { mbar_expect_tx(bar, AX_STAGE - 8192); bulk_g2s(a, asrc, 8192, bar); }
                #pragma unroll
                for (int b = 0; b < 5; b++) tma_load_2d(a + 16384 + b * 8192, womap, t.c * 320 + b * 64, (t.k0 + kc) * 64, bar);
            }
            if (++st == NST_G) { st = 0; ph ^= 1; }
        }
        if (t.type == 3) break;
    }
}
__device__ __forceinline__ void gemm_signaller(volatile int* s_done) {
    for (int n = 0;; n++) {
        nbar_sync(2, 288);
        const int j = s_done[n & 7];
        if (j < 0) break;
        if ((threadIdx.x & 31) == 0) {
            const Task t = decode_task(j);
            __threadfence();
            atomicAdd(&g_gcnt[t.rb][t.c], 1u);
            if (t.type == 0) atomicAdd(&g_gcnt[t.rb + 1][t.c], 1u);
        }
        __syncwarp();
    }
}
__device__ __forceinline__ void gemm_consumer(unsigned char* smem, bf16* __restrict__ out, volatile int* s_tasks, volatile int* s_done) {
    const uint32_t sb = smem_u32(smem);
    const int tid = threadIdx.x, lane = tid & 31;
    const int wg = __shfl_sync(~0u, tid >> 7, 0), warp = __shfl_sync(~0u, (tid >> 5) & 3, 0);
    uint32_t st = 0, ph = 0;
    int ndone = 0;
    for (int n = 0;; n++) {
        mbar_wait_sleep(sb + AX_BAR + 16 + 8 * st, ph);
        const Task t = decode_task(__shfl_sync(~0u, s_tasks[n & 7], 0));
        if (t.type > 1) {
            nbar_sync(1, 256);
            if ((tid & 127) == 0) mbar_arrive(sb + AX_EMPTY + 8 * st);
            if (++st == NST_G) { st = 0; ph ^= 1; }
            if (t.type == 3) break;
            const int np = (t.rb >= NFINE) ? 13 : 4;
            const float* pbase = (t.rb >= NFINE) ? g_part31 + (size_t)(t.rb - NFINE) * 13 * 64 * DM - (size_t)t.rb * 64 * DM : g_part;
            const size_t pstride = (t.rb >= NFINE) ? (size_t)64 * DM : (size_t)SEQ * DM;
            auto combine = [&](int i, auto NP) {
                const int r = t.k0 + i / 80, cc = t.c * 320 + (i % 80) * 4;
                float4 v[NP.value];
                #pragma unroll
                for (int q = 0; q < NP.value; q++) v[q] = __ldcg(reinterpret_cast<const float4*>(pbase + q * pstride + (size_t)r * DM + cc));
                const float gt = __ldcg(g_g + r);
                const uint2 bb = __ldcg(reinterpret_cast<const uint2*>(g_b + (size_t)r * DM + cc));
                float4 a = v[0];
                #pragma unroll
                for (int q = 1; q < NP.value; q++) { a.x += v[q].x; a.y += v[q].y; a.z += v[q].z; a.w += v[q].w; }
                const float b0 = __uint_as_float(bb.x << 16), b1 = __uint_as_float(bb.x & 0xffff0000u), b2 = __uint_as_float(bb.y << 16), b3 = __uint_as_float(bb.y & 0xffff0000u);
                uint2 o; o.x = pack_bf16(gt * a.x + (1.f - gt) * b0, gt * a.y + (1.f - gt) * b1); o.y = pack_bf16(gt * a.z + (1.f - gt) * b2, gt * a.w + (1.f - gt) * b3);
                *reinterpret_cast<uint2*>(out + (size_t)r * DM + cc) = o;
            };
            if (np == 4) {
                const int nit = t.nch * 80 / 256;
                for (int it0 = 0; it0 < nit; it0 += 5) {
                    #pragma unroll
                    for (int it = 0; it < 5; it++) combine(tid + 256 * (it0 + it), IntC<4>());
                }
            } else {
                #pragma unroll
                for (int it = 0; it < 3; it++) { const int i = tid + 256 * it; if (i < 640) combine(i, IntC<13>()); }
            }
            if (n < 56 && (blockIdx.x >= NATT || n < 4)) ATRID((blockIdx.x >= NATT ? 6 : 58) + n, s_tasks[n & 7]);
            continue;
        }
        const int g = lane >> 2, tq = lane & 3;
        if (t.type == 0) {
            float acc[160];
            #pragma unroll
            for (int i = 0; i < 160; i++) acc[i] = 0.f;
            uint32_t prev = 0;
            for (int kc = 0; kc < 16; kc++) {
                mbar_wait(sb + AX_BAR + 16 + 8 * st, ph);
                const uint32_t a = sb + AX_DATA + st * AX_STAGE;
                const uint64_t da = make_desc(a + wg * 8192, 16, 1024), db = make_desc(a + 16384, 8192, 1024);
                wg_fence();
                #pragma unroll
                for (int ks = 0; ks < 4; ks++) {
                    wgmma_n192_tB<0>(acc, da + ks * 2, db + ks * 128);
                    wgmma_n128_tB<96>(acc, da + ks * 2, db + ks * 128 + 3 * 512);
                }
                wg_commit();
                asm volatile("wgmma.wait_group.sync.aligned 1;" ::: "memory");
                if (kc > 0 && (tid & 127) == 0) mbar_arrive(sb + AX_EMPTY + 8 * prev);
                prev = st;
                if (++st == NST_G) { st = 0; ph ^= 1; }
            }
            wg_wait0();
            if ((tid & 127) == 0) mbar_arrive(sb + AX_EMPTY + 8 * prev);
            float* base = g_part + ((size_t)t.plane * SEQ + t.rb * 64 + wg * 64 + warp * 16 + g) * DM + t.c * 320 + 2 * tq;
            #pragma unroll
            for (int q = 0; q < 40; q++) {
                *reinterpret_cast<float2*>(base + q * 8) = make_float2(acc[4 * q], acc[4 * q + 1]);
                *reinterpret_cast<float2*>(base + 8 * DM + q * 8) = make_float2(acc[4 * q + 2], acc[4 * q + 3]);
            }
        } else {
            float* base = (t.rb >= NFINE ? g_part31 + (size_t)((t.rb - NFINE) * 13 + t.plane) * 64 * DM : g_part + ((size_t)t.plane * SEQ + t.rb * 64) * DM) + (size_t)(warp * 16 + g) * DM + t.c * 320 + 2 * tq;
            if (wg == 0) {
                float acc[160];
                #pragma unroll
                for (int i = 0; i < 96; i++) acc[i] = 0.f;
                uint32_t prev = 0;
                for (int kc = 0; kc < t.nch; kc++) {
                    mbar_wait(sb + AX_BAR + 16 + 8 * st, ph);
                    const uint32_t a = sb + AX_DATA + st * AX_STAGE;
                    const uint64_t da = make_desc(a, 16, 1024), db = make_desc(a + 16384, 8192, 1024);
                    wg_fence();
                    #pragma unroll
                    for (int ks = 0; ks < 4; ks++) wgmma_n192_tB<0>(acc, da + ks * 2, db + ks * 128);
                    wg_commit();
                    asm volatile("wgmma.wait_group.sync.aligned 1;" ::: "memory");
                    if (kc > 0 && (tid & 127) == 0) mbar_arrive(sb + AX_EMPTY + 8 * prev);
                    prev = st;
                    if (++st == NST_G) { st = 0; ph ^= 1; }
                }
                wg_wait0();
                if ((tid & 127) == 0) mbar_arrive(sb + AX_EMPTY + 8 * prev);
                #pragma unroll
                for (int q = 0; q < 24; q++) {
                    *reinterpret_cast<float2*>(base + q * 8) = make_float2(acc[4 * q], acc[4 * q + 1]);
                    *reinterpret_cast<float2*>(base + 8 * DM + q * 8) = make_float2(acc[4 * q + 2], acc[4 * q + 3]);
                }
            } else {
                float acc[160];
                #pragma unroll
                for (int i = 96; i < 160; i++) acc[i] = 0.f;
                uint32_t prev = 0;
                for (int kc = 0; kc < t.nch; kc++) {
                    mbar_wait(sb + AX_BAR + 16 + 8 * st, ph);
                    const uint32_t a = sb + AX_DATA + st * AX_STAGE;
                    const uint64_t da = make_desc(a, 16, 1024), db = make_desc(a + 16384, 8192, 1024);
                    wg_fence();
                    #pragma unroll
                    for (int ks = 0; ks < 4; ks++) wgmma_n128_tB<96>(acc, da + ks * 2, db + ks * 128 + 3 * 512);
                    wg_commit();
                    asm volatile("wgmma.wait_group.sync.aligned 1;" ::: "memory");
                    if (kc > 0 && (tid & 127) == 0) mbar_arrive(sb + AX_EMPTY + 8 * prev);
                    prev = st;
                    if (++st == NST_G) { st = 0; ph ^= 1; }
                }
                wg_wait0();
                if ((tid & 127) == 0) mbar_arrive(sb + AX_EMPTY + 8 * prev);
                #pragma unroll
                for (int q = 24; q < 40; q++) {
                    *reinterpret_cast<float2*>(base + q * 8) = make_float2(acc[4 * q], acc[4 * q + 1]);
                    *reinterpret_cast<float2*>(base + 8 * DM + q * 8) = make_float2(acc[4 * q + 2], acc[4 * q + 3]);
                }
            }
        }
        if (tid == 0) s_done[ndone & 7] = s_tasks[n & 7];
        ndone++;
        nbar_arrive(2, 288);
        if (n < 56 && (blockIdx.x >= NATT || n < 4)) ATRID((blockIdx.x >= NATT ? 6 : 58) + n, s_tasks[n & 7]);
    }
    if (tid == 0) s_done[ndone & 7] = -1;
    nbar_arrive(2, 288);
}

__global__ void __launch_bounds__(384, 1)
k_aux(const __grid_constant__ CUtensorMap womap, const bf16* __restrict__ x, const bf16* __restrict__ A_re, const bf16* __restrict__ A_im,
      const bf16* __restrict__ B_re, const bf16* __restrict__ B_im, const bf16* __restrict__ C_re, const bf16* __restrict__ C_im,
      const bf16* __restrict__ log_dt, const bf16* __restrict__ Dskip, const bf16* __restrict__ gw, bf16* __restrict__ out) {
    extern __shared__ __align__(1024) unsigned char smem[];
    const uint32_t sb = smem_u32(smem);
    const int tid = threadIdx.x, warp = tid >> 5, lane = tid & 31;
    __shared__ unsigned s_epoch;
    __shared__ int s_task, s_tasks[8], s_done[8];
    if (tid == 0) {
        for (int i = 0; i < 2 + NST_G; i++) mbar_init(sb + AX_BAR + 8 * i, 1);
        for (int i = 0; i < NST_G; i++) mbar_init(sb + AX_EMPTY + 8 * i, blockIdx.x < NATT ? 8 : 2);
        asm volatile("fence.mbarrier_init.release.cluster;" ::: "memory");
        s_epoch = *reinterpret_cast<volatile unsigned*>(&g_epoch);
    }
    __syncthreads();
    const unsigned epoch = s_epoch;
    ATR(0);
    const int wg = __shfl_sync(~0u, tid >> 7, 0);
    if (wg == 2) {
        asm volatile("setmaxnreg.dec.sync.aligned.u32 40;");
        if (blockIdx.x < NATT) { if (warp == 8) attn_producer(smem, blockIdx.x, epoch); else if (warp == 9) attn_storer(smem, blockIdx.x); __syncwarp(); }
        nbar_sync(3, 384);
        nbar_sync(3, 384);
        if (warp == 8) { if (lane == 0) gemm_producer(smem, &womap, epoch, s_tasks); }
        else if (warp == 9) gemm_signaller(s_done);
        __syncwarp();
        nbar_sync(4, 384);
    } else {
        asm volatile("setmaxnreg.inc.sync.aligned.u32 232;");
        if (blockIdx.x < NATT) attn_loop(smem, blockIdx.x, epoch);
        else {
            int ntask = 0;
            for (;;) {
                nbar_sync(1, 256);
                if (tid == 0) s_task = (int)(atomicAdd(&g_taskctr, 1u) - epoch * (unsigned)(80 + NAUX - NATT));
                nbar_sync(1, 256);
                const int task = s_task;
                if (task >= 80) break;
                for (int r = task * 26 + warp; r < min(SEQ, task * 26 + 26); r += 8) {
                    float sum = 0.f;
                    for (int i = lane * 2; i < DM; i += 64) {
                        __nv_bfloat162 xv = *reinterpret_cast<const __nv_bfloat162*>(x + (size_t)r * DM + i), wv = *reinterpret_cast<const __nv_bfloat162*>(gw + i);
                        sum += bf2f(xv.x) * bf2f(wv.x) + bf2f(xv.y) * bf2f(wv.y);
                    }
                    #pragma unroll
                    for (int o = 16; o; o >>= 1) sum += __shfl_xor_sync(~0u, sum, o);
                    if (lane == 0) g_g[r] = 1.f / (1.f + expf(-sum));
                }
                ssm_group(smem + AX_DATA, task, x, A_re, A_im, B_re, B_im, C_re, C_im, log_dt, Dskip);
                nbar_sync(1, 256);
                if (tid == 0) { __threadfence(); atomicAdd(&g_ssmcnt, 1u); }
                if (ntask < 4) ATR(2 + ntask);
                ntask++;
            }
        }
        fence_async();
        nbar_sync(3, 384);
        if (tid == 0) {
            for (int i = 0; i < NST_G; i++) {
                asm volatile("mbarrier.inval.shared::cta.b64 [%0];" :: "r"(sb + AX_BAR + 16 + 8 * i) : "memory");
                asm volatile("mbarrier.inval.shared::cta.b64 [%0];" :: "r"(sb + AX_EMPTY + 8 * i) : "memory");
                mbar_init(sb + AX_BAR + 16 + 8 * i, 1); mbar_init(sb + AX_EMPTY + 8 * i, 2);
            }
            asm volatile("fence.mbarrier_init.release.cluster;" ::: "memory");
        }
        nbar_sync(3, 384);
        gemm_consumer(smem, out, s_tasks, s_done);
        nbar_sync(4, 384);
        if (tid == 0) {
            __threadfence();
            unsigned old = atomicAdd(&g_auxdone, 1u);
            if (old == NAUX - 1) { g_auxdone = 0; __threadfence(); atomicAdd(&g_epoch, 1u); }
        }
    }
    asm volatile("griddepcontrol.wait;" ::: "memory");
}

extern "C" void kernel_launch(void* const* d_in, const int* in_sizes, int n_in, void* d_out, int out_size) {
    const bf16* x = (const bf16*)d_in[0];
    const bf16* mem0 = (const bf16*)d_in[1];
    const bf16* Wq = (const bf16*)d_in[2];
    const bf16* Wk = (const bf16*)d_in[3];
    const bf16* Wv = (const bf16*)d_in[4];
    const bf16* Wo = (const bf16*)d_in[5];
    const bf16 *A_re = (const bf16*)d_in[8], *A_im = (const bf16*)d_in[9], *B_re = (const bf16*)d_in[10], *B_im = (const bf16*)d_in[11];
    const bf16 *C_re = (const bf16*)d_in[12], *C_im = (const bf16*)d_in[13], *log_dt = (const bf16*)d_in[14], *Dskip = (const bf16*)d_in[15];
    const bf16* gw = (const bf16*)d_in[16];
    bf16* out = (bf16*)d_out;
    cudaStream_t st = cudaStreamPerThread;
    static bool init = false;
    static CUtensorMap xmap, womap, wqmap, wkmap, wvmap;
    static const void* xmap_ptr = nullptr; static const void* womap_ptr = nullptr; static const void* w_ptr[3] = {nullptr, nullptr, nullptr};
    if (!init) {
        cudaFuncSetAttribute(k_chain, cudaFuncAttributeMaxDynamicSharedMemorySize, SM_TOTAL);
        cudaFuncSetAttribute(k_aux, cudaFuncAttributeMaxDynamicSharedMemorySize, AX_TOTAL);
        init = true;
    }
    if (xmap_ptr != (const void*)x || womap_ptr != (const void*)Wo || w_ptr[0] != Wq || w_ptr[1] != Wk || w_ptr[2] != Wv) {
        void* fn = nullptr; cudaDriverEntryPointQueryResult qres;
        cudaGetDriverEntryPoint("cuTensorMapEncodeTiled", &fn, cudaEnableDefault, &qres);
        typedef CUresult (*EncFn)(CUtensorMap*, CUtensorMapDataType, cuuint32_t, void*, const cuuint64_t*, const cuuint64_t*, const cuuint32_t*, const cuuint32_t*,
                                  CUtensorMapInterleave, CUtensorMapSwizzle, CUtensorMapL2promotion, CUtensorMapFloatOOBfill);
        cuuint32_t es[2] = {1, 1};
        {
          cuuint64_t dims[3] = {64, SEQ, 10}; cuuint64_t strides[2] = {DM * 2, 128}; cuuint32_t box[3] = {64, 32, 10}; cuuint32_t es3[3] = {1, 1, 1};
          ((EncFn)fn)(&xmap, CU_TENSOR_MAP_DATA_TYPE_BFLOAT16, 3, (void*)x, dims, strides, box, es3, CU_TENSOR_MAP_INTERLEAVE_NONE, CU_TENSOR_MAP_SWIZZLE_128B,
                      CU_TENSOR_MAP_L2_PROMOTION_L2_128B, CU_TENSOR_MAP_FLOAT_OOB_FILL_NONE); }
        { cuuint64_t dims[2] = {DM, HD}; cuuint64_t strides[1] = {DM * 2}; cuuint32_t box[2] = {64, 64};
          ((EncFn)fn)(&womap, CU_TENSOR_MAP_DATA_TYPE_BFLOAT16, 2, (void*)Wo, dims, strides, box, es, CU_TENSOR_MAP_INTERLEAVE_NONE, CU_TENSOR_MAP_SWIZZLE_128B,
                      CU_TENSOR_MAP_L2_PROMOTION_L2_128B, CU_TENSOR_MAP_FLOAT_OOB_FILL_NONE); }
        { cuuint64_t dims[2] = {HD, DM}; cuuint64_t strides[1] = {HD * 2}; cuuint32_t box[2] = {64, 128};
          const bf16* ws[3] = {Wq, Wk, Wv}; CUtensorMap* ms[3] = {&wqmap, &wkmap, &wvmap};
          for (int i = 0; i < 3; i++)
              ((EncFn)fn)(ms[i], CU_TENSOR_MAP_DATA_TYPE_BFLOAT16, 2, (void*)ws[i], dims, strides, box, es, CU_TENSOR_MAP_INTERLEAVE_NONE, CU_TENSOR_MAP_SWIZZLE_128B,
                          CU_TENSOR_MAP_L2_PROMOTION_L2_128B, CU_TENSOR_MAP_FLOAT_OOB_FILL_NONE); }
        xmap_ptr = (const void*)x; womap_ptr = (const void*)Wo; w_ptr[0] = Wq; w_ptr[1] = Wk; w_ptr[2] = Wv;
    }
    k_chain<<<96, 384, SM_TOTAL, st>>>(xmap, wqmap, wkmap, wvmap, womap, x, mem0);
    {
        cudaLaunchConfig_t cfg = {};
        cfg.gridDim = dim3(NAUX); cfg.blockDim = dim3(384); cfg.dynamicSmemBytes = AX_TOTAL; cfg.stream = st;
        cudaLaunchAttribute at[1];
        at[0].id = cudaLaunchAttributeProgrammaticStreamSerialization; at[0].val.programmaticStreamSerializationAllowed = 1;
        cfg.attrs = at; cfg.numAttrs = 1;
        cudaLaunchKernelEx(&cfg, k_aux, womap, x, A_re, A_im, B_re, B_im, C_re, C_im, log_dt, Dskip, gw, out);
    }
}
```

```cpp
#include <cuda_runtime.h>
#include <cuda_bf16.h>
#include <stdint.h>
#include <cuda.h>

typedef __nv_bfloat16 bf16;

#define SEQ 2048
#define DM 640
#define NH 32
#define DH 128
#define NM 8
#define SEG 32
#define NSEG 64
#define NST 128
#define HD 4096

__device__ bf16  g_b[SEQ * DM];
__device__ float g_g[SEQ];

__device__ __forceinline__ float bf2f(bf16 v) { return __bfloat162float(v); }
__device__ __forceinline__ uint32_t pack_bf16(float lo, float hi) {
    uint32_t r; asm("cvt.rn.bf16x2.f32 %0, %1, %2;" : "=r"(r) : "f"(hi), "f"(lo)); return r;
}
__device__ __forceinline__ uint32_t f2tf32(float x) { uint32_t r; asm("cvt.rna.tf32.f32 %0, %1;" : "=r"(r) : "f"(x)); return r; }
__device__ __forceinline__ void mma_tf32(float (&d)[4], uint32_t a0, uint32_t a1, uint32_t a2, uint32_t a3, uint32_t b0, uint32_t b1) {
    asm volatile("mma.sync.aligned.m16n8k8.row.col.f32.tf32.tf32.f32 {%0,%1,%2,%3}, {%4,%5,%6,%7}, {%8,%9}, {%0,%1,%2,%3};\n"
        : "+f"(d[0]), "+f"(d[1]), "+f"(d[2]), "+f"(d[3]) : "r"(a0), "r"(a1), "r"(a2), "r"(a3), "r"(b0), "r"(b1));
}
__device__ __forceinline__ void mma_bf16(float (&d)[4], uint32_t a0, uint32_t a1, uint32_t a2, uint32_t a3, uint32_t b0, uint32_t b1) {
    asm volatile("mma.sync.aligned.m16n8k16.row.col.f32.bf16.bf16.f32 {%0,%1,%2,%3}, {%4,%5,%6,%7}, {%8,%9}, {%0,%1,%2,%3};\n"
        : "+f"(d[0]), "+f"(d[1]), "+f"(d[2]), "+f"(d[3]) : "r"(a0), "r"(a1), "r"(a2), "r"(a3), "r"(b0), "r"(b1));
}
struct cf { float re, im; };
__device__ __forceinline__ cf cmul(cf a, cf b) { cf r; r.re = a.re * b.re - a.im * b.im; r.im = a.re * b.im + a.im * b.re; return r; }
__device__ __forceinline__ cf csq(cf a) { cf r; r.re = a.re * a.re - a.im * a.im; r.im = 2.f * a.re * a.im; return r; }
__device__ __forceinline__ cf cexpL(float zr, float zi, float L) {
    float e = __expf(zr * L);
    float ang = zi * L;
    float k = rintf(ang * 0.15915494309189535f);
    ang = fmaf(-k, 6.2831854820251465f, ang);
    ang = fmaf(-k, -1.7484555314695172e-07f, ang);
    cf r; r.re = e * __cosf(ang); r.im = e * __sinf(ang); return r;
}

#define SSM_CH 8
#define KC_PITCH 648
#define XS_PAD 128
#define XS_PITCH (XS_PAD + 2048 + 8)
#define YS_PITCH (2048 + 8)
#define KT_LEN (2048 + 48)
struct SsmSmem {
    float Kc[SSM_CH][KC_PITCH];
    bf16  xs[SSM_CH][XS_PITCH];
    union {
        bf16  KT[SSM_CH][2][KT_LEN];
        float st[SSM_CH][NST][8];
    } u;
    bf16  ys[SSM_CH][YS_PITCH];
    uint16_t kidx[2048];
};

__device__ __forceinline__ int kc_index(int l) {
    return l < 256 ? l : (l < 512 ? 256 + ((l - 256) >> 1) : (l < 1024 ? 384 + ((l - 512) >> 2) : 512 + ((l - 1024) >> 3)));
}

__device__ __forceinline__ void ssm_group(unsigned char* smem_raw, int grp, const bf16* __restrict__ x, const bf16* __restrict__ A_re, const bf16* __restrict__ A_im,
        const bf16* __restrict__ B_re, const bf16* __restrict__ B_im, const bf16* __restrict__ C_re, const bf16* __restrict__ C_im,
        const bf16* __restrict__ log_dt, const bf16* __restrict__ Dskip) {
    SsmSmem& S = *reinterpret_cast<SsmSmem*>(smem_raw);
    const int tid = threadIdx.x, w = tid >> 5, lane = tid & 31, g = lane >> 2, t = lane & 3;
    const int d0 = grp * SSM_CH;
    asm volatile("bar.sync 1, 256;" ::: "memory");
    #pragma unroll
    for (int it = 0; it < 8; it++) {
        const int l = tid + 256 * it;
        uint4 v = *reinterpret_cast<const uint4*>(x + (size_t)l * DM + d0);
        const bf16* p = reinterpret_cast<const bf16*>(&v);
        const int lr = (l & ~15) | (15 - (l & 15));
        #pragma unroll
        for (int c = 0; c < 8; c++) S.xs[c][XS_PAD + lr] = p[c];
        S.kidx[l] = (uint16_t)((int)bf2f(__float2bfloat16_rn((float)l)) == 2048 ? 640 : kc_index((int)bf2f(__float2bfloat16_rn((float)l))));
    }
    for (int i = tid; i < SSM_CH * XS_PAD / 2; i += 256) reinterpret_cast<uint32_t*>(&S.xs[i / (XS_PAD / 2)][0])[i % (XS_PAD / 2)] = 0u;
    {
        const int d = d0 + w;
        const float dt = bf2f(__float2bfloat16_rn(expf(bf2f(log_dt[d]))));
        #pragma unroll
        for (int i = 0; i < 4; i++) {
            const int n = lane + 32 * i;
            float zr = dt * bf2f(A_re[d * NST + n]), zi = dt * bf2f(A_im[d * NST + n]);
            cf dB; dB.re = dt * bf2f(B_re[d * NST + n]); dB.im = dt * bf2f(B_im[d * NST + n]);
            cf C; C.re = bf2f(C_re[d * NST + n]); C.im = bf2f(C_im[d * NST + n]);
            cf wv = cmul(C, dB);
            cf u8 = cexpL(zr, zi, 8.f), u128 = cexpL(zr, zi, 128.f);
            float* st = S.u.st[w][n];
            *reinterpret_cast<float4*>(st) = make_float4(zr, zi, wv.re, wv.im);
            *reinterpret_cast<float4*>(st + 4) = make_float4(u8.re, u8.im, u128.re, u128.im);
        }
        __syncwarp();
        float a0a[4] = {0, 0, 0, 0}, a0b[4] = {0, 0, 0, 0}, a1[4] = {0, 0, 0, 0}, a2a[4] = {0, 0, 0, 0}, a2b[4] = {0, 0, 0, 0};
        float k2048 = 0.f;
        const float Lg = (g < 4) ? (512.f + 4.f * g) : (g < 6 ? 1024.f + 8.f * (g - 4) : 1536.f + 8.f * (g - 6));
        #pragma unroll 4
        for (int kk = 0; kk < 32; kk++) {
            const float* st = S.u.st[w][4 * kk + t];
            float4 s0 = *reinterpret_cast<const float4*>(st), s1 = *reinterpret_cast<const float4*>(st + 4);
            cf wv; wv.re = s0.z; wv.im = s0.w;
            cf u8; u8.re = s1.x; u8.im = s1.y;
            cf u128; u128.re = s1.z; u128.im = s1.w;
            cf e1 = cexpL(s0.x, s0.y, (float)g);
            cf e23 = cexpL(s0.x, s0.y, Lg);
            cf e1b = cmul(e1, u8);
            cf e2 = csq(e1);
            cf p = csq(csq(csq(e2)));
            cf f0 = cmul(wv, p), f1 = cmul(f0, u128), f2 = cmul(f1, u128), f3 = cmul(f2, u128);
            uint32_t A00 = f2tf32(f0.re), A01 = f2tf32(f1.re), A02 = f2tf32(-f0.im), A03 = f2tf32(-f1.im);
            uint32_t A10 = f2tf32(f2.re), A11 = f2tf32(f3.re), A12 = f2tf32(-f2.im), A13 = f2tf32(-f3.im);
            mma_tf32(a0a, A00, A01, A02, A03, f2tf32(e1.re), f2tf32(e1.im));
            mma_tf32(a0b, A00, A01, A02, A03, f2tf32(e1b.re), f2tf32(e1b.im));
            mma_tf32(a1, A10, A11, A12, A13, f2tf32(e2.re), f2tf32(e2.im));
            uint32_t E0 = f2tf32(e23.re), E1 = f2tf32(e23.im);
            mma_tf32(a2a, A00, A01, A02, A03, E0, E1);
            mma_tf32(a2b, A10, A11, A12, A13, E0, E1);
            cf e2048 = csq(e23);
            k2048 += wv.re * e2048.re - wv.im * e2048.im;
        }
        k2048 += __shfl_xor_sync(~0u, k2048, 1);
        k2048 += __shfl_xor_sync(~0u, k2048, 2);
        float* Kc = S.Kc[w];
        Kc[16 * g + 2 * t] = a0a[0]; Kc[16 * g + 2 * t + 1] = a0a[1]; Kc[16 * (g + 8) + 2 * t] = a0a[2]; Kc[16 * (g + 8) + 2 * t + 1] = a0a[3];
        Kc[16 * g + 8 + 2 * t] = a0b[0]; Kc[16 * g + 8 + 2 * t + 1] = a0b[1]; Kc[16 * (g + 8) + 8 + 2 * t] = a0b[2]; Kc[16 * (g + 8) + 8 + 2 * t + 1] = a0b[3];
        Kc[256 + 8 * g + 2 * t] = a1[0]; Kc[256 + 8 * g + 2 * t + 1] = a1[1]; Kc[256 + 8 * (g + 8) + 2 * t] = a1[2]; Kc[256 + 8 * (g + 8) + 2 * t + 1] = a1[3];
        #pragma unroll
        for (int mt = 0; mt < 2; mt++) {
            #pragma unroll
            for (int e = 0; e < 4; e++) {
                int A = mt * 16 + g + (e >> 1) * 8, j = 2 * t + (e & 1);
                int Lj = (j < 4) ? 512 + 4 * j : (j < 6 ? 1024 + 8 * (j - 4) : 1536 + 8 * (j - 6));
                Kc[kc_index(Lj + 16 * A)] = mt ? a2b[e] : a2a[e];
            }
        }
        if (lane == 16) Kc[640] = k2048;
    }
    __syncwarp();
    {
        asm volatile("bar.sync 1, 256;" ::: "memory");
        bf16* k0 = S.u.KT[w][0];
        bf16* k1 = S.u.KT[w][1];
        const float* Kc = S.Kc[w];
        #pragma unroll 8
        for (int j = lane; j < 2048; j += 32) {
            const bf16 v = __float2bfloat16_rn(Kc[S.kidx[j]]);
            k0[16 + j] = v;
            k1[15 + j] = v;
        }
        if (lane < 16) { k0[lane] = __float2bfloat16_rn(0.f); if (lane < 15) k1[lane] = __float2bfloat16_rn(0.f); }
        k0[2064 + lane] = __float2bfloat16_rn(0.f); k1[2063 + lane] = __float2bfloat16_rn(0.f);
        __syncwarp();
    }
    {
        float acc[16][4];
        #pragma unroll
        for (int v = 0; v < 16; v++) { acc[v][0] = acc[v][1] = acc[v][2] = acc[v][3] = 0.f; }
        const bf16* kt = (g & 1) ? &S.u.KT[w][0][0] : &S.u.KT[w][1][0];
        const int ibase0 = g + 1 + 2 * t - ((g & 1) ? 0 : 1);
        #pragma unroll 1
        for (int r = 0; r < 8; r++) {
            uint32_t B[16][2];
            #pragma unroll
            for (int v = 0; v < 16; v++) {
                const bf16* p = &S.xs[w][XS_PAD + 16 * (8 * v + g - r) + 2 * t];
                B[v][0] = *reinterpret_cast<const uint32_t*>(p);
                B[v][1] = *reinterpret_cast<const uint32_t*>(p + 8);
            }
            #pragma unroll
            for (int q = 0; q < 16; q++) {
                const int i0 = ibase0 + 16 * r + 128 * q;
                const uint32_t A0 = *reinterpret_cast<const uint32_t*>(kt + i0);
                const uint32_t A1 = *reinterpret_cast<const uint32_t*>(kt + i0 + 8);
                const uint32_t A3 = *reinterpret_cast<const uint32_t*>(kt + i0 + 16);
                #pragma unroll
                for (int v = q; v < 16; v++) mma_bf16(acc[v], A0, A1, A1, A3, B[v - q][0], B[v - q][1]);
            }
        }
        bf16* ys = S.ys[w];
        #pragma unroll
        for (int v = 0; v < 16; v++) {
            const int a = 8 * v + 2 * t;
            ys[16 * a + g] = __float2bfloat16_rn(acc[v][0]); ys[16 * (a + 1) + g] = __float2bfloat16_rn(acc[v][1]);
            ys[16 * a + g + 8] = __float2bfloat16_rn(acc[v][2]); ys[16 * (a + 1) + g + 8] = __float2bfloat16_rn(acc[v][3]);
        }
    }
    asm volatile("bar.sync 1, 256;" ::: "memory");
    {
        float dsk[8];
        #pragma unroll
        for (int c = 0; c < 8; c++) dsk[c] = bf2f(Dskip[d0 + c]);
        #pragma unroll 2
        for (int it = 0; it < 8; it++) {
            const int l = tid + 256 * it;
            const int lr = XS_PAD + ((l & ~15) | (15 - (l & 15)));
            float o[8];
            #pragma unroll
            for (int c = 0; c < 8; c++) o[c] = bf2f(S.ys[c][l]) + bf2f(__float2bfloat16_rn(bf2f(S.xs[c][lr]) * dsk[c]));
            *reinterpret_cast<uint4*>(g_b + (size_t)l * DM + d0) = make_uint4(pack_bf16(o[0], o[1]), pack_bf16(o[2], o[3]), pack_bf16(o[4], o[5]), pack_bf16(o[6], o[7]));
        }
    }
}

__device__ __forceinline__ uint32_t smem_u32(const void* p) { return (uint32_t)__cvta_generic_to_shared(p); }
__device__ __forceinline__ void mbar_init(uint32_t bar, uint32_t cnt) { asm volatile("mbarrier.init.shared::cta.b64 [%0], %1;" :: "r"(bar), "r"(cnt) : "memory"); }
__device__ __forceinline__ void mbar_expect_tx(uint32_t bar, uint32_t bytes) { asm volatile("mbarrier.arrive.expect_tx.shared::cta.b64 _, [%0], %1;" :: "r"(bar), "r"(bytes) : "memory"); }
__device__ __forceinline__ void mbar_arrive(uint32_t bar) { asm volatile("mbarrier.arrive.shared::cta.b64 _, [%0];" :: "r"(bar) : "memory"); }
__device__ __forceinline__ void mbar_wait(uint32_t bar, uint32_t parity) {
    uint32_t ok; int guard = 0;
    do {
        asm volatile("{\n.reg .pred P1;\nmbarrier.test_wait.parity.shared::cta.b64 P1, [%1], %2;\nselp.u32 %0,1,0,P1;\n}" : "=r"(ok) : "r"(bar), "r"(parity) : "memory");
    } while (!ok && ++guard < (1 << 26));
}
__device__ __forceinline__ void mbar_wait_sleep(uint32_t bar, uint32_t parity) {
    uint32_t ok; int guard = 0;
    do {
        asm volatile("{\n.reg .pred P1;\nmbarrier.try_wait.parity.shared::cta.b64 P1, [%1], %2;\nselp.u32 %0,1,0,P1;\n}" : "=r"(ok) : "r"(bar), "r"(parity) : "memory");
    } while (!ok && ++guard < (1 << 22));
}
__device__ __forceinline__ uint32_t mapa(uint32_t addr, uint32_t rank) { uint32_t r; asm volatile("mapa.shared::cluster.u32 %0, %1, %2;" : "=r"(r) : "r"(addr), "r"(rank)); return r; }
__device__ __forceinline__ void st_async4(uint32_t addr, float a, float b, float c, float d, uint32_t bar) {
    asm volatile("st.async.weak.shared::cluster.mbarrier::complete_tx::bytes.v4.f32 [%0], {%1,%2,%3,%4}, [%5];" :: "r"(addr), "f"(a), "f"(b), "f"(c), "f"(d), "r"(bar) : "memory");
}
__device__ __forceinline__ void bulk_s2c(uint32_t dst, uint32_t src, uint32_t bytes, uint32_t bar) {
    asm volatile("cp.async.bulk.shared::cluster.shared::cta.mbarrier::complete_tx::bytes [%0], [%1], %2, [%3];" :: "r"(dst), "r"(src), "r"(bytes), "r"(bar) : "memory");
}
__device__ __forceinline__ void bulk_g2s(uint32_t dst, const void* src, uint32_t bytes, uint32_t bar) {
    asm volatile("cp.async.bulk.shared::cluster.global.mbarrier::complete_tx::bytes [%0], [%1], %2, [%3];" :: "r"(dst), "l"(src), "r"(bytes), "r"(bar) : "memory");
}
__device__ __forceinline__ void bulk_s2g(void* dst, uint32_t src, uint32_t bytes) {
    asm volatile("cp.async.bulk.global.shared::cta.bulk_group [%0], [%1], %2;" :: "l"(dst), "r"(src), "r"(bytes) : "memory");
}
__device__ __forceinline__ void bulk_commit() { asm volatile("cp.async.bulk.commit_group;" ::: "memory"); }
__device__ __forceinline__ void bulk_wait_read0() { asm volatile("cp.async.bulk.wait_group.read 0;" ::: "memory"); }
__device__ __forceinline__ void bulk_wait0() { asm volatile("cp.async.bulk.wait_group 0;" ::: "memory"); }
__device__ __forceinline__ void fence_async() { asm volatile("fence.proxy.async.shared::cta;" ::: "memory"); }
__device__ __forceinline__ void nbar_sync(int id, int n) { asm volatile("bar.sync %0, %1;" :: "r"(id), "r"(n) : "memory"); }
__device__ __forceinline__ void nbar_arrive(int id, int n) { asm volatile("bar.arrive %0, %1;" :: "r"(id), "r"(n) : "memory"); }
__device__ __forceinline__ void cp_async16(uint32_t dst, const void* src) { asm volatile("cp.async.cg.shared.global [%0], [%1], 16;" :: "r"(dst), "l"(src) : "memory"); }
__device__ __forceinline__ void cp_async_wait_all() { asm volatile("cp.async.wait_all;" ::: "memory"); }
__device__ __forceinline__ void ldsm4(uint32_t (&r)[4], uint32_t addr) {
    asm volatile("ldmatrix.sync.aligned.m8n8.x4.shared.b16 {%0,%1,%2,%3}, [%4];" : "=r"(r[0]), "=r"(r[1]), "=r"(r[2]), "=r"(r[3]) : "r"(addr) : "memory");
}
__device__ __forceinline__ void ldsm4t(uint32_t (&r)[4], uint32_t addr) {
    asm volatile("ldmatrix.sync.aligned.m8n8.x4.trans.shared.b16 {%0,%1,%2,%3}, [%4];" : "=r"(r[0]), "=r"(r[1]), "=r"(r[2]), "=r"(r[3]) : "r"(addr) : "memory");
}
__device__ __forceinline__ void stsm2t(uint32_t addr, uint32_t r0, uint32_t r1) {
    asm volatile("stmatrix.sync.aligned.m8n8.x2.trans.shared.b16 [%0], {%1,%2};" :: "r"(addr), "r"(r0), "r"(r1) : "memory");
}
__device__ __forceinline__ uint4 ld_relaxed4(const void* p) { uint4 v; asm volatile("ld.relaxed.gpu.global.v4.u32 {%0,%1,%2,%3}, [%4];" : "=r"(v.x), "=r"(v.y), "=r"(v.z), "=r"(v.w) : "l"(p) : "memory"); return v; }
__device__ __forceinline__ void st_relaxed2(void* p, uint32_t a, uint32_t b) { asm volatile("st.relaxed.gpu.global.v2.u32 [%0], {%1,%2};" :: "l"(p), "r"(a), "r"(b) : "memory"); }
__device__ __forceinline__ void st_relaxed1(void* p, uint32_t a) { asm volatile("st.relaxed.gpu.global.u32 [%0], %1;" :: "l"(p), "r"(a) : "memory"); }
__device__ __forceinline__ unsigned ld_acquire(const unsigned* p) { unsigned v; asm volatile("ld.acquire.gpu.global.u32 %0, [%1];" : "=r"(v) : "l"(p) : "memory"); return v; }
__device__ __forceinline__ float ex2_approx(float x) { float r; asm("ex2.approx.ftz.f32 %0, %1;" : "=f"(r) : "f"(x)); return r; }
__device__ __forceinline__ uint64_t make_desc(uint32_t saddr, uint32_t lbo, uint32_t sbo) {
    return (uint64_t)((saddr & 0x3FFFF) >> 4) | ((uint64_t)((lbo & 0x3FFFF) >> 4) << 16) | ((uint64_t)((sbo & 0x3FFFF) >> 4) << 32) | (1ull << 62);
}
__device__ __forceinline__ void wg_fence() { asm volatile("wgmma.fence.sync.aligned;" ::: "memory"); }
__device__ __forceinline__ void wg_commit() { asm volatile("wgmma.commit_group.sync.aligned;" ::: "memory"); }
__device__ __forceinline__ void wg_wait0() { asm volatile("wgmma.wait_group.sync.aligned 0;" ::: "memory"); }
__device__ __forceinline__ void wgmma_n40_tA(float (&d)[20], uint64_t da, uint64_t db, int scale_d) {
    asm volatile("{\n.reg .pred p;\nsetp.ne.b32 p, %22, 0;\n"
        "wgmma.mma_async.sync.aligned.m64n40k16.f32.bf16.bf16 {%0,%1,%2,%3,%4,%5,%6,%7,%8,%9,%10,%11,%12,%13,%14,%15,%16,%17,%18,%19}, %20, %21, p, 1, 1, 1, 0;\n}\n"
        : "+f"(d[0]), "+f"(d[1]), "+f"(d[2]), "+f"(d[3]), "+f"(d[4]), "+f"(d[5]), "+f"(d[6]), "+f"(d[7]), "+f"(d[8]), "+f"(d[9]),
          "+f"(d[10]), "+f"(d[11]), "+f"(d[12]), "+f"(d[13]), "+f"(d[14]), "+f"(d[15]), "+f"(d[16]), "+f"(d[17]), "+f"(d[18]), "+f"(d[19])
        : "l"(da), "l"(db), "r"(scale_d));
}

#define NRED 80
#define CAL_THR 410u
#define COMM_REGS "40"
#define NPOOL 576
#define RPS 1
__device__ __align__(4096) uint32_t g_pool[(NPOOL + 1) * 1024];
__device__ unsigned g_cls[NPOOL];
__device__ unsigned g_side[96];
__device__ unsigned g_calcnt;
__device__ unsigned g_epoch;
__device__ unsigned g_flag[NSEG][NH];
__device__ __align__(1024) bf16 g_Qimg[NSEG * NH * 2 * 32 * 64];
__device__ __align__(1024) bf16 g_Kimg[NSEG * NH * 2 * 40 * 64];
__device__ __align__(1024) bf16 g_Vimg[NSEG * NH * 2 * 40 * 64];

#define SM_XB    0
#define SM_VT    81920
#define SM_KT    (SM_VT + 20480)
#define SM_QT    (SM_KT + 10240)
#define SM_QS    (SM_QT + 4096)
#define SM_MEMB  (SM_QS + 1024)
#define SM_RED   (SM_MEMB + 10240)
#define SM_SC    (SM_RED + 16384)
#define SM_CRED  (SM_SC + 5120)
#define SM_PB    (SM_CRED + 1024)
#define SM_TRACE (SM_PB + 1024)
#define SM_WO    163840
#define SM_BAR   (SM_WO + 65536)
#define SM_TPM   (SM_BAR + 256)
#define SM_TRD   (SM_TPM + 256)
#define SM_TPUB  (SM_TRD + 16)
#define SM_TGAT  (SM_TPUB + 128)
#define SM_CAL   (SM_TGAT + 64)
#define SM_TOTAL (SM_CAL + 128)
#define B_SC   (SM_BAR + 0)
#define B_V    (SM_BAR + 16)
#define B_P    (SM_BAR + 48)
#define B_X    (SM_BAR + 56)
#define B_EXP  (SM_BAR + 72)

#define TR(ev) do {} while (0)
__device__ __forceinline__ uint32_t tag_of(int s) { return (uint32_t)(((s >> 1) & 1) + 1); }
__device__ __forceinline__ unsigned probe_latency(uint32_t* p, uint32_t zero) {
    uint32_t v, best = 0xffffffffu;
    asm volatile("atom.relaxed.gpu.global.add.u32 %0, [%1], 0;" : "=r"(v) : "l"(p) : "memory");
    #pragma unroll 1
    for (int r = 0; r < 4; r++) {
        uint32_t c0, c1;
        asm volatile("mov.u32 %0, %%clock;" : "=r"(c0) : "r"(v) : "memory");
        asm volatile("atom.relaxed.gpu.global.add.u32 %0, [%1], 0;" : "=r"(v) : "l"(p + ((v + c0) & zero)) : "memory");
        asm volatile("{\n.reg .u32 t;\nand.b32 t, %1, %2;\nmov.u32 %0, %%clock;\nadd.u32 %0, %0, t;\n}" : "=r"(c1) : "r"(v), "r"(zero) : "memory");
        best = min(best, c1 - c0);
    }
    return best;
}
__device__ __forceinline__ void cluster_sync_all() { asm volatile("barrier.cluster.arrive.release.aligned;\nbarrier.cluster.wait.acquire.aligned;" ::: "memory"); }
__device__ __forceinline__ void tma_load_2d(uint32_t dst, const void* map, int c0, int c1, uint32_t bar) {
    asm volatile("cp.async.bulk.tensor.2d.shared::cluster.global.mbarrier::complete_tx::bytes [%0], [%1, {%3, %4}], [%2];"
        :: "r"(dst), "l"(map), "r"(bar), "r"(c0), "r"(c1) : "memory");
}
__device__ __forceinline__ void tma_load_3d(uint32_t dst, const void* map, int c0, int c1, int c2, uint32_t bar) {
    asm volatile("cp.async.bulk.tensor.3d.shared::cluster.global.mbarrier::complete_tx::bytes [%0], [%1, {%3, %4, %5}], [%2];"
        :: "r"(dst), "l"(map), "r"(bar), "r"(c0), "r"(c1), "r"(c2) : "memory");
}
__device__ __forceinline__ void stsm4t(uint32_t addr, uint32_t r0, uint32_t r1, uint32_t r2, uint32_t r3) {
    asm volatile("stmatrix.sync.aligned.m8n8.x4.trans.shared.b16 [%0], {%1,%2,%3,%4};" :: "r"(addr), "r"(r0), "r"(r1), "r"(r2), "r"(r3) : "memory");
}
__device__ __forceinline__ void wgmma_n32_rs(float (&d)[16], const uint32_t (&a)[4], uint64_t db, int scale_d) {
    asm volatile("{\n.reg .pred p;\nsetp.ne.b32 p, %21, 0;\n"
        "wgmma.mma_async.sync.aligned.m64n32k16.f32.bf16.bf16 {%0,%1,%2,%3,%4,%5,%6,%7,%8,%9,%10,%11,%12,%13,%14,%15}, {%16,%17,%18,%19}, %20, p, 1, 1, 0;\n}\n"
        : "+f"(d[0]), "+f"(d[1]), "+f"(d[2]), "+f"(d[3]), "+f"(d[4]), "+f"(d[5]), "+f"(d[6]), "+f"(d[7]),
          "+f"(d[8]), "+f"(d[9]), "+f"(d[10]), "+f"(d[11]), "+f"(d[12]), "+f"(d[13]), "+f"(d[14]), "+f"(d[15])
        : "r"(a[0]), "r"(a[1]), "r"(a[2]), "r"(a[3]), "l"(db), "r"(scale_d));
}

__device__ __forceinline__ void st_async4u(uint32_t addr, uint4 v, uint32_t bar) {
    asm volatile("st.async.weak.shared::cluster.mbarrier::complete_tx::bytes.v4.u32 [%0], {%1,%2,%3,%4}, [%5];" :: "r"(addr), "r"(v.x), "r"(v.y), "r"(v.z), "r"(v.w), "r"(bar) : "memory");
}
__device__ __forceinline__ void export_issue(uint32_t sb, int s, int h, uint32_t rank) {
    const size_t img = (size_t)(s * NH + h) * 2;
    const int sl = s & 1;
    if (rank == 2) {
        bulk_s2g(g_Vimg + img * 2560, sb + SM_VT + sl * 10240, 5120);
        bulk_s2g(g_Vimg + (img + 1) * 2560, sb + SM_VT + sl * 10240 + 5120, 5120);
    } else {
        bulk_s2g(g_Qimg + (img + rank) * 2048, sb + SM_QT, 4096);
        bulk_s2g(g_Kimg + (img + rank) * 2560, sb + SM_KT + sl * 5120, 5120);
    }
    bulk_commit();
    bulk_wait_read0();
    mbar_arrive(sb + B_EXP);
}
__device__ __forceinline__ void export_signal(int s, int h) {
    bulk_wait0();
    asm volatile("fence.proxy.async;" ::: "memory");
    __threadfence();
    atomicAdd(&g_flag[s][h], 1u);
}

__device__ __forceinline__ void score_tile(uint32_t sb, int sl, int nt, int lane, uint32_t rank) {
    float sc[4] = {0, 0, 0, 0}, sd[4] = {0, 0, 0, 0};
    const int r = lane & 7;
    uint32_t qa[2][4], kb[2][4];
    #pragma unroll
    for (int j = 0; j < 2; j++) {
        const int chunk = (lane >> 3) + 4 * j;
        ldsm4(kb[j], sb + SM_KT + sl * 5120 + (8 * nt + r) * 128 + ((chunk ^ r) << 4));
        ldsm4(qa[j], sb + SM_QS + r * 128 + ((chunk ^ r) << 4));
    }
    mma_bf16(sc, qa[0][0], 0u, qa[0][1], 0u, kb[0][0], kb[0][1]);
    mma_bf16(sd, qa[1][0], 0u, qa[1][1], 0u, kb[1][0], kb[1][1]);
    mma_bf16(sc, qa[0][2], 0u, qa[0][3], 0u, kb[0][2], kb[0][3]);
    mma_bf16(sd, qa[1][2], 0u, qa[1][3], 0u, kb[1][2], kb[1][3]);
    sc[0] += sd[0]; sc[1] += sd[1];
    const float o0 = __shfl_down_sync(~0u, sc[0], 1), o1 = __shfl_down_sync(~0u, sc[1], 1);
    if ((lane & 1) == 0) {
        const uint32_t a = SM_SC + sl * 2560 + rank * 1280 + ((lane >> 2) * 40 + 8 * nt + 2 * (lane & 3)) * 4;
        const uint32_t bo = B_SC + 8 * sl;
        { const uint32_t rb = mapa(sb, 2); st_async4(rb + a, sc[0], sc[1], o0, o1, rb + bo); }
        { const uint32_t rb = mapa(sb, rank ^ 1); st_async4(rb + a, sc[0], sc[1], o0, o1, rb + bo); }
        asm volatile("st.shared.v4.f32 [%0], {%1,%2,%3,%4};" :: "r"(sb + a), "f"(sc[0]), "f"(sc[1]), "f"(o0), "f"(o1) : "memory");
    }
    __syncwarp();
    if (lane == 0) mbar_arrive(sb + B_SC + 8 * sl);
}
__device__ __forceinline__ void wgmma_n40_rs(float (&d)[20], const uint32_t (&a)[4], uint64_t db, int scale_d) {
    asm volatile("{\n.reg .pred p;\nsetp.ne.b32 p, %25, 0;\n"
        "wgmma.mma_async.sync.aligned.m64n40k16.f32.bf16.bf16 {%0,%1,%2,%3,%4,%5,%6,%7,%8,%9,%10,%11,%12,%13,%14,%15,%16,%17,%18,%19}, {%20,%21,%22,%23}, %24, p, 1, 1, 0;\n}\n"
        : "+f"(d[0]), "+f"(d[1]), "+f"(d[2]), "+f"(d[3]), "+f"(d[4]), "+f"(d[5]), "+f"(d[6]), "+f"(d[7]), "+f"(d[8]), "+f"(d[9]),
          "+f"(d[10]), "+f"(d[11]), "+f"(d[12]), "+f"(d[13]), "+f"(d[14]), "+f"(d[15]), "+f"(d[16]), "+f"(d[17]), "+f"(d[18]), "+f"(d[19])
        : "r"(a[0]), "r"(a[1]), "r"(a[2]), "r"(a[3]), "l"(db), "r"(scale_d));
}
__device__ __forceinline__ void pu_mma(float (&o)[4], const float (&u)[20], const uint32_t (&pb)[5]) {
    float o2[4] = {0, 0, 0, 0};
    o[0] = o[1] = o[2] = o[3] = 0.f;
    mma_bf16(o, pack_bf16(u[0], u[1]), pack_bf16(u[2], u[3]), pack_bf16(u[4], u[5]), pack_bf16(u[6], u[7]), pb[0], pb[1]);
    mma_bf16(o2, pack_bf16(u[8], u[9]), pack_bf16(u[10], u[11]), pack_bf16(u[12], u[13]), pack_bf16(u[14], u[15]), pb[2], pb[3]);
    mma_bf16(o, pack_bf16(u[16], u[17]), pack_bf16(u[18], u[19]), 0u, 0u, pb[4], 0u);
    o[0] += o2[0]; o[1] += o2[1]; o[2] += o2[2]; o[3] += o2[3];
}
__device__ __forceinline__ void pu_store(const float (&o)[4], float2 inv, uint2 off, int lane, uint32_t tg) {
    unsigned char* pool = reinterpret_cast<unsigned char*>(g_pool) + lane * 8;
    st_relaxed2(pool + off.x, (__float_as_uint(o[0] * inv.x) & ~3u) | tg, (__float_as_uint(o[1] * inv.y) & ~3u) | tg);
    st_relaxed2(pool + off.y, (__float_as_uint(o[2] * inv.x) & ~3u) | tg, (__float_as_uint(o[3] * inv.y) & ~3u) | tg);
}
__device__ __forceinline__ float rcp_approx(float x) { float r; asm("rcp.approx.ftz.f32 %0, %1;" : "=f"(r) : "f"(x)); return r; }
template <int NT>
__device__ __forceinline__ void u_pass(unsigned char* smem, uint32_t sb, int s, uint32_t rank, int wg, int warp, int lane) {
    const int sl = s & 1;
#define NRS_V 6
    constexpr int NRS = NRS_V;
    uint32_t wa[NRS][4];
    {
        const int mi = lane >> 3, chunk = 2 * warp + (mi & 1);
        #pragma unroll
        for (int ks = 0; ks < NRS; ks++) {
            const int row = 16 * ks + (mi >> 1) * 8 + (lane & 7);
            ldsm4t(wa[ks], sb + SM_WO + (2 * wg) * 16384 + row * 128 + ((chunk ^ (row & 7)) << 4));
        }
    }
    if (rank < 2) { mbar_wait(sb + B_V + 8 * sl, (s >> 1) & 1); fence_async(); }
    if (wg == 0 && warp == 0) TR(4);
    float U0[20];
    wg_fence();
    #pragma unroll
    for (int ks = 0; ks < NRS; ks++)
        wgmma_n40_rs(U0, wa[ks], make_desc(sb + SM_VT + sl * 10240 + (ks >> 2) * 5120 + (ks & 3) * 32, 16, 1024), ks > 0);
    #pragma unroll
    for (int ks = NRS; ks < 8; ks++)
        wgmma_n40_tA(U0, make_desc(sb + SM_WO + (2 * wg) * 16384 + ks * 2048, 1024, 1024),
                     make_desc(sb + SM_VT + sl * 10240 + (ks >> 2) * 5120 + (ks & 3) * 32, 16, 1024), 1);
    wg_commit();
    const uint32_t tg = tag_of(s);
    uint32_t pb[5];
    float sm[4], sm2[4];
    auto get_p = [&]() {
        nbar_sync(9, 288);
        const uint32_t* pbs = reinterpret_cast<const uint32_t*>(smem + SM_PB);
        #pragma unroll
        for (int q = 0; q < 5; q++) pb[q] = pbs[q * 32 + lane];
        sm[0] = sm[1] = sm[2] = sm[3] = 0.f; sm2[0] = sm2[1] = sm2[2] = sm2[3] = 0.f;
        const uint32_t one = 0x3f803f80u;
        mma_bf16(sm, one, one, one, one, pb[0], pb[1]);
        mma_bf16(sm2, one, one, one, one, pb[2], pb[3]);
        mma_bf16(sm, one, one, 0u, 0u, pb[4], 0u);
    };
    const uint2* tpm = reinterpret_cast<const uint2*>(smem + SM_TPM) + (sl * 4 + 2 * wg) * 4 + warp;
    if (NT == 2) {
        wg_wait0();
        float U1[20];
        wg_fence();
        #pragma unroll
        for (int ks = 0; ks < 8; ks++)
            wgmma_n40_tA(U1, make_desc(sb + SM_WO + (2 * wg + 1) * 16384 + ks * 2048, 1024, 1024),
                         make_desc(sb + SM_VT + sl * 10240 + (ks >> 2) * 5120 + (ks & 3) * 32, 16, 1024), ks > 0);
        wg_commit();
        const uint2 off0 = tpm[0], off1 = tpm[4];
        get_p();
        float o0[4], o1[4];
        pu_mma(o0, U0, pb);
        wg_wait0();
        pu_mma(o1, U1, pb);
        const float2 inv = make_float2(rcp_approx(sm[0] + sm2[0]), rcp_approx(sm[1] + sm2[1]));
        if (wg == 0 && warp == 0) TR(8);
        pu_store(o0, inv, off0, lane, tg);
        pu_store(o1, inv, off1, lane, tg);
        if (wg == 0 && warp == 0) TR(6);
    } else {
        const uint2 off0 = tpm[0];
        wg_wait0();
        get_p();
        float o0[4];
        pu_mma(o0, U0, pb);
        const float2 inv = make_float2(rcp_approx(sm[0] + sm2[0]), rcp_approx(sm[1] + sm2[1]));
        pu_store(o0, inv, off0, lane, tg);
    }
}

__global__ void __cluster_dims__(3, 1, 1) __launch_bounds__(384, 1)
k_chain(const __grid_constant__ CUtensorMap xmap, const __grid_constant__ CUtensorMap wqmap, const __grid_constant__ CUtensorMap wkmap,
        const __grid_constant__ CUtensorMap wvmap, const __grid_constant__ CUtensorMap womap, const bf16* __restrict__ xptr, const bf16* __restrict__ mem0) {
    extern __shared__ __align__(1024) unsigned char smem[];
    const uint32_t sb = smem_u32(smem);
    const int tid = threadIdx.x, lane = tid & 31;
    const int wg = __shfl_sync(~0u, tid >> 7, 0), warp = __shfl_sync(~0u, (tid >> 5) & 3, 0);
    uint32_t rank; asm volatile("mov.u32 %0, %%cluster_ctarank;" : "=r"(rank));
    const int cta = blockIdx.x, h = cta / 3;
    asm volatile("griddepcontrol.launch_dependents;");
    if (tid == 0) {
        for (int i = 0; i < 2; i++) { mbar_init(sb + B_SC + 8 * i, rank < 2 ? 6 : 1); mbar_init(sb + B_V + 8 * i, 1); mbar_init(sb + B_X + 8 * i, 1); }
        mbar_init(sb + B_P, 1); mbar_init(sb + B_EXP, 1);
        asm volatile("fence.mbarrier_init.release.cluster;" ::: "memory");
    }
    if (tid < 80) asm volatile("prefetch.global.L2 [%0];" :: "l"(mem0 + tid * 64));
    if (h < 2) { for (int i = tid; i < 320; i += 384) asm volatile("prefetch.global.L2 [%0];" :: "l"(xptr + (size_t)h * 32 * DM + i * 64)); }
    {
        const int w12 = tid >> 5;
        if (lane == 0 && w12 < 7) {
            uint32_t* pp = (w12 < 6) ? g_pool + (size_t)(cta * 6 + w12) * 1024 + 512 : g_pool + (size_t)NPOOL * 1024 + (cta & 31) * 32 + (cta >> 5) * 8;
            const unsigned lat = probe_latency(pp, blockIdx.y);
            if (w12 < 6) g_cls[cta * 6 + w12] = lat > CAL_THR ? 1u : 0u; else g_side[cta] = lat > CAL_THR ? 1u : 0u;
        }
        __syncwarp();
        uint4* z = reinterpret_cast<uint4*>(g_pool + (size_t)cta * 6 * 1024);
        #pragma unroll
        for (int q = 0; q < 4; q++) z[tid + 384 * q] = make_uint4(0, 0, 0, 0);
        __threadfence();
        __syncwarp();
        if (lane == 0) atomicAdd(&g_calcnt, 1u);
    }
    __syncthreads();
    if (tid == 0) {
        const int ntile = (rank == 2) ? 4 : 3;
        const int tile0 = (rank == 2) ? 0 : (rank == 0 ? 4 : 7);
        mbar_expect_tx(sb + B_P, 163840 + ntile * 16384);
        const void* m0 = (rank == 2) ? &wvmap : &wqmap;
        const void* m1 = (rank == 2) ? &wvmap : &wkmap;
        const int c0 = h * DH + (rank == 1 ? 64 : 0), c1 = h * DH + (rank == 0 ? 0 : 64);
        for (int b = 0; b < 5; b++) {
            tma_load_2d(sb + b * 16384, m0, c0, b * 128, sb + B_P);
            tma_load_2d(sb + 81920 + b * 16384, m1, c1, b * 128, sb + B_P);
        }
        for (int lt = 0; lt < ntile; lt++) {
            tma_load_2d(sb + SM_WO + lt * 16384, &womap, (tile0 + lt) * 64, h * DH, sb + B_P);
            tma_load_2d(sb + SM_WO + lt * 16384 + 8192, &womap, (tile0 + lt) * 64, h * DH + 64, sb + B_P);
        }
    }
    {
        const int tile0 = (rank == 2) ? 0 : (rank == 0 ? 4 : 7);
        if (wg == 2) {
            const int ct = tid & 127;
            if (ct == 0) {
                const unsigned target = (*reinterpret_cast<volatile unsigned*>(&g_epoch) + 1u) * (96u * 12u);
                int guard = 0;
                while ((int)(ld_acquire(&g_calcnt) - target) < 0 && ++guard < (1 << 22)) {}
            }
            nbar_sync(4, 128);
            uint32_t* bm = reinterpret_cast<uint32_t*>(smem + SM_CAL);
            {
                unsigned v[5];
                #pragma unroll
                for (int q = 0; q < 5; q++) { const int b = ct + 128 * q; v[q] = (b < NPOOL) ? (__ldcg(&g_cls[b]) ^ __ldcg(&g_side[b / 6])) : 0u; }
                const unsigned sv = (ct < 96) ? __ldcg(&g_side[ct]) : 0u;
                #pragma unroll
                for (int q = 0; q < 5; q++) { const unsigned m = __ballot_sync(~0u, v[q] & 1u); if (lane == 0 && q * 4 + warp < 18) bm[q * 4 + warp] = m; }
                const unsigned m = __ballot_sync(~0u, sv & 1u);
                if (lane == 0 && warp < 3) bm[18 + warp] = m;
            }
            nbar_sync(4, 128);
            int nblk1 = 0;
            for (int i = 0; i < 18; i++) nblk1 += __popc(bm[i]);
            const unsigned red_last = (1u << (NRED - 64)) - 1u;
            const int nred1 = __popc(bm[18]) + __popc(bm[19]) + __popc(bm[20] & red_last);
            auto side_of = [&](int c) -> int { return (bm[18 + (c >> 5)] >> (c & 31)) & 1; };
            auto rank_of = [&](int c) -> int {
                int ones = 0;
                for (int i = 0; i < (c >> 5); i++) ones += __popc(bm[18 + i]);
                ones += __popc(bm[18 + (c >> 5)] & ((1u << (c & 31)) - 1u));
                return side_of(c) ? ones : c - ones;
            };
            auto nth = [&](int side, int idx) -> uint32_t {
                for (int i = 0; i < 18; i++) {
                    const unsigned m = side ? bm[i] : ~bm[i];
                    const int n = __popc(m);
                    if (idx < n) return (uint32_t)(i * 32 + __fns(m, 0, idx + 1));
                    idx -= n;
                }
                return 0u;
            };
            auto phys = [&](int side, int idx) -> uint32_t {
                const int c = side ? nblk1 : NPOOL - nblk1;
                return (idx < c) ? nth(side, idx) : nth(side ^ 1, (NPOOL - c) - 1 - (idx - c));
            };
            const int e = ct;
            if (e < 64) {
                const int slot = e >> 5, lt = (e >> 3) & 3, w = (e >> 1) & 3, hf = e & 1;
                const int tile = min(tile0 + lt, 9);
                const int r = 2 * (4 * tile + w) + hf;
                reinterpret_cast<uint32_t*>(smem + SM_TPM)[e] = phys(side_of(r), 4 * rank_of(r) + slot * 2 + (h >> 4)) * 4096u + (h & 15) * 256u;
            } else if (e < 68) {
                const int i = e - 64;
                reinterpret_cast<uint32_t*>(smem + SM_TRD)[i] = (cta < NRED) ? phys(side_of(cta), 4 * rank_of(cta) + i) * 4096u : 0u;
            } else if (e < 100) {
                const int i = e - 68, slot = i >> 3, rep = i & 7, side = (rep / RPS) & 1;
                reinterpret_cast<uint32_t*>(smem + SM_TPUB)[i] = phys(side, 4 * (side ? nred1 : NRED - nred1) + (slot * RPS + (rep % RPS)) * 3 + (cta >> 5)) * 4096u + (cta & 31) * 128u;
            } else if (e < 112) {
                const int i = e - 100, slot = i / 3, b = i % 3, side = side_of(cta);
                reinterpret_cast<uint32_t*>(smem + SM_TGAT)[slot * 4 + b] = phys(side, 4 * (side ? nred1 : NRED - nred1) + (slot * RPS + (h % RPS)) * 3 + b) * 4096u;
            }
        }
    }
    __syncthreads();
    mbar_wait_sleep(sb + B_P, 0);

    if (wg == 2) {
        asm volatile("setmaxnreg.dec.sync.aligned.u32 " COMM_REGS ";");
        const int ct = tid & 127;
        nbar_sync(5, 384);
        for (int c = ct; c < 640; c += 128) {
            int ks = c >> 4, hf = (c >> 3) & 1, r = c & 7;
            *reinterpret_cast<uint4*>(smem + SM_MEMB + c * 16) = *reinterpret_cast<const uint4*>(mem0 + r * DM + ks * 16 + hf * 8);
        }
        if (ct == 0) {
            for (int sg = 0; sg < 2; sg++) {
                mbar_expect_tx(sb + B_X + 8 * sg, 40960);
                tma_load_3d(sb + SM_XB + sg * 40960, &xmap, 0, sg * 32, 0, sb + B_X + 8 * sg);
            }
            mbar_expect_tx(sb + B_SC, rank < 2 ? 1280 : 2560);
            if (rank < 2) mbar_expect_tx(sb + B_V, 8192 + 2048);
        }
        nbar_sync(5, 384);
        cluster_sync_all();
        unsigned char* const pool = reinterpret_cast<unsigned char*>(g_pool);
        for (int s = 0; s < NSEG - 1; s++) {
            if (warp == 1) nbar_sync(12, 288);
            if (warp == 0) {
                const int g = lane >> 2, t = lane & 3;
                mbar_wait(sb + B_SC + 8 * (s & 1), (s >> 1) & 1);
                TR(5);
                const uint32_t sa = sb + SM_SC + (s & 1) * 2560 + (g * 40 + 2 * t) * 4;
                float v[5][2], u[5][2];
                #pragma unroll
                for (int q = 0; q < 5; q++) {
                    asm volatile("ld.shared.v2.f32 {%0,%1}, [%2];" : "=f"(v[q][0]), "=f"(v[q][1]) : "r"(sa + 32 * q) : "memory");
                    asm volatile("ld.shared.v2.f32 {%0,%1}, [%2];" : "=f"(u[q][0]), "=f"(u[q][1]) : "r"(sa + 1280 + 32 * q) : "memory");
                }
                float mx = -3.0e38f;
                #pragma unroll
                for (int q = 0; q < 5; q++) {
                    v[q][0] += u[q][0]; v[q][1] += u[q][1];
                    mx = fmaxf(mx, fmaxf(v[q][0], v[q][1]));
                }
                mx = fmaxf(mx, __shfl_xor_sync(~0u, mx, 1));
                mx = fmaxf(mx, __shfl_xor_sync(~0u, mx, 2));
                const float sc2 = 0.08838834764831845f * 1.4426950408889634f;
                const float mxs = mx * sc2;
                uint32_t* pbs = reinterpret_cast<uint32_t*>(smem + SM_PB);
                #pragma unroll
                for (int q = 0; q < 5; q++) {
                    const float e0 = ex2_approx(fmaf(v[q][0], sc2, -mxs)), e1 = ex2_approx(fmaf(v[q][1], sc2, -mxs));
                    pbs[q * 32 + lane] = pack_bf16(e0, e1);
                }
                __syncwarp();
                TR(0);
                nbar_arrive(9, 288);
            } else if (warp == 1 && lane == 0) {
                if (s + 1 < NSEG - 1) {
                    mbar_expect_tx(sb + B_SC + 8 * ((s + 1) & 1), rank < 2 ? 1280 : 2560);
                    if (rank < 2) mbar_expect_tx(sb + B_V + 8 * ((s + 1) & 1), 8192 + 2048);
                }
                if (s + 2 < NSEG) {
                    mbar_expect_tx(sb + B_X + 8 * (s & 1), 40960);
                    tma_load_3d(sb + SM_XB + (s & 1) * 40960, &xmap, 0, (s + 2) * 32, 0, sb + B_X + 8 * (s & 1));
                }
                export_issue(sb, s, h, rank);
                if (s >= NSEG - 4) export_signal(s, h);
            }
            __syncwarp();
            nbar_sync(3, 384);
            const uint32_t tg = tag_of(s);
            if (cta < NRED) {
                const unsigned char* base = pool + reinterpret_cast<const uint32_t*>(smem + SM_TRD)[(s & 1) * 2 + (warp >> 1)] + (warp & 1) * 2048 + lane * 16;
                uint4 v[4]; int guard = 0;
                #pragma unroll
                for (int j = 0; j < 4; j++) v[j] = make_uint4(0, 0, 0, 0);
                uint32_t pend = 0xF;
                do {
                    #pragma unroll
                    for (int j = 0; j < 4; j++) if (pend & (1u << j)) v[j] = ld_relaxed4(base + j * 512);
                    #pragma unroll
                    for (int j = 0; j < 4; j++)
                        if (((v[j].x & 3) == tg) && ((v[j].y & 3) == tg) && ((v[j].z & 3) == tg) && ((v[j].w & 3) == tg)) pend &= ~(1u << j);
                } while (__any_sync(~0u, pend != 0) && ++guard < (1 << 20));
                if (warp == 0) TR(9);
                float a0 = 0, a1 = 0, a2 = 0, a3 = 0;
                #pragma unroll
                for (int j = 0; j < 4; j++) { a0 += __uint_as_float(v[j].x); a1 += __uint_as_float(v[j].y); a2 += __uint_as_float(v[j].z); a3 += __uint_as_float(v[j].w); }
                a0 += __shfl_xor_sync(~0u, a0, 16); a1 += __shfl_xor_sync(~0u, a1, 16); a2 += __shfl_xor_sync(~0u, a2, 16); a3 += __shfl_xor_sync(~0u, a3, 16);
                float* cr = reinterpret_cast<float*>(smem + SM_CRED);
                if (lane < 16) *reinterpret_cast<float4*>(cr + warp * 64 + lane * 4) = make_float4(a0, a1, a2, a3);
                nbar_sync(4, 128);
                {
                    int rho = lane >> 2, pp = lane & 3;
                    int i0 = ((2 * pp) * 4 + (rho >> 1)) * 2 + (rho & 1), i1 = i0 + 8;
                    uint32_t wv = pack_bf16((cr[i0] + cr[64 + i0]) + (cr[128 + i0] + cr[192 + i0]), (cr[i1] + cr[64 + i1]) + (cr[128 + i1] + cr[192 + i1]));
                    if (wv == 0) wv = 0x8000u;
                    if (warp == 0) TR(10);
                    const uint32_t* tp = reinterpret_cast<const uint32_t*>(smem + SM_TPUB) + warp;
                    if (warp < 2 * RPS) st_relaxed1(pool + tp[((s + 1) & 3) * 8] + lane * 4, wv);
                    if (RPS == 4) st_relaxed1(pool + tp[((s + 1) & 3) * 8 + 4] + lane * 4, wv);
                    if (warp < 2 * RPS) st_relaxed1(pool + tp[(s & 3) * 8] + lane * 4, 0u);
                    if (RPS == 4) st_relaxed1(pool + tp[(s & 3) * 8 + 4] + lane * 4, 0u);
                }
            }
            {
                const int c0 = warp * 160 + lane;
                const uint32_t* tg3 = reinterpret_cast<const uint32_t*>(smem + SM_TGAT) + ((s + 1) & 3) * 4;
                const uint32_t g0 = tg3[0], g1 = tg3[1], g2 = tg3[2];
                uint4 v[5]; int guard = 0;
                #pragma unroll
                for (int j = 0; j < 5; j++) v[j] = make_uint4(0, 0, 0, 0);
                uint32_t pend = 0x1F;
                do {
                    #pragma unroll
                    for (int j = 0; j < 5; j++) {
                        const int c = c0 + 32 * j;
                        if (pend & (1u << j)) v[j] = ld_relaxed4(pool + ((c >> 8) == 0 ? g0 : ((c >> 8) == 1 ? g1 : g2)) + (c & 255) * 16);
                    }
                    #pragma unroll
                    for (int j = 0; j < 5; j++) if (v[j].x && v[j].y && v[j].z && v[j].w) pend &= ~(1u << j);
                } while (__any_sync(~0u, pend != 0) && ++guard < (1 << 20));
                #pragma unroll
                for (int j = 0; j < 5; j++) *reinterpret_cast<uint4*>(smem + SM_MEMB + (c0 + 32 * j) * 16) = v[j];
                if (warp == 0) TR(11);
                if (warp == 3) TR(12);
                nbar_arrive(warp < 2 ? 7 + warp : 8 + warp, 160);
            }
            if (warp == 1 && lane == 0 && s < NSEG - 4) export_signal(s, h);
            __syncwarp();
        }
        if (warp == 1) { nbar_sync(12, 288); if (lane == 0) { export_issue(sb, NSEG - 1, h, rank); export_signal(NSEG - 1, h); } }
        __syncwarp();
        nbar_sync(3, 384);
        __syncwarp();
        cluster_sync_all();
    } else {
        asm volatile("setmaxnreg.inc.sync.aligned.u32 232;");
        const int wtid = tid & 127;
        const int cw = wg * 4 + warp;
        uint32_t areg[2][20][4];
        #pragma unroll
        for (int mt = 0; mt < 2; mt++)
            #pragma unroll
            for (int kk = 0; kk < 20; kk++) {
                int mi = lane >> 3;
                int row = 16 * (20 * wg + kk) + (mi >> 1) * 8 + (lane & 7);
                int chunk = 2 * warp + (mi & 1);
                ldsm4t(areg[mt][kk], sb + mt * 81920 + row * 128 + ((chunk ^ (row & 7)) << 4));
            }
        nbar_sync(5, 384);
        nbar_sync(5, 384);
        cluster_sync_all();

        for (int s = -1; s < NSEG; s++) {
            const int sl = s & 1;
            if (s >= 0) {
            if (s > 0) nbar_sync(7 + 3 * wg, 160);
            float fin[4];
            {
                float acc[2][2][4];
                #pragma unroll
                for (int i = 0; i < 2; i++)
                    #pragma unroll
                    for (int j = 0; j < 2; j++) { acc[i][j][0] = acc[i][j][1] = acc[i][j][2] = acc[i][j][3] = 0.f; }
                uint32_t b[3][4];
                const uint32_t mb = sb + SM_MEMB + (20 * wg) * 256 + lane * 16;
                ldsm4(b[0], mb); ldsm4(b[1], mb + 512);
                #pragma unroll
                for (int kp = 0; kp < 10; kp++) {
                    if (kp == 3 && s > 0) nbar_sync(8 + 3 * wg, 160);
                    if (kp + 2 < 10) ldsm4(b[(kp + 2) % 3], mb + (kp + 2) * 512);
                    const uint32_t (&bb)[4] = b[kp % 3];
                    mma_bf16(acc[0][0], areg[0][2 * kp][0], areg[0][2 * kp][1], areg[0][2 * kp][2], areg[0][2 * kp][3], bb[0], bb[1]);
                    mma_bf16(acc[1][0], areg[1][2 * kp][0], areg[1][2 * kp][1], areg[1][2 * kp][2], areg[1][2 * kp][3], bb[0], bb[1]);
                    mma_bf16(acc[0][1], areg[0][2 * kp + 1][0], areg[0][2 * kp + 1][1], areg[0][2 * kp + 1][2], areg[0][2 * kp + 1][3], bb[2], bb[3]);
                    mma_bf16(acc[1][1], areg[1][2 * kp + 1][0], areg[1][2 * kp + 1][1], areg[1][2 * kp + 1][2], areg[1][2 * kp + 1][3], bb[2], bb[3]);
                }
                float4* red = reinterpret_cast<float4*>(smem + SM_RED);
                float m0[4], m1[4];
                #pragma unroll
                for (int i = 0; i < 4; i++) { m0[i] = acc[0][0][i] + acc[0][1][i]; m1[i] = acc[1][0][i] + acc[1][1][i]; }
                red[(wg ^ 1) * 128 + wtid] = wg == 0 ? make_float4(m1[0], m1[1], m1[2], m1[3]) : make_float4(m0[0], m0[1], m0[2], m0[3]);
                nbar_sync(1, 256);
                float4 r = red[wg * 128 + wtid];
                fin[0] = (wg == 0 ? m0[0] : m1[0]) + r.x; fin[1] = (wg == 0 ? m0[1] : m1[1]) + r.y;
                fin[2] = (wg == 0 ? m0[2] : m1[2]) + r.z; fin[3] = (wg == 0 ? m0[3] : m1[3]) + r.w;
            }
            if (cw == 0) TR(1);
            {
                uint32_t p0 = pack_bf16(fin[0], fin[1]), p1 = pack_bf16(fin[2], fin[3]);
                const uint32_t doff = (rank == 2) ? SM_VT + sl * 10240 + wg * 5120 : (wg == 0 ? SM_QS : SM_KT + sl * 5120);
                const int r = lane & 7, chunk = 2 * warp + ((lane >> 3) & 1);
                const uint32_t coff = doff + r * 128 + ((chunk ^ r) << 4);
                stsm2t(sb + coff, p0, p1);
                if (rank == 2 && s < NSEG - 1) {
                    __syncwarp();
                    const uint4 v = *reinterpret_cast<const uint4*>(smem + coff);
                    const uint32_t rb = mapa(sb, lane >> 4);
                    st_async4u(rb + coff, v, rb + B_V + 8 * sl);
                }
            }
            fence_async();
            nbar_sync(1, 256);
            nbar_arrive(12, 288);
            if (cw == 0) TR(2);
            if (rank < 2 && s < NSEG - 1) {
                if (wg == 1) score_tile(sb, sl, 1 + warp, lane, rank);
                else if (warp == 0) score_tile(sb, sl, 0, lane, rank);
            }
            if (s == NSEG - 1) break;
            if (cw == 0) TR(3);
            if (wg == 0 || rank == 2) u_pass<2>(smem, sb, s, rank, wg, warp, lane);
            else                      u_pass<1>(smem, sb, s, rank, wg, warp, lane);
            if (cw == 0) TR(7);
            nbar_arrive(3, 384);
            }
            {
                const int sn = s + 1, sln = sn & 1;
                mbar_wait(sb + B_X + 8 * sln, (sn >> 1) & 1);
                float acc[2][16];
                wg_fence();
                #pragma unroll
                for (int mt = 0; mt < 2; mt++)
                    #pragma unroll
                    for (int kk = 0; kk < 20; kk++) {
                        uint64_t db = make_desc(sb + SM_XB + sln * 40960 + (5 * wg + (kk >> 2)) * 4096 + (kk & 3) * 32, 16, 1024);
                        wgmma_n32_rs(acc[mt], areg[mt][kk], db, kk > 0);
                    }
                wg_commit();
                if (cw == 0 && s >= 0) TR(14);
                wg_wait0();
                if (cw == 0 && s >= 0) TR(15);
                float4* red = reinterpret_cast<float4*>(smem + SM_RED);
                #pragma unroll
                for (int j = 0; j < 4; j++) {
                    red[((wg ^ 1) * 4 + j) * 128 + wtid] = make_float4(wg == 0 ? acc[1][4 * j] : acc[0][4 * j], wg == 0 ? acc[1][4 * j + 1] : acc[0][4 * j + 1],
                                                                       wg == 0 ? acc[1][4 * j + 2] : acc[0][4 * j + 2], wg == 0 ? acc[1][4 * j + 3] : acc[0][4 * j + 3]);
                }
                if (s >= 0) mbar_wait(sb + B_EXP, s & 1);
                nbar_sync(1, 256);
                uint32_t pk[8];
                #pragma unroll
                for (int j = 0; j < 4; j++) {
                    float4 r = red[(wg * 4 + j) * 128 + wtid];
                    pk[2 * j] = pack_bf16((wg == 0 ? acc[0][4 * j] : acc[1][4 * j]) + r.x, (wg == 0 ? acc[0][4 * j + 1] : acc[1][4 * j + 1]) + r.y);
                    pk[2 * j + 1] = pack_bf16((wg == 0 ? acc[0][4 * j + 2] : acc[1][4 * j + 2]) + r.z, (wg == 0 ? acc[0][4 * j + 3] : acc[1][4 * j + 3]) + r.w);
                }
                const uint32_t dst = (rank == 2) ? sb + SM_VT + sln * 10240 + wg * 5120 + 1024 : (wg == 0 ? sb + SM_QT : sb + SM_KT + sln * 5120 + 1024);
                #pragma unroll
                for (int jj = 0; jj < 2; jj++) {
                    int mi = lane >> 3, tok = 8 * (2 * jj + (mi >> 1)) + (lane & 7), chunk = 2 * warp + (mi & 1);
                    stsm4t(dst + tok * 128 + ((chunk ^ (tok & 7)) << 4), pk[4 * jj], pk[4 * jj + 1], pk[4 * jj + 2], pk[4 * jj + 3]);
                }
                fence_async();
                nbar_sync(1, 256);
                if (rank == 2 && lane == 0 && cw < 4 && sn < NSEG - 1) {
                    const uint32_t off = SM_VT + sln * 10240 + (cw & 1) * 5120 + 1024;
                    const uint32_t rb = mapa(sb, cw >> 1);
                    bulk_s2c(rb + off, sb + off, 4096, rb + B_V + 8 * sln);
                }
                if (cw == 0 && s >= 0) TR(13);
            }
        }
        nbar_arrive(3, 384);
        __syncwarp();
        cluster_sync_all();
    }
}

#define NAUX 36
__device__ __align__(1024) bf16 g_Oimg[16 * 64 * 128 * 64];
__device__ float    g_part[4 * SEQ * DM];
__device__ float    g_part31[3 * 13 * 64 * DM];
__device__ unsigned g_ocnt[32];
__device__ unsigned g_gcnt[32][2];
__device__ unsigned g_ssmcnt, g_auxdone, g_taskctr, g_gemmctr;
#define NATT 8
#define ATR(i) do {} while (0)
#define ATRID(i, id) do {} while (0)

__device__ __forceinline__ void wait_counter(const unsigned* p, unsigned target) {
    int guard = 0;
    while ((int)(ld_acquire(p) - target) < 0 && ++guard < (1 << 22)) __nanosleep(64);
}
__device__ __forceinline__ void fence_async_all() { asm volatile("fence.proxy.async;" ::: "memory"); }
template <int OFF>
__device__ __forceinline__ void wgmma_n192_tB(float (&d)[160], uint64_t da, uint64_t db) {
    asm volatile("wgmma.mma_async.sync.aligned.m64n192k16.f32.bf16.bf16 {%0,%1,%2,%3,%4,%5,%6,%7,%8,%9,%10,%11,%12,%13,%14,%15,%16,%17,%18,%19,%20,%21,%22,%23,%24,%25,%26,%27,%28,%29,%30,%31,%32,%33,%34,%35,%36,%37,%38,%39,%40,%41,%42,%43,%44,%45,%46,%47,%48,%49,%50,%51,%52,%53,%54,%55,%56,%57,%58,%59,%60,%61,%62,%63,%64,%65,%66,%67,%68,%69,%70,%71,%72,%73,%74,%75,%76,%77,%78,%79,%80,%81,%82,%83,%84,%85,%86,%87,%88,%89,%90,%91,%92,%93,%94,%95}, %96, %97, 1, 1, 1, 0, 1;\n"
        : "+f"(d[OFF + 0]), "+f"(d[OFF + 1]), "+f"(d[OFF + 2]), "+f"(d[OFF + 3]), "+f"(d[OFF + 4]), "+f"(d[OFF + 5]), "+f"(d[OFF + 6]), "+f"(d[OFF + 7]), "+f"(d[OFF + 8]), "+f"(d[OFF + 9]), "+f"(d[OFF + 10]), "+f"(d[OFF + 11]), "+f"(d[OFF + 12]), "+f"(d[OFF + 13]), "+f"(d[OFF + 14]), "+f"(d[OFF + 15]), "+f"(d[OFF + 16]), "+f"(d[OFF + 17]), "+f"(d[OFF + 18]), "+f"(d[OFF + 19]), "+f"(d[OFF + 20]), "+f"(d[OFF + 21]), "+f"(d[OFF + 22]), "+f"(d[OFF + 23]), "+f"(d[OFF + 24]), "+f"(d[OFF + 25]), "+f"(d[OFF + 26]), "+f"(d[OFF + 27]), "+f"(d[OFF + 28]), "+f"(d[OFF + 29]), "+f"(d[OFF + 30]), "+f"(d[OFF + 31]), "+f"(d[OFF + 32]), "+f"(d[OFF + 33]), "+f"(d[OFF + 34]), "+f"(d[OFF + 35]), "+f"(d[OFF + 36]), "+f"(d[OFF + 37]), "+f"(d[OFF + 38]), "+f"(d[OFF + 39]), "+f"(d[OFF + 40]), "+f"(d[OFF + 41]), "+f"(d[OFF + 42]), "+f"(d[OFF + 43]), "+f"(d[OFF + 44]), "+f"(d[OFF + 45]), "+f"(d[OFF + 46]), "+f"(d[OFF + 47]), "+f"(d[OFF + 48]), "+f"(d[OFF + 49]), "+f"(d[OFF + 50]), "+f"(d[OFF + 51]), "+f"(d[OFF + 52]), "+f"(d[OFF + 53]), "+f"(d[OFF + 54]), "+f"(d[OFF + 55]), "+f"(d[OFF + 56]), "+f"(d[OFF + 57]), "+f"(d[OFF + 58]), "+f"(d[OFF + 59]), "+f"(d[OFF + 60]), "+f"(d[OFF + 61]), "+f"(d[OFF + 62]), "+f"(d[OFF + 63]), "+f"(d[OFF + 64]), "+f"(d[OFF + 65]), "+f"(d[OFF + 66]), "+f"(d[OFF + 67]), "+f"(d[OFF + 68]), "+f"(d[OFF + 69]), "+f"(d[OFF + 70]), "+f"(d[OFF + 71]), "+f"(d[OFF + 72]), "+f"(d[OFF + 73]), "+f"(d[OFF + 74]), "+f"(d[OFF + 75]), "+f"(d[OFF + 76]), "+f"(d[OFF + 77]), "+f"(d[OFF + 78]), "+f"(d[OFF + 79]), "+f"(d[OFF + 80]), "+f"(d[OFF + 81]), "+f"(d[OFF + 82]), "+f"(d[OFF + 83]), "+f"(d[OFF + 84]), "+f"(d[OFF + 85]), "+f"(d[OFF + 86]), "+f"(d[OFF + 87]), "+f"(d[OFF + 88]), "+f"(d[OFF + 89]), "+f"(d[OFF + 90]), "+f"(d[OFF + 91]), "+f"(d[OFF + 92]), "+f"(d[OFF + 93]), "+f"(d[OFF + 94]), "+f"(d[OFF + 95])
        : "l"(da), "l"(db));
}
template <int OFF>
__device__ __forceinline__ void wgmma_n128_tB(float (&d)[160], uint64_t da, uint64_t db) {
    asm volatile("wgmma.mma_async.sync.aligned.m64n128k16.f32.bf16.bf16 {%0,%1,%2,%3,%4,%5,%6,%7,%8,%9,%10,%11,%12,%13,%14,%15,%16,%17,%18,%19,%20,%21,%22,%23,%24,%25,%26,%27,%28,%29,%30,%31,%32,%33,%34,%35,%36,%37,%38,%39,%40,%41,%42,%43,%44,%45,%46,%47,%48,%49,%50,%51,%52,%53,%54,%55,%56,%57,%58,%59,%60,%61,%62,%63}, %64, %65, 1, 1, 1, 0, 1;\n"
        : "+f"(d[OFF + 0]), "+f"(d[OFF + 1]), "+f"(d[OFF + 2]), "+f"(d[OFF + 3]), "+f"(d[OFF + 4]), "+f"(d[OFF + 5]), "+f"(d[OFF + 6]), "+f"(d[OFF + 7]), "+f"(d[OFF + 8]), "+f"(d[OFF + 9]), "+f"(d[OFF + 10]), "+f"(d[OFF + 11]), "+f"(d[OFF + 12]), "+f"(d[OFF + 13]), "+f"(d[OFF + 14]), "+f"(d[OFF + 15]), "+f"(d[OFF + 16]), "+f"(d[OFF + 17]), "+f"(d[OFF + 18]), "+f"(d[OFF + 19]), "+f"(d[OFF + 20]), "+f"(d[OFF + 21]), "+f"(d[OFF + 22]), "+f"(d[OFF + 23]), "+f"(d[OFF + 24]), "+f"(d[OFF + 25]), "+f"(d[OFF + 26]), "+f"(d[OFF + 27]), "+f"(d[OFF + 28]), "+f"(d[OFF + 29]), "+f"(d[OFF + 30]), "+f"(d[OFF + 31]), "+f"(d[OFF + 32]), "+f"(d[OFF + 33]), "+f"(d[OFF + 34]), "+f"(d[OFF + 35]), "+f"(d[OFF + 36]), "+f"(d[OFF + 37]), "+f"(d[OFF + 38]), "+f"(d[OFF + 39]), "+f"(d[OFF + 40]), "+f"(d[OFF + 41]), "+f"(d[OFF + 42]), "+f"(d[OFF + 43]), "+f"(d[OFF + 44]), "+f"(d[OFF + 45]), "+f"(d[OFF + 46]), "+f"(d[OFF + 47]), "+f"(d[OFF + 48]), "+f"(d[OFF + 49]), "+f"(d[OFF + 50]), "+f"(d[OFF + 51]), "+f"(d[OFF + 52]), "+f"(d[OFF + 53]), "+f"(d[OFF + 54]), "+f"(d[OFF + 55]), "+f"(d[OFF + 56]), "+f"(d[OFF + 57]), "+f"(d[OFF + 58]), "+f"(d[OFF + 59]), "+f"(d[OFF + 60]), "+f"(d[OFF + 61]), "+f"(d[OFF + 62]), "+f"(d[OFF + 63])
        : "l"(da), "l"(db));
}
__device__ __forceinline__ void stsm4(uint32_t addr, uint32_t r0, uint32_t r1, uint32_t r2, uint32_t r3) {
    asm volatile("stmatrix.sync.aligned.m8n8.x4.shared.b16 [%0], {%1,%2,%3,%4};" :: "r"(addr), "r"(r0), "r"(r1), "r"(r2), "r"(r3) : "memory");
}

#define AX_BAR   0
#define NST_G 4
#define AX_EMPTY (AX_BAR + 16 + 8 * NST_G)
#define AX_DATA  1024
#define AX_UNIT  28672
#define AX_STAGE 57344
#define AX_TOTAL (AX_DATA + 8 * AX_UNIT)

__device__ __forceinline__ void attn_compute(unsigned char* smem, uint32_t sb, uint32_t buf, int warp, int lane);
__device__ __forceinline__ void attn_producer(unsigned char* smem, int hg, unsigned epoch) {
    const uint32_t sb = smem_u32(smem);
    const int lane = threadIdx.x & 31;
    {
        for (int s = 0; s < NSEG; s++) {
            const uint32_t buf = AX_DATA + (s & 1) * (4 * AX_UNIT), bar = sb + AX_BAR + 8 * (s & 1);
            if (lane < 4) wait_counter(&g_flag[s][4 * hg + lane], (epoch + 1) * 3u);
            if (lane == 4) mbar_wait_sleep(sb + AX_EMPTY + 8 * (s & 1), ((s >> 1) & 1) ^ 1);
            __syncwarp();
            if (lane == 0) mbar_expect_tx(bar, 4 * AX_UNIT);
            __syncwarp();
            if (lane < 24) {
                fence_async_all();
                const int u = lane / 6, r = lane % 6, hf = r & 1, kind = r >> 1;
                const uint32_t ub = sb + buf + u * AX_UNIT;
                const size_t img = ((size_t)(s * NH + 4 * hg + u) * 2) + hf;
                if (kind == 0) bulk_g2s(ub + hf * 4096, g_Qimg + img * 2048, 4096, bar);
                else if (kind == 1) bulk_g2s(ub + 8192 + hf * 5120, g_Kimg + img * 2560, 5120, bar);
                else bulk_g2s(ub + 18432 + hf * 5120, g_Vimg + img * 2560, 5120, bar);
            }
            __syncwarp();
        }
    }
}
__device__ __forceinline__ void attn_loop(unsigned char* smem, int hg, unsigned epoch) {
    const uint32_t sb = smem_u32(smem);
    const int tid = threadIdx.x, warp = tid >> 5, lane = tid & 31;
    for (int s = 0; s < NSEG; s++) {
        const uint32_t buf = AX_DATA + (s & 1) * (4 * AX_UNIT), bar = sb + AX_BAR + 8 * (s & 1);
        mbar_wait_sleep(bar, (s >> 1) & 1);
        if (s >= 36) ATR(2 + 2 * (s - 36));
        attn_compute(smem, sb, buf, warp, lane);
        if (s >= 36) ATR(3 + 2 * (s - 36));
        fence_async();
        __syncwarp();
        if (lane == 0) mbar_arrive(sb + AX_EMPTY + 16 + 8 * (s & 1));
    }
}
__device__ __forceinline__ void attn_storer(unsigned char* smem, int hg) {
    const uint32_t sb = smem_u32(smem);
    const int lane = threadIdx.x & 31;
    for (int s = 0; s < NSEG; s++) {
        const uint32_t buf = AX_DATA + (s & 1) * (4 * AX_UNIT);
        mbar_wait_sleep(sb + AX_EMPTY + 16 + 8 * (s & 1), (s >> 1) & 1);
        if (lane < 8) {
            const int uu = lane >> 1, hf = lane & 1, hh = 4 * hg + uu;
            bulk_s2g(g_Oimg + (((size_t)(s >> 2) * 64 + hh * 2 + hf) * 128 + (s & 3) * 32) * 64, sb + buf + uu * AX_UNIT + hf * 4096, 4096);
            bulk_commit();
            bulk_wait_read0();
            mbar_arrive(sb + AX_EMPTY + 8 * (s & 1));
            bulk_wait0();
            fence_async_all();
            __threadfence();
            atomicAdd(&g_ocnt[s >> 1], 1u);
        }
        __syncwarp();
    }
}
__device__ __forceinline__ void attn_compute(unsigned char* smem, uint32_t sb, uint32_t buf, int warp, int lane) {
    const int g = lane >> 2, t = lane & 3;
    const int u = warp >> 1, qh = warp & 1;
    const uint32_t ub = sb + buf + u * AX_UNIT;
    float sc[5][4];
    #pragma unroll
    for (int j = 0; j < 5; j++) { sc[j][0] = sc[j][1] = sc[j][2] = sc[j][3] = 0.f; }
    #pragma unroll
    for (int ks = 0; ks < 8; ks++) {
        const int hf = ks >> 2, c0 = (ks & 3) * 2;
        uint32_t a[4];
        { int mi = lane >> 3, row = 16 * qh + (mi & 1) * 8 + (lane & 7), chunk = c0 + (mi >> 1);
          ldsm4(a, ub + hf * 4096 + row * 128 + ((chunk ^ (row & 7)) << 4)); }
        #pragma unroll
        for (int jp = 0; jp < 3; jp++) {
            uint32_t b[4];
            int mi = lane >> 3, nt = 2 * jp + (mi >> 1); if (nt > 4) nt = 4;
            int row = 8 * nt + (lane & 7), chunk = c0 + (mi & 1);
            ldsm4(b, ub + 8192 + hf * 5120 + row * 128 + ((chunk ^ (row & 7)) << 4));
            mma_bf16(sc[2 * jp], a[0], a[1], a[2], a[3], b[0], b[1]);
            if (jp < 2) mma_bf16(sc[2 * jp + 1], a[0], a[1], a[2], a[3], b[2], b[3]);
        }
    }
    uint32_t pa[3][4];
    {
        const float sc2 = 0.08838834764831845f * 1.4426950408889634f;
        float mx0 = -3.0e38f, mx1 = -3.0e38f;
        const int q0 = 16 * qh + g, q1 = q0 + 8;
        #pragma unroll
        for (int j = 0; j < 5; j++)
            #pragma unroll
            for (int e = 0; e < 2; e++) {
                int key = 8 * j + 2 * t + e - 8;
                sc[j][e] = (key <= q0) ? sc[j][e] * sc2 : -3.0e38f;
                sc[j][2 + e] = (key <= q1) ? sc[j][2 + e] * sc2 : -3.0e38f;
                mx0 = fmaxf(mx0, sc[j][e]); mx1 = fmaxf(mx1, sc[j][2 + e]);
            }
        mx0 = fmaxf(mx0, __shfl_xor_sync(~0u, mx0, 1)); mx0 = fmaxf(mx0, __shfl_xor_sync(~0u, mx0, 2));
        mx1 = fmaxf(mx1, __shfl_xor_sync(~0u, mx1, 1)); mx1 = fmaxf(mx1, __shfl_xor_sync(~0u, mx1, 2));
        float s0 = 0.f, s1 = 0.f;
        #pragma unroll
        for (int j = 0; j < 5; j++)
            #pragma unroll
            for (int e = 0; e < 2; e++) {
                sc[j][e] = ex2_approx(sc[j][e] - mx0); sc[j][2 + e] = ex2_approx(sc[j][2 + e] - mx1);
                s0 += sc[j][e]; s1 += sc[j][2 + e];
            }
        s0 += __shfl_xor_sync(~0u, s0, 1); s0 += __shfl_xor_sync(~0u, s0, 2);
        s1 += __shfl_xor_sync(~0u, s1, 1); s1 += __shfl_xor_sync(~0u, s1, 2);
        const float i0 = __frcp_rn(s0), i1 = __frcp_rn(s1);
        #pragma unroll
        for (int k = 0; k < 3; k++) {
            pa[k][0] = pack_bf16(sc[2 * k][0] * i0, sc[2 * k][1] * i0);
            pa[k][1] = pack_bf16(sc[2 * k][2] * i1, sc[2 * k][3] * i1);
            if (k < 2) { pa[k][2] = pack_bf16(sc[2 * k + 1][0] * i0, sc[2 * k + 1][1] * i0); pa[k][3] = pack_bf16(sc[2 * k + 1][2] * i1, sc[2 * k + 1][3] * i1); }
            else { pa[k][2] = 0u; pa[k][3] = 0u; }
        }
    }
    __syncwarp();
    nbar_sync(5 + u, 64);
    #pragma unroll
    for (int np = 0; np < 8; np++) {
        const int hf = np >> 2, c0 = (np & 3) * 2;
        float o0[4] = {0, 0, 0, 0}, o1[4] = {0, 0, 0, 0};
        #pragma unroll
        for (int k = 0; k < 3; k++) {
            uint32_t b[4];
            int mi = lane >> 3;
            int row = 16 * k + (mi & 1) * 8 + (lane & 7); if (row > 39) row = 39 - 7 + (lane & 7);
            int chunk = c0 + (mi >> 1);
            ldsm4t(b, ub + 18432 + hf * 5120 + row * 128 + ((chunk ^ (row & 7)) << 4));
            mma_bf16(o0, pa[k][0], pa[k][1], pa[k][2], pa[k][3], b[0], k < 2 ? b[1] : 0u);
            mma_bf16(o1, pa[k][0], pa[k][1], pa[k][2], pa[k][3], b[2], k < 2 ? b[3] : 0u);
        }
        int mi = lane >> 3, row = 16 * qh + (mi & 1) * 8 + (lane & 7), chunk = c0 + (mi >> 1);
        stsm4(ub + hf * 4096 + row * 128 + ((chunk ^ (row & 7)) << 4), pack_bf16(o0[0], o0[1]), pack_bf16(o0[2], o0[3]), pack_bf16(o1[0], o1[1]), pack_bf16(o1[2], o1[3]));
    }
}

template <int V> struct IntC { static constexpr int value = V; };
struct Task { int type, rb, c, k0, nch, plane; };
#define NFINE 29
#define NGEMM (8 + 144 + 8 * 2 + 4 + 8 * 4 + 26 * 3 + 16 * 3)
__device__ __forceinline__ Task decode_task(int j) {
    Task t; t.type = 0; t.rb = 0; t.c = 0; t.k0 = 0; t.nch = 16; t.plane = 0;
    auto H = [&](int rb, int i) { t.type = 1; t.rb = rb; t.c = i & 1; t.plane = i >> 1; t.k0 = t.plane * 16; };
    auto CF = [&](int rb, int i) { t.type = 2; t.rb = rb; t.c = i & 1; t.k0 = rb * 64 + (i >> 1) * 16; t.nch = 16; };
    auto H13 = [&](int rb, int i) { t.type = 1; t.rb = rb; t.c = i & 1; t.plane = i >> 1; t.k0 = t.plane * 5; t.nch = (t.plane == 12) ? 4 : 5; };
    auto C13 = [&](int rb, int i) { t.type = 2; t.rb = rb; t.c = i & 1; t.k0 = rb * 64 + (i >> 1) * 8; t.nch = 8; };
    if (j >= NGEMM) { t.type = 3; return t; }
    if (j < 8) { t.c = j & 1; t.plane = j >> 1; t.k0 = t.plane * 16; return t; }
    j -= 8;
    if (j < 144) {
        const int q = j / 12, r = j % 12;
        if (r < 8) { t.rb = 2 * (q + 1); t.c = r & 1; t.plane = r >> 1; t.k0 = t.plane * 16; }
        else { t.type = 2; t.rb = 2 * q + ((r - 8) >> 1); t.c = r & 1; t.k0 = t.rb * 64; t.nch = 64; }
        return t;
    }
    j -= 144;
    if (j < 8) { H(26, j); return t; }
    j -= 8;
    if (j < 8) { H(27, j); return t; }
    j -= 8;
    if (j < 4) { t.type = 2; t.rb = 24 + (j >> 1); t.c = j & 1; t.k0 = t.rb * 64; t.nch = 64; return t; }
    j -= 4;
    if (j < 8) { H(28, j); return t; }
    j -= 8;
    if (j < 8) { CF(26, j); return t; }
    j -= 8;
    if (j < 8) { CF(27, j); return t; }
    j -= 8;
    if (j < 26) { H13(29, j); return t; }
    j -= 26;
    if (j < 8) { CF(28, j); return t; }
    j -= 8;
    if (j < 26) { H13(30, j); return t; }
    j -= 26;
    if (j < 16) { C13(29, j); return t; }
    j -= 16;
    if (j < 26) { H13(31, j); return t; }
    j -= 26;
    if (j < 16) { C13(30, j); return t; }
    j -= 16;
    C13(31, j);
    return t;
}
__device__ __forceinline__ void gemm_producer(unsigned char* smem, const CUtensorMap* womap, unsigned epoch, volatile int* s_tasks) {
    const uint32_t sb = smem_u32(smem);
    uint32_t st = 0, ph = 1;
    for (int n = 0;; n++) {
        const int j = (int)(atomicAdd(&g_gemmctr, 1u) - epoch * (unsigned)(NGEMM + NAUX));
        const Task t = decode_task(j);
        if (t.type <= 1) {
            wait_counter(&g_ocnt[t.rb], (epoch + 1) * 128u);
            if (t.type == 0) wait_counter(&g_ocnt[t.rb + 1], (epoch + 1) * 128u);
            fence_async_all();
        } else if (t.type == 2) {
            wait_counter(&g_gcnt[t.rb][t.c], (epoch + 1) * (t.rb >= NFINE ? 13u : 4u));
            wait_counter(&g_ssmcnt, (epoch + 1) * 80u);
        }
        const int nch = (t.type <= 1) ? t.nch : 1;
        for (int kc = 0; kc < nch; kc++) {
            mbar_wait_sleep(sb + AX_EMPTY + 8 * st, ph);
            const uint32_t a = sb + AX_DATA + st * AX_STAGE, bar = sb + AX_BAR + 16 + 8 * st;
            if (kc == 0) s_tasks[n & 7] = j;
            if (t.type > 1) mbar_arrive(bar);
            else {
                const bf16* asrc = g_Oimg + ((size_t)(t.rb >> 1) * 64 + t.k0 + kc) * 8192 + (t.rb & 1) * 4096;
                if (t.type == 0) { mbar_expect_tx(bar, AX_STAGE); bulk_g2s(a, asrc, 8192, bar); bulk_g2s(a + 8192, asrc + 4096, 8192, bar); }
                else { mbar_expect_tx(bar, AX_STAGE - 8192); bulk_g2s(a, asrc, 8192, bar); }
                #pragma unroll
                for (int b = 0; b < 5; b++) tma_load_2d(a + 16384 + b * 8192, womap, t.c * 320 + b * 64, (t.k0 + kc) * 64, bar);
            }
            if (++st == NST_G) { st = 0; ph ^= 1; }
        }
        if (t.type == 3) break;
    }
}
__device__ __forceinline__ void gemm_signaller(volatile int* s_done) {
    for (int n = 0;; n++) {
        nbar_sync(2, 288);
        const int j = s_done[n & 7];
        if (j < 0) break;
        if ((threadIdx.x & 31) == 0) {
            const Task t = decode_task(j);
            __threadfence();
            atomicAdd(&g_gcnt[t.rb][t.c], 1u);
            if (t.type == 0) atomicAdd(&g_gcnt[t.rb + 1][t.c], 1u);
        }
        __syncwarp();
    }
}
__device__ __forceinline__ void gemm_consumer(unsigned char* smem, bf16* __restrict__ out, volatile int* s_tasks, volatile int* s_done) {
    const uint32_t sb = smem_u32(smem);
    const int tid = threadIdx.x, lane = tid & 31;
    const int wg = __shfl_sync(~0u, tid >> 7, 0), warp = __shfl_sync(~0u, (tid >> 5) & 3, 0);
    uint32_t st = 0, ph = 0;
    int ndone = 0;
    for (int n = 0;; n++) {
        mbar_wait_sleep(sb + AX_BAR + 16 + 8 * st, ph);
        const Task t = decode_task(__shfl_sync(~0u, s_tasks[n & 7], 0));
        if (t.type > 1) {
            nbar_sync(1, 256);
            if ((tid & 127) == 0) mbar_arrive(sb + AX_EMPTY + 8 * st);
            if (++st == NST_G) { st = 0; ph ^= 1; }
            if (t.type == 3) break;
            const int np = (t.rb >= NFINE) ? 13 : 4;
            const float* pbase = (t.rb >= NFINE) ? g_part31 + (size_t)(t.rb - NFINE) * 13 * 64 * DM - (size_t)t.rb * 64 * DM : g_part;
            const size_t pstride = (t.rb >= NFINE) ? (size_t)64 * DM : (size_t)SEQ * DM;
            auto combine = [&](int i, auto NP) {
                const int r = t.k0 + i / 80, cc = t.c * 320 + (i % 80) * 4;
                float4 v[NP.value];
                #pragma unroll
                for (int q = 0; q < NP.value; q++) v[q] = __ldcg(reinterpret_cast<const float4*>(pbase + q * pstride + (size_t)r * DM + cc));
                const float gt = __ldcg(g_g + r);
                const uint2 bb = __ldcg(reinterpret_cast<const uint2*>(g_b + (size_t)r * DM + cc));
                float4 a = v[0];
                #pragma unroll
                for (int q = 1; q < NP.value; q++) { a.x += v[q].x; a.y += v[q].y; a.z += v[q].z; a.w += v[q].w; }
                const float b0 = __uint_as_float(bb.x << 16), b1 = __uint_as_float(bb.x & 0xffff0000u), b2 = __uint_as_float(bb.y << 16), b3 = __uint_as_float(bb.y & 0xffff0000u);
                uint2 o; o.x = pack_bf16(gt * a.x + (1.f - gt) * b0, gt * a.y + (1.f - gt) * b1); o.y = pack_bf16(gt * a.z + (1.f - gt) * b2, gt * a.w + (1.f - gt) * b3);
                *reinterpret_cast<uint2*>(out + (size_t)r * DM + cc) = o;
            };
            if (np == 4) {
                const int nit = t.nch * 80 / 256;
                for (int it0 = 0; it0 < nit; it0 += 5) {
                    #pragma unroll
                    for (int it = 0; it < 5; it++) combine(tid + 256 * (it0 + it), IntC<4>());
                }
            } else {
                #pragma unroll
                for (int it = 0; it < 3; it++) { const int i = tid + 256 * it; if (i < 640) combine(i, IntC<13>()); }
            }
            if (n < 56 && (blockIdx.x >= NATT || n < 4)) ATRID((blockIdx.x >= NATT ? 6 : 58) + n, s_tasks[n & 7]);
            continue;
        }
        const int g = lane >> 2, tq = lane & 3;
        if (t.type == 0) {
            float acc[160];
            #pragma unroll
            for (int i = 0; i < 160; i++) acc[i] = 0.f;
            uint32_t prev = 0;
            for (int kc = 0; kc < 16; kc++) {
                mbar_wait(sb + AX_BAR + 16 + 8 * st, ph);
                const uint32_t a = sb + AX_DATA + st * AX_STAGE;
                const uint64_t da = make_desc(a + wg * 8192, 16, 1024), db = make_desc(a + 16384, 8192, 1024);
                wg_fence();
                #pragma unroll
                for (int ks = 0; ks < 4; ks++) {
                    wgmma_n192_tB<0>(acc, da + ks * 2, db + ks * 128);
                    wgmma_n128_tB<96>(acc, da + ks * 2, db + ks * 128 + 3 * 512);
                }
                wg_commit();
                asm volatile("wgmma.wait_group.sync.aligned 1;" ::: "memory");
                if (kc > 0 && (tid & 127) == 0) mbar_arrive(sb + AX_EMPTY + 8 * prev);
                prev = st;
                if (++st == NST_G) { st = 0; ph ^= 1; }
            }
            wg_wait0();
            if ((tid & 127) == 0) mbar_arrive(sb + AX_EMPTY + 8 * prev);
            float* base = g_part + ((size_t)t.plane * SEQ + t.rb * 64 + wg * 64 + warp * 16 + g) * DM + t.c * 320 + 2 * tq;
            #pragma unroll
            for (int q = 0; q < 40; q++) {
                *reinterpret_cast<float2*>(base + q * 8) = make_float2(acc[4 * q], acc[4 * q + 1]);
                *reinterpret_cast<float2*>(base + 8 * DM + q * 8) = make_float2(acc[4 * q + 2], acc[4 * q + 3]);
            }
        } else {
            float* base = (t.rb >= NFINE ? g_part31 + (size_t)((t.rb - NFINE) * 13 + t.plane) * 64 * DM : g_part + ((size_t)t.plane * SEQ + t.rb * 64) * DM) + (size_t)(warp * 16 + g) * DM + t.c * 320 + 2 * tq;
            if (wg == 0) {
                float acc[160];
                #pragma unroll
                for (int i = 0; i < 96; i++) acc[i] = 0.f;
                uint32_t prev = 0;
                for (int kc = 0; kc < t.nch; kc++) {
                    mbar_wait(sb + AX_BAR + 16 + 8 * st, ph);
                    const uint32_t a = sb + AX_DATA + st * AX_STAGE;
                    const uint64_t da = make_desc(a, 16, 1024), db = make_desc(a + 16384, 8192, 1024);
                    wg_fence();
                    #pragma unroll
                    for (int ks = 0; ks < 4; ks++) wgmma_n192_tB<0>(acc, da + ks * 2, db + ks * 128);
                    wg_commit();
                    asm volatile("wgmma.wait_group.sync.aligned 1;" ::: "memory");
                    if (kc > 0 && (tid & 127) == 0) mbar_arrive(sb + AX_EMPTY + 8 * prev);
                    prev = st;
                    if (++st == NST_G) { st = 0; ph ^= 1; }
                }
                wg_wait0();
                if ((tid & 127) == 0) mbar_arrive(sb + AX_EMPTY + 8 * prev);
                #pragma unroll
                for (int q = 0; q < 24; q++) {
                    *reinterpret_cast<float2*>(base + q * 8) = make_float2(acc[4 * q], acc[4 * q + 1]);
                    *reinterpret_cast<float2*>(base + 8 * DM + q * 8) = make_float2(acc[4 * q + 2], acc[4 * q + 3]);
                }
            } else {
                float acc[160];
                #pragma unroll
                for (int i = 96; i < 160; i++) acc[i] = 0.f;
                uint32_t prev = 0;
                for (int kc = 0; kc < t.nch; kc++) {
                    mbar_wait(sb + AX_BAR + 16 + 8 * st, ph);
                    const uint32_t a = sb + AX_DATA + st * AX_STAGE;
                    const uint64_t da = make_desc(a, 16, 1024), db = make_desc(a + 16384, 8192, 1024);
                    wg_fence();
                    #pragma unroll
                    for (int ks = 0; ks < 4; ks++) wgmma_n128_tB<96>(acc, da + ks * 2, db + ks * 128 + 3 * 512);
                    wg_commit();
                    asm volatile("wgmma.wait_group.sync.aligned 1;" ::: "memory");
                    if (kc > 0 && (tid & 127) == 0) mbar_arrive(sb + AX_EMPTY + 8 * prev);
                    prev = st;
                    if (++st == NST_G) { st = 0; ph ^= 1; }
                }
                wg_wait0();
                if ((tid & 127) == 0) mbar_arrive(sb + AX_EMPTY + 8 * prev);
                #pragma unroll
                for (int q = 24; q < 40; q++) {
                    *reinterpret_cast<float2*>(base + q * 8) = make_float2(acc[4 * q], acc[4 * q + 1]);
                    *reinterpret_cast<float2*>(base + 8 * DM + q * 8) = make_float2(acc[4 * q + 2], acc[4 * q + 3]);
                }
            }
        }
        if (tid == 0) s_done[ndone & 7] = s_tasks[n & 7];
        ndone++;
        nbar_arrive(2, 288);
        if (n < 56 && (blockIdx.x >= NATT || n < 4)) ATRID((blockIdx.x >= NATT ? 6 : 58) + n, s_tasks[n & 7]);
    }
    if (tid == 0) s_done[ndone & 7] = -1;
    nbar_arrive(2, 288);
}

__global__ void __launch_bounds__(384, 1)
k_aux(const __grid_constant__ CUtensorMap womap, const bf16* __restrict__ x, const bf16* __restrict__ A_re, const bf16* __restrict__ A_im,
      const bf16* __restrict__ B_re, const bf16* __restrict__ B_im, const bf16* __restrict__ C_re, const bf16* __restrict__ C_im,
      const bf16* __restrict__ log_dt, const bf16* __restrict__ Dskip, const bf16* __restrict__ gw, bf16* __restrict__ out) {
    extern __shared__ __align__(1024) unsigned char smem[];
    const uint32_t sb = smem_u32(smem);
    const int tid = threadIdx.x, warp = tid >> 5, lane = tid & 31;
    __shared__ unsigned s_epoch;
    __shared__ int s_task, s_tasks[8], s_done[8];
    if (tid == 0) {
        for (int i = 0; i < 2 + NST_G; i++) mbar_init(sb + AX_BAR + 8 * i, 1);
        for (int i = 0; i < NST_G; i++) mbar_init(sb + AX_EMPTY + 8 * i, blockIdx.x < NATT ? 8 : 2);
        asm volatile("fence.mbarrier_init.release.cluster;" ::: "memory");
        s_epoch = *reinterpret_cast<volatile unsigned*>(&g_epoch);
    }
    __syncthreads();
    const unsigned epoch = s_epoch;
    ATR(0);
    const int wg = __shfl_sync(~0u, tid >> 7, 0);
    if (wg == 2) {
        asm volatile("setmaxnreg.dec.sync.aligned.u32 40;");
        if (blockIdx.x < NATT) { if (warp == 8) attn_producer(smem, blockIdx.x, epoch); else if (warp == 9) attn_storer(smem, blockIdx.x); __syncwarp(); }
        nbar_sync(3, 384);
        nbar_sync(3, 384);
        if (warp == 8) { if (lane == 0) gemm_producer(smem, &womap, epoch, s_tasks); }
        else if (warp == 9) gemm_signaller(s_done);
        __syncwarp();
        nbar_sync(4, 384);
    } else {
        asm volatile("setmaxnreg.inc.sync.aligned.u32 232;");
        if (blockIdx.x < NATT) attn_loop(smem, blockIdx.x, epoch);
        else {
            int ntask = 0;
            for (;;) {
                nbar_sync(1, 256);
                if (tid == 0) s_task = (int)(atomicAdd(&g_taskctr, 1u) - epoch * (unsigned)(80 + NAUX - NATT));
                nbar_sync(1, 256);
                const int task = s_task;
                if (task >= 80) break;
                for (int r = task * 26 + warp; r < min(SEQ, task * 26 + 26); r += 8) {
                    float sum = 0.f;
                    for (int i = lane * 2; i < DM; i += 64) {
                        __nv_bfloat162 xv = *reinterpret_cast<const __nv_bfloat162*>(x + (size_t)r * DM + i), wv = *reinterpret_cast<const __nv_bfloat162*>(gw + i);
                        sum += bf2f(xv.x) * bf2f(wv.x) + bf2f(xv.y) * bf2f(wv.y);
                    }
                    #pragma unroll
                    for (int o = 16; o; o >>= 1) sum += __shfl_xor_sync(~0u, sum, o);
                    if (lane == 0) g_g[r] = 1.f / (1.f + expf(-sum));
                }
                ssm_group(smem + AX_DATA, task, x, A_re, A_im, B_re, B_im, C_re, C_im, log_dt, Dskip);
                nbar_sync(1, 256);
                if (tid == 0) { __threadfence(); atomicAdd(&g_ssmcnt, 1u); }
                if (ntask < 4) ATR(2 + ntask);
                ntask++;
            }
        }
        fence_async();
        nbar_sync(3, 384);
        if (tid == 0) {
            for (int i = 0; i < NST_G; i++) {
                asm volatile("mbarrier.inval.shared::cta.b64 [%0];" :: "r"(sb + AX_BAR + 16 + 8 * i) : "memory");
                asm volatile("mbarrier.inval.shared::cta.b64 [%0];" :: "r"(sb + AX_EMPTY + 8 * i) : "memory");
                mbar_init(sb + AX_BAR + 16 + 8 * i, 1); mbar_init(sb + AX_EMPTY + 8 * i, 2);
            }
            asm volatile("fence.mbarrier_init.release.cluster;" ::: "memory");
        }
        nbar_sync(3, 384);
        gemm_consumer(smem, out, s_tasks, s_done);
        nbar_sync(4, 384);
        if (tid == 0) {
            __threadfence();
            unsigned old = atomicAdd(&g_auxdone, 1u);
            if (old == NAUX - 1) { g_auxdone = 0; __threadfence(); atomicAdd(&g_epoch, 1u); }
        }
    }
    asm volatile("griddepcontrol.wait;" ::: "memory");
}

extern "C" void kernel_launch(void* const* d_in, const int* in_sizes, int n_in, void* d_out, int out_size) {
    const bf16* x = (const bf16*)d_in[0];
    const bf16* mem0 = (const bf16*)d_in[1];
    const bf16* Wq = (const bf16*)d_in[2];
    const bf16* Wk = (const bf16*)d_in[3];
    const bf16* Wv = (const bf16*)d_in[4];
    const bf16* Wo = (const bf16*)d_in[5];
    const bf16 *A_re = (const bf16*)d_in[8], *A_im = (const bf16*)d_in[9], *B_re = (const bf16*)d_in[10], *B_im = (const bf16*)d_in[11];
    const bf16 *C_re = (const bf16*)d_in[12], *C_im = (const bf16*)d_in[13], *log_dt = (const bf16*)d_in[14], *Dskip = (const bf16*)d_in[15];
    const bf16* gw = (const bf16*)d_in[16];
    bf16* out = (bf16*)d_out;
    cudaStream_t st = cudaStreamPerThread;
    static bool init = false;
    static CUtensorMap xmap, womap, wqmap, wkmap, wvmap;
    static const void* xmap_ptr = nullptr; static const void* womap_ptr = nullptr; static const void* w_ptr[3] = {nullptr, nullptr, nullptr};
    if (!init) {
        cudaFuncSetAttribute(k_chain, cudaFuncAttributeMaxDynamicSharedMemorySize, SM_TOTAL);
        cudaFuncSetAttribute(k_aux, cudaFuncAttributeMaxDynamicSharedMemorySize, AX_TOTAL);
        init = true;
    }
    if (xmap_ptr != (const void*)x || womap_ptr != (const void*)Wo || w_ptr[0] != Wq || w_ptr[1] != Wk || w_ptr[2] != Wv) {
        void* fn = nullptr; cudaDriverEntryPointQueryResult qres;
        cudaGetDriverEntryPoint("cuTensorMapEncodeTiled", &fn, cudaEnableDefault, &qres);
        typedef CUresult (*EncFn)(CUtensorMap*, CUtensorMapDataType, cuuint32_t, void*, const cuuint64_t*, const cuuint64_t*, const cuuint32_t*, const cuuint32_t*,
                                  CUtensorMapInterleave, CUtensorMapSwizzle, CUtensorMapL2promotion, CUtensorMapFloatOOBfill);
        cuuint32_t es[2] = {1, 1};
        {
          cuuint64_t dims[3] = {64, SEQ, 10}; cuuint64_t strides[2] = {DM * 2, 128}; cuuint32_t box[3] = {64, 32, 10}; cuuint32_t es3[3] = {1, 1, 1};
          ((EncFn)fn)(&xmap, CU_TENSOR_MAP_DATA_TYPE_BFLOAT16, 3, (void*)x, dims, strides, box, es3, CU_TENSOR_MAP_INTERLEAVE_NONE, CU_TENSOR_MAP_SWIZZLE_128B,
                      CU_TENSOR_MAP_L2_PROMOTION_L2_128B, CU_TENSOR_MAP_FLOAT_OOB_FILL_NONE); }
        { cuuint64_t dims[2] = {DM, HD}; cuuint64_t strides[1] = {DM * 2}; cuuint32_t box[2] = {64, 64};
          ((EncFn)fn)(&womap, CU_TENSOR_MAP_DATA_TYPE_BFLOAT16, 2, (void*)Wo, dims, strides, box, es, CU_TENSOR_MAP_INTERLEAVE_NONE, CU_TENSOR_MAP_SWIZZLE_128B,
                      CU_TENSOR_MAP_L2_PROMOTION_L2_128B, CU_TENSOR_MAP_FLOAT_OOB_FILL_NONE); }
        { cuuint64_t dims[2] = {HD, DM}; cuuint64_t strides[1] = {HD * 2}; cuuint32_t box[2] = {64, 128};
          const bf16* ws[3] = {Wq, Wk, Wv}; CUtensorMap* ms[3] = {&wqmap, &wkmap, &wvmap};
          for (int i = 0; i < 3; i++)
              ((EncFn)fn)(ms[i], CU_TENSOR_MAP_DATA_TYPE_BFLOAT16, 2, (void*)ws[i], dims, strides, box, es, CU_TENSOR_MAP_INTERLEAVE_NONE, CU_TENSOR_MAP_SWIZZLE_128B,
                          CU_TENSOR_MAP_L2_PROMOTION_L2_128B, CU_TENSOR_MAP_FLOAT_OOB_FILL_NONE); }
        xmap_ptr = (const void*)x; womap_ptr = (const void*)Wo; w_ptr[0] = Wq; w_ptr[1] = Wk; w_ptr[2] = Wv;
    }
    k_chain<<<96, 384, SM_TOTAL, st>>>(xmap, wqmap, wkmap, wvmap, womap, x, mem0);
    {
        cudaLaunchConfig_t cfg = {};
        cfg.gridDim = dim3(NAUX); cfg.blockDim = dim3(384); cfg.dynamicSmemBytes = AX_TOTAL; cfg.stream = st;
        cudaLaunchAttribute at[1];
        at[0].id = cudaLaunchAttributeProgrammaticStreamSerialization; at[0].val.programmaticStreamSerializationAllowed = 1;
        cfg.attrs = at; cfg.numAttrs = 1;
        cudaLaunchKernelEx(&cfg, k_aux, womap, x, A_re, A_im, B_re, B_im, C_re, C_im, log_dt, Dskip, gw, out);
    }
}
```

```cpp
#include <cuda_runtime.h>
#include <cuda_bf16.h>
#include <stdint.h>
#include <cuda.h>

typedef __nv_bfloat16 bf16;

#define SEQ 2048
#define DM 640
#define NH 32
#define DH 128
#define NM 8
#define SEG 32
#define NSEG 64
#define NST 128
#define HD 4096

__device__ bf16  g_b[SEQ * DM];
__device__ float g_g[SEQ];

__device__ __forceinline__ float bf2f(bf16 v) { return __bfloat162float(v); }
__device__ __forceinline__ uint32_t pack_bf16(float lo, float hi) {
    uint32_t r; asm("cvt.rn.bf16x2.f32 %0, %1, %2;" : "=r"(r) : "f"(hi), "f"(lo)); return r;
}
__device__ __forceinline__ uint32_t f2tf32(float x) { uint32_t r; asm("cvt.rna.tf32.f32 %0, %1;" : "=r"(r) : "f"(x)); return r; }
__device__ __forceinline__ void mma_tf32(float (&d)[4], uint32_t a0, uint32_t a1, uint32_t a2, uint32_t a3, uint32_t b0, uint32_t b1) {
    asm volatile("mma.sync.aligned.m16n8k8.row.col.f32.tf32.tf32.f32 {%0,%1,%2,%3}, {%4,%5,%6,%7}, {%8,%9}, {%0,%1,%2,%3};\n"
        : "+f"(d[0]), "+f"(d[1]), "+f"(d[2]), "+f"(d[3]) : "r"(a0), "r"(a1), "r"(a2), "r"(a3), "r"(b0), "r"(b1));
}
__device__ __forceinline__ void mma_bf16(float (&d)[4], uint32_t a0, uint32_t a1, uint32_t a2, uint32_t a3, uint32_t b0, uint32_t b1) {
    asm volatile("mma.sync.aligned.m16n8k16.row.col.f32.bf16.bf16.f32 {%0,%1,%2,%3}, {%4,%5,%6,%7}, {%8,%9}, {%0,%1,%2,%3};\n"
        : "+f"(d[0]), "+f"(d[1]), "+f"(d[2]), "+f"(d[3]) : "r"(a0), "r"(a1), "r"(a2), "r"(a3), "r"(b0), "r"(b1));
}
struct cf { float re, im; };
__device__ __forceinline__ cf cmul(cf a, cf b) { cf r; r.re = a.re * b.re - a.im * b.im; r.im = a.re * b.im + a.im * b.re; return r; }
__device__ __forceinline__ cf csq(cf a) { cf r; r.re = a.re * a.re - a.im * a.im; r.im = 2.f * a.re * a.im; return r; }
__device__ __forceinline__ cf cexpL(float zr, float zi, float L) {
    float e = __expf(zr * L);
    float ang = zi * L;
    float k = rintf(ang * 0.15915494309189535f);
    ang = fmaf(-k, 6.2831854820251465f, ang);
    ang = fmaf(-k, -1.7484555314695172e-07f, ang);
    cf r; r.re = e * __cosf(ang); r.im = e * __sinf(ang); return r;
}

#define SSM_CH 8
#define KC_PITCH 648
#define XS_PAD 128
#define XS_PITCH (XS_PAD + 2048 + 8)
#define YS_PITCH (2048 + 8)
#define KT_LEN (2048 + 48)
struct SsmSmem {
    float Kc[SSM_CH][KC_PITCH];
    bf16  xs[SSM_CH][XS_PITCH];
    union {
        bf16  KT[SSM_CH][2][KT_LEN];
        float st[SSM_CH][NST][8];
    } u;
    bf16  ys[SSM_CH][YS_PITCH];
    uint16_t kidx[2048];
};

__device__ __forceinline__ int kc_index(int l) {
    return l < 256 ? l : (l < 512 ? 256 + ((l - 256) >> 1) : (l < 1024 ? 384 + ((l - 512) >> 2) : 512 + ((l - 1024) >> 3)));
}

__device__ __forceinline__ void ssm_group(unsigned char* smem_raw, int grp, const bf16* __restrict__ x, const bf16* __restrict__ A_re, const bf16* __restrict__ A_im,
        const bf16* __restrict__ B_re, const bf16* __restrict__ B_im, const bf16* __restrict__ C_re, const bf16* __restrict__ C_im,
        const bf16* __restrict__ log_dt, const bf16* __restrict__ Dskip) {
    SsmSmem& S = *reinterpret_cast<SsmSmem*>(smem_raw);
    const int tid = threadIdx.x, w = tid >> 5, lane = tid & 31, g = lane >> 2, t = lane & 3;
    const int d0 = grp * SSM_CH;
    asm volatile("bar.sync 1, 256;" ::: "memory");
    #pragma unroll
    for (int it = 0; it < 8; it++) {
        const int l = tid + 256 * it;
        uint4 v = *reinterpret_cast<const uint4*>(x + (size_t)l * DM + d0);
        const bf16* p = reinterpret_cast<const bf16*>(&v);
        const int lr = (l & ~15) | (15 - (l & 15));
        #pragma unroll
        for (int c = 0; c < 8; c++) S.xs[c][XS_PAD + lr] = p[c];
        S.kidx[l] = (uint16_t)((int)bf2f(__float2bfloat16_rn((float)l)) == 2048 ? 640 : kc_index((int)bf2f(__float2bfloat16_rn((float)l))));
    }
    for (int i = tid; i < SSM_CH * XS_PAD / 2; i += 256) reinterpret_cast<uint32_t*>(&S.xs[i / (XS_PAD / 2)][0])[i % (XS_PAD / 2)] = 0u;
    {
        const int d = d0 + w;
        const float dt = bf2f(__float2bfloat16_rn(expf(bf2f(log_dt[d]))));
        #pragma unroll
        for (int i = 0; i < 4; i++) {
            const int n = lane + 32 * i;
            float zr = dt * bf2f(A_re[d * NST + n]), zi = dt * bf2f(A_im[d * NST + n]);
            cf dB; dB.re = dt * bf2f(B_re[d * NST + n]); dB.im = dt * bf2f(B_im[d * NST + n]);
            cf C; C.re = bf2f(C_re[d * NST + n]); C.im = bf2f(C_im[d * NST + n]);
            cf wv = cmul(C, dB);
            cf u8 = cexpL(zr, zi, 8.f), u128 = cexpL(zr, zi, 128.f);
            float* st = S.u.st[w][n];
            *reinterpret_cast<float4*>(st) = make_float4(zr, zi, wv.re, wv.im);
            *reinterpret_cast<float4*>(st + 4) = make_float4(u8.re, u8.im, u128.re, u128.im);
        }
        __syncwarp();
        float a0a[4] = {0, 0, 0, 0}, a0b[4] = {0, 0, 0, 0}, a1[4] = {0, 0, 0, 0}, a2a[4] = {0, 0, 0, 0}, a2b[4] = {0, 0, 0, 0};
        float k2048 = 0.f;
        const float Lg = (g < 4) ? (512.f + 4.f * g) : (g < 6 ? 1024.f + 8.f * (g - 4) : 1536.f + 8.f * (g - 6));
        #pragma unroll 4
        for (int kk = 0; kk < 32; kk++) {
            const float* st = S.u.st[w][4 * kk + t];
            float4 s0 = *reinterpret_cast<const float4*>(st), s1 = *reinterpret_cast<const float4*>(st + 4);
            cf wv; wv.re = s0.z; wv.im = s0.w;
            cf u8; u8.re = s1.x; u8.im = s1.y;
            cf u128; u128.re = s1.z; u128.im = s1.w;
            cf e1 = cexpL(s0.x, s0.y, (float)g);
            cf e23 = cexpL(s0.x, s0.y, Lg);
            cf e1b = cmul(e1, u8);
            cf e2 = csq(e1);
            cf p = csq(csq(csq(e2)));
            cf f0 = cmul(wv, p), f1 = cmul(f0, u128), f2 = cmul(f1, u128), f3 = cmul(f2, u128);
            uint32_t A00 = f2tf32(f0.re), A01 = f2tf32(f1.re), A02 = f2tf32(-f0.im), A03 = f2tf32(-f1.im);
            uint32_t A10 = f2tf32(f2.re), A11 = f2tf32(f3.re), A12 = f2tf32(-f2.im), A13 = f2tf32(-f3.im);
            mma_tf32(a0a, A00, A01, A02, A03, f2tf32(e1.re), f2tf32(e1.im));
            mma_tf32(a0b, A00, A01, A02, A03, f2tf32(e1b.re), f2tf32(e1b.im));
            mma_tf32(a1, A10, A11, A12, A13, f2tf32(e2.re), f2tf32(e2.im));
            uint32_t E0 = f2tf32(e23.re), E1 = f2tf32(e23.im);
            mma_tf32(a2a, A00, A01, A02, A03, E0, E1);
            mma_tf32(a2b, A10, A11, A12, A13, E0, E1);
            cf e2048 = csq(e23);
            k2048 += wv.re * e2048.re - wv.im * e2048.im;
        }
        k2048 += __shfl_xor_sync(~0u, k2048, 1);
        k2048 += __shfl_xor_sync(~0u, k2048, 2);
        float* Kc = S.Kc[w];
        Kc[16 * g + 2 * t] = a0a[0]; Kc[16 * g + 2 * t + 1] = a0a[1]; Kc[16 * (g + 8) + 2 * t] = a0a[2]; Kc[16 * (g + 8) + 2 * t + 1] = a0a[3];
        Kc[16 * g + 8 + 2 * t] = a0b[0]; Kc[16 * g + 8 + 2 * t + 1] = a0b[1]; Kc[16 * (g + 8) + 8 + 2 * t] = a0b[2]; Kc[16 * (g + 8) + 8 + 2 * t + 1] = a0b[3];
        Kc[256 + 8 * g + 2 * t] = a1[0]; Kc[256 + 8 * g + 2 * t + 1] = a1[1]; Kc[256 + 8 * (g + 8) + 2 * t] = a1[2]; Kc[256 + 8 * (g + 8) + 2 * t + 1] = a1[3];
        #pragma unroll
        for (int mt = 0; mt < 2; mt++) {
            #pragma unroll
            for (int e = 0; e < 4; e++) {
                int A = mt * 16 + g + (e >> 1) * 8, j = 2 * t + (e & 1);
                int Lj = (j < 4) ? 512 + 4 * j : (j < 6 ? 1024 + 8 * (j - 4) : 1536 + 8 * (j - 6));
                Kc[kc_index(Lj + 16 * A)] = mt ? a2b[e] : a2a[e];
            }
        }
        if (lane == 16) Kc[640] = k2048;
    }
    __syncwarp();
    {
        asm volatile("bar.sync 1, 256;" ::: "memory");
        bf16* k0 = S.u.KT[w][0];
        bf16* k1 = S.u.KT[w][1];
        const float* Kc = S.Kc[w];
        #pragma unroll 8
        for (int j = lane; j < 2048; j += 32) {
            const bf16 v = __float2bfloat16_rn(Kc[S.kidx[j]]);
            k0[16 + j] = v;
            k1[15 + j] = v;
        }
        if (lane < 16) { k0[lane] = __float2bfloat16_rn(0.f); if (lane < 15) k1[lane] = __float2bfloat16_rn(0.f); }
        k0[2064 + lane] = __float2bfloat16_rn(0.f); k1[2063 + lane] = __float2bfloat16_rn(0.f);
        __syncwarp();
    }
    {
        float acc[16][4];
        #pragma unroll
        for (int v = 0; v < 16; v++) { acc[v][0] = acc[v][1] = acc[v][2] = acc[v][3] = 0.f; }
        const bf16* kt = (g & 1) ? &S.u.KT[w][0][0] : &S.u.KT[w][1][0];
        const int ibase0 = g + 1 + 2 * t - ((g & 1) ? 0 : 1);
        #pragma unroll 1
        for (int r = 0; r < 8; r++) {
            uint32_t B[16][2];
            #pragma unroll
            for (int v = 0; v < 16; v++) {
                const bf16* p = &S.xs[w][XS_PAD + 16 * (8 * v + g - r) + 2 * t];
                B[v][0] = *reinterpret_cast<const uint32_t*>(p);
                B[v][1] = *reinterpret_cast<const uint32_t*>(p + 8);
            }
            #pragma unroll
            for (int q = 0; q < 16; q++) {
                const int i0 = ibase0 + 16 * r + 128 * q;
                const uint32_t A0 = *reinterpret_cast<const uint32_t*>(kt + i0);
                const uint32_t A1 = *reinterpret_cast<const uint32_t*>(kt + i0 + 8);
                const uint32_t A3 = *reinterpret_cast<const uint32_t*>(kt + i0 + 16);
                #pragma unroll
                for (int v = q; v < 16; v++) mma_bf16(acc[v], A0, A1, A1, A3, B[v - q][0], B[v - q][1]);
            }
        }
        bf16* ys = S.ys[w];
        #pragma unroll
        for (int v = 0; v < 16; v++) {
            const int a = 8 * v + 2 * t;
            ys[16 * a + g] = __float2bfloat16_rn(acc[v][0]); ys[16 * (a + 1) + g] = __float2bfloat16_rn(acc[v][1]);
            ys[16 * a + g + 8] = __float2bfloat16_rn(acc[v][2]); ys[16 * (a + 1) + g + 8] = __float2bfloat16_rn(acc[v][3]);
        }
    }
    asm volatile("bar.sync 1, 256;" ::: "memory");
    {
        float dsk[8];
        #pragma unroll
        for (int c = 0; c < 8; c++) dsk[c] = bf2f(Dskip[d0 + c]);
        #pragma unroll 2
        for (int it = 0; it < 8; it++) {
            const int l = tid + 256 * it;
            const int lr = XS_PAD + ((l & ~15) | (15 - (l & 15)));
            float o[8];
            #pragma unroll
            for (int c = 0; c < 8; c++) o[c] = bf2f(S.ys[c][l]) + bf2f(__float2bfloat16_rn(bf2f(S.xs[c][lr]) * dsk[c]));
            *reinterpret_cast<uint4*>(g_b + (size_t)l * DM + d0) = make_uint4(pack_bf16(o[0], o[1]), pack_bf16(o[2], o[3]), pack_bf16(o[4], o[5]), pack_bf16(o[6], o[7]));
        }
    }
}

__device__ __forceinline__ uint32_t smem_u32(const void* p) { return (uint32_t)__cvta_generic_to_shared(p); }
__device__ __forceinline__ void mbar_init(uint32_t bar, uint32_t cnt) { asm volatile("mbarrier.init.shared::cta.b64 [%0], %1;" :: "r"(bar), "r"(cnt) : "memory"); }
__device__ __forceinline__ void mbar_expect_tx(uint32_t bar, uint32_t bytes) { asm volatile("mbarrier.arrive.expect_tx.shared::cta.b64 _, [%0], %1;" :: "r"(bar), "r"(bytes) : "memory"); }
__device__ __forceinline__ void mbar_arrive(uint32_t bar) { asm volatile("mbarrier.arrive.shared::cta.b64 _, [%0];" :: "r"(bar) : "memory"); }
__device__ __forceinline__ void mbar_wait(uint32_t bar, uint32_t parity) {
    uint32_t ok; int guard = 0;
    do {
        asm volatile("{\n.reg .pred P1;\nmbarrier.test_wait.parity.shared::cta.b64 P1, [%1], %2;\nselp.u32 %0,1,0,P1;\n}" : "=r"(ok) : "r"(bar), "r"(parity) : "memory");
    } while (!ok && ++guard < (1 << 26));
}
__device__ __forceinline__ void mbar_wait_sleep(uint32_t bar, uint32_t parity) {
    uint32_t ok; int guard = 0;
    do {
        asm volatile("{\n.reg .pred P1;\nmbarrier.try_wait.parity.shared::cta.b64 P1, [%1], %2;\nselp.u32 %0,1,0,P1;\n}" : "=r"(ok) : "r"(bar), "r"(parity) : "memory");
    } while (!ok && ++guard < (1 << 22));
}
__device__ __forceinline__ uint32_t mapa(uint32_t addr, uint32_t rank) { uint32_t r; asm volatile("mapa.shared::cluster.u32 %0, %1, %2;" : "=r"(r) : "r"(addr), "r"(rank)); return r; }
__device__ __forceinline__ void st_async4(uint32_t addr, float a, float b, float c, float d, uint32_t bar) {
    asm volatile("st.async.weak.shared::cluster.mbarrier::complete_tx::bytes.v4.f32 [%0], {%1,%2,%3,%4}, [%5];" :: "r"(addr), "f"(a), "f"(b), "f"(c), "f"(d), "r"(bar) : "memory");
}
__device__ __forceinline__ void bulk_s2c(uint32_t dst, uint32_t src, uint32_t bytes, uint32_t bar) {
    asm volatile("cp.async.bulk.shared::cluster.shared::cta.mbarrier::complete_tx::bytes [%0], [%1], %2, [%3];" :: "r"(dst), "r"(src), "r"(bytes), "r"(bar) : "memory");
}
__device__ __forceinline__ void bulk_g2s(uint32_t dst, const void* src, uint32_t bytes, uint32_t bar) {
    asm volatile("cp.async.bulk.shared::cluster.global.mbarrier::complete_tx::bytes [%0], [%1], %2, [%3];" :: "r"(dst), "l"(src), "r"(bytes), "r"(bar) : "memory");
}
__device__ __forceinline__ void bulk_s2g(void* dst, uint32_t src, uint32_t bytes) {
    asm volatile("cp.async.bulk.global.shared::cta.bulk_group [%0], [%1], %2;" :: "l"(dst), "r"(src), "r"(bytes) : "memory");
}
__device__ __forceinline__ void bulk_commit() { asm volatile("cp.async.bulk.commit_group;" ::: "memory"); }
__device__ __forceinline__ void bulk_wait_read0() { asm volatile("cp.async.bulk.wait_group.read 0;" ::: "memory"); }
__device__ __forceinline__ void bulk_wait0() { asm volatile("cp.async.bulk.wait_group 0;" ::: "memory"); }
__device__ __forceinline__ void fence_async() { asm volatile("fence.proxy.async.shared::cta;" ::: "memory"); }
__device__ __forceinline__ void nbar_sync(int id, int n) { asm volatile("bar.sync %0, %1;" :: "r"(id), "r"(n) : "memory"); }
__device__ __forceinline__ void nbar_arrive(int id, int n) { asm volatile("bar.arrive %0, %1;" :: "r"(id), "r"(n) : "memory"); }
__device__ __forceinline__ void cp_async16(uint32_t dst, const void* src) { asm volatile("cp.async.cg.shared.global [%0], [%1], 16;" :: "r"(dst), "l"(src) : "memory"); }
__device__ __forceinline__ void cp_async_wait_all() { asm volatile("cp.async.wait_all;" ::: "memory"); }
__device__ __forceinline__ void ldsm4(uint32_t (&r)[4], uint32_t addr) {
    asm volatile("ldmatrix.sync.aligned.m8n8.x4.shared.b16 {%0,%1,%2,%3}, [%4];" : "=r"(r[0]), "=r"(r[1]), "=r"(r[2]), "=r"(r[3]) : "r"(addr) : "memory");
}
__device__ __forceinline__ void ldsm4t(uint32_t (&r)[4], uint32_t addr) {
    asm volatile("ldmatrix.sync.aligned.m8n8.x4.trans.shared.b16 {%0,%1,%2,%3}, [%4];" : "=r"(r[0]), "=r"(r[1]), "=r"(r[2]), "=r"(r[3]) : "r"(addr) : "memory");
}
__device__ __forceinline__ void stsm2t(uint32_t addr, uint32_t r0, uint32_t r1) {
    asm volatile("stmatrix.sync.aligned.m8n8.x2.trans.shared.b16 [%0], {%1,%2};" :: "r"(addr), "r"(r0), "r"(r1) : "memory");
}
__device__ __forceinline__ uint4 ld_relaxed4(const void* p) { uint4 v; asm volatile("ld.relaxed.gpu.global.v4.u32 {%0,%1,%2,%3}, [%4];" : "=r"(v.x), "=r"(v.y), "=r"(v.z), "=r"(v.w) : "l"(p) : "memory"); return v; }
__device__ __forceinline__ void st_relaxed2(void* p, uint32_t a, uint32_t b) { asm volatile("st.relaxed.gpu.global.v2.u32 [%0], {%1,%2};" :: "l"(p), "r"(a), "r"(b) : "memory"); }
__device__ __forceinline__ void st_relaxed1(void* p, uint32_t a) { asm volatile("st.relaxed.gpu.global.u32 [%0], %1;" :: "l"(p), "r"(a) : "memory"); }
__device__ __forceinline__ unsigned ld_acquire(const unsigned* p) { unsigned v; asm volatile("ld.acquire.gpu.global.u32 %0, [%1];" : "=r"(v) : "l"(p) : "memory"); return v; }
__device__ __forceinline__ float ex2_approx(float x) { float r; asm("ex2.approx.ftz.f32 %0, %1;" : "=f"(r) : "f"(x)); return r; }
__device__ __forceinline__ uint64_t make_desc(uint32_t saddr, uint32_t lbo, uint32_t sbo) {
    return (uint64_t)((saddr & 0x3FFFF) >> 4) | ((uint64_t)((lbo & 0x3FFFF) >> 4) << 16) | ((uint64_t)((sbo & 0x3FFFF) >> 4) << 32) | (1ull << 62);
}
__device__ __forceinline__ void wg_fence() { asm volatile("wgmma.fence.sync.aligned;" ::: "memory"); }
__device__ __forceinline__ void wg_commit() { asm volatile("wgmma.commit_group.sync.aligned;" ::: "memory"); }
__device__ __forceinline__ void wg_wait0() { asm volatile("wgmma.wait_group.sync.aligned 0;" ::: "memory"); }
__device__ __forceinline__ void wgmma_n40_tA(float (&d)[20], uint64_t da, uint64_t db, int scale_d) {
    asm volatile("{\n.reg .pred p;\nsetp.ne.b32 p, %22, 0;\n"
        "wgmma.mma_async.sync.aligned.m64n40k16.f32.bf16.bf16 {%0,%1,%2,%3,%4,%5,%6,%7,%8,%9,%10,%11,%12,%13,%14,%15,%16,%17,%18,%19}, %20, %21, p, 1, 1, 1, 0;\n}\n"
        : "+f"(d[0]), "+f"(d[1]), "+f"(d[2]), "+f"(d[3]), "+f"(d[4]), "+f"(d[5]), "+f"(d[6]), "+f"(d[7]), "+f"(d[8]), "+f"(d[9]),
          "+f"(d[10]), "+f"(d[11]), "+f"(d[12]), "+f"(d[13]), "+f"(d[14]), "+f"(d[15]), "+f"(d[16]), "+f"(d[17]), "+f"(d[18]), "+f"(d[19])
        : "l"(da), "l"(db), "r"(scale_d));
}

#define NRED 80
#define CAL_THR 410u
#define COMM_REGS "40"
#define NPOOL 576
#define RPS 1
__device__ __align__(4096) uint32_t g_pool[(NPOOL + 1) * 1024];
__device__ unsigned g_cls[NPOOL];
__device__ unsigned g_side[96];
__device__ unsigned g_calcnt;
__device__ unsigned g_epoch;
__device__ unsigned g_flag[NSEG][NH];
__device__ __align__(1024) bf16 g_Qimg[NSEG * NH * 2 * 32 * 64];
__device__ __align__(1024) bf16 g_Kimg[NSEG * NH * 2 * 40 * 64];
__device__ __align__(1024) bf16 g_Vimg[NSEG * NH * 2 * 40 * 64];

#define SM_XB    0
#define SM_VT    81920
#define SM_KT    (SM_VT + 20480)
#define SM_QT    (SM_KT + 10240)
#define SM_QS    (SM_QT + 4096)
#define SM_MEMB  (SM_QS + 1024)
#define SM_RED   (SM_MEMB + 10240)
#define SM_SC    (SM_RED + 16384)
#define SM_CRED  (SM_SC + 5120)
#define SM_PB    (SM_CRED + 1024)
#define SM_TRACE (SM_PB + 1024)
#define SM_WO    163840
#define SM_BAR   (SM_WO + 65536)
#define SM_TPM   (SM_BAR + 256)
#define SM_TRD   (SM_TPM + 256)
#define SM_TPUB  (SM_TRD + 16)
#define SM_TGAT  (SM_TPUB + 128)
#define SM_CAL   (SM_TGAT + 64)
#define SM_TOTAL (SM_CAL + 128)
#define B_SC   (SM_BAR + 0)
#define B_V    (SM_BAR + 16)
#define B_P    (SM_BAR + 48)
#define B_X    (SM_BAR + 56)
#define B_EXP  (SM_BAR + 72)

#define TR(ev) do {} while (0)
__device__ __forceinline__ uint32_t tag_of(int s) { return (uint32_t)(((s >> 1) & 1) + 1); }
__device__ __forceinline__ unsigned probe_latency(uint32_t* p, uint32_t zero) {
    uint32_t v, best = 0xffffffffu;
    asm volatile("atom.relaxed.gpu.global.add.u32 %0, [%1], 0;" : "=r"(v) : "l"(p) : "memory");
    #pragma unroll 1
    for (int r = 0; r < 4; r++) {
        uint32_t c0, c1;
        asm volatile("mov.u32 %0, %%clock;" : "=r"(c0) : "r"(v) : "memory");
        asm volatile("atom.relaxed.gpu.global.add.u32 %0, [%1], 0;" : "=r"(v) : "l"(p + ((v + c0) & zero)) : "memory");
        asm volatile("{\n.reg .u32 t;\nand.b32 t, %1, %2;\nmov.u32 %0, %%clock;\nadd.u32 %0, %0, t;\n}" : "=r"(c1) : "r"(v), "r"(zero) : "memory");
        best = min(best, c1 - c0);
    }
    return best;
}
__device__ __forceinline__ void cluster_sync_all() { asm volatile("barrier.cluster.arrive.release.aligned;\nbarrier.cluster.wait.acquire.aligned;" ::: "memory"); }
__device__ __forceinline__ void tma_load_2d(uint32_t dst, const void* map, int c0, int c1, uint32_t bar) {
    asm volatile("cp.async.bulk.tensor.2d.shared::cluster.global.mbarrier::complete_tx::bytes [%0], [%1, {%3, %4}], [%2];"
        :: "r"(dst), "l"(map), "r"(bar), "r"(c0), "r"(c1) : "memory");
}
__device__ __forceinline__ void tma_load_3d(uint32_t dst, const void* map, int c0, int c1, int c2, uint32_t bar) {
    asm volatile("cp.async.bulk.tensor.3d.shared::cluster.global.mbarrier::complete_tx::bytes [%0], [%1, {%3, %4, %5}], [%2];"
        :: "r"(dst), "l"(map), "r"(bar), "r"(c0), "r"(c1), "r"(c2) : "memory");
}
__device__ __forceinline__ void stsm4t(uint32_t addr, uint32_t r0, uint32_t r1, uint32_t r2, uint32_t r3) {
    asm volatile("stmatrix.sync.aligned.m8n8.x4.trans.shared.b16 [%0], {%1,%2,%3,%4};" :: "r"(addr), "r"(r0), "r"(r1), "r"(r2), "r"(r3) : "memory");
}
__device__ __forceinline__ void wgmma_n32_rs(float (&d)[16], const uint32_t (&a)[4], uint64_t db, int scale_d) {
    asm volatile("{\n.reg .pred p;\nsetp.ne.b32 p, %21, 0;\n"
        "wgmma.mma_async.sync.aligned.m64n32k16.f32.bf16.bf16 {%0,%1,%2,%3,%4,%5,%6,%7,%8,%9,%10,%11,%12,%13,%14,%15}, {%16,%17,%18,%19}, %20, p, 1, 1, 0;\n}\n"
        : "+f"(d[0]), "+f"(d[1]), "+f"(d[2]), "+f"(d[3]), "+f"(d[4]), "+f"(d[5]), "+f"(d[6]), "+f"(d[7]),
          "+f"(d[8]), "+f"(d[9]), "+f"(d[10]), "+f"(d[11]), "+f"(d[12]), "+f"(d[13]), "+f"(d[14]), "+f"(d[15])
        : "r"(a[0]), "r"(a[1]), "r"(a[2]), "r"(a[3]), "l"(db), "r"(scale_d));
}

__device__ __forceinline__ void st_async4u(uint32_t addr, uint4 v, uint32_t bar) {
    asm volatile("st.async.weak.shared::cluster.mbarrier::complete_tx::bytes.v4.u32 [%0], {%1,%2,%3,%4}, [%5];" :: "r"(addr), "r"(v.x), "r"(v.y), "r"(v.z), "r"(v.w), "r"(bar) : "memory");
}
__device__ __forceinline__ void export_issue(uint32_t sb, int s, int h, uint32_t rank) {
    const size_t img = (size_t)(s * NH + h) * 2;
    const int sl = s & 1;
    if (rank == 2) {
        bulk_s2g(g_Vimg + img * 2560, sb + SM_VT + sl * 10240, 5120);
        bulk_s2g(g_Vimg + (img + 1) * 2560, sb + SM_VT + sl * 10240 + 5120, 5120);
    } else {
        bulk_s2g(g_Qimg + (img + rank) * 2048, sb + SM_QT, 4096);
        bulk_s2g(g_Kimg + (img + rank) * 2560, sb + SM_KT + sl * 5120, 5120);
    }
    bulk_commit();
    bulk_wait_read0();
    mbar_arrive(sb + B_EXP);
}
__device__ __forceinline__ void export_signal(int s, int h) {
    bulk_wait0();
    asm volatile("fence.proxy.async;" ::: "memory");
    __threadfence();
    atomicAdd(&g_flag[s][h], 1u);
}

__device__ __forceinline__ void score_tile(uint32_t sb, int sl, int nt, int lane, uint32_t rank) {
    float sc[4] = {0, 0, 0, 0}, sd[4] = {0, 0, 0, 0};
    const int r = lane & 7;
    uint32_t qa[2][4], kb[2][4];
    #pragma unroll
    for (int j = 0; j < 2; j++) {
        const int chunk = (lane >> 3) + 4 * j;
        ldsm4(kb[j], sb + SM_KT + sl * 5120 + (8 * nt + r) * 128 + ((chunk ^ r) << 4));
        ldsm4(qa[j], sb + SM_QS + r * 128 + ((chunk ^ r) << 4));
    }
    mma_bf16(sc, qa[0][0], 0u, qa[0][1], 0u, kb[0][0], kb[0][1]);
    mma_bf16(sd, qa[1][0], 0u, qa[1][1], 0u, kb[1][0], kb[1][1]);
    mma_bf16(sc, qa[0][2], 0u, qa[0][3], 0u, kb[0][2], kb[0][3]);
    mma_bf16(sd, qa[1][2], 0u, qa[1][3], 0u, kb[1][2], kb[1][3]);
    sc[0] += sd[0]; sc[1] += sd[1];
    const float o0 = __shfl_down_sync(~0u, sc[0], 1), o1 = __shfl_down_sync(~0u, sc[1], 1);
    if ((lane & 1) == 0) {
        const uint32_t a = SM_SC + sl * 2560 + rank * 1280 + ((lane >> 2) * 40 + 8 * nt + 2 * (lane & 3)) * 4;
        const uint32_t bo = B_SC + 8 * sl;
        { const uint32_t rb = mapa(sb, 2); st_async4(rb + a, sc[0], sc[1], o0, o1, rb + bo); }
        { const uint32_t rb = mapa(sb, rank ^ 1); st_async4(rb + a, sc[0], sc[1], o0, o1, rb + bo); }
        asm volatile("st.shared.v4.f32 [%0], {%1,%2,%3,%4};" :: "r"(sb + a), "f"(sc[0]), "f"(sc[1]), "f"(o0), "f"(o1) : "memory");
    }
    __syncwarp();
    if (lane == 0) mbar_arrive(sb + B_SC + 8 * sl);
}
__device__ __forceinline__ void wgmma_n40_rs(float (&d)[20], const uint32_t (&a)[4], uint64_t db, int scale_d) {
    asm volatile("{\n.reg .pred p;\nsetp.ne.b32 p, %25, 0;\n"
        "wgmma.mma_async.sync.aligned.m64n40k16.f32.bf16.bf16 {%0,%1,%2,%3,%4,%5,%6,%7,%8,%9,%10,%11,%12,%13,%14,%15,%16,%17,%18,%19}, {%20,%21,%22,%23}, %24, p, 1, 1, 0;\n}\n"
        : "+f"(d[0]), "+f"(d[1]), "+f"(d[2]), "+f"(d[3]), "+f"(d[4]), "+f"(d[5]), "+f"(d[6]), "+f"(d[7]), "+f"(d[8]), "+f"(d[9]),
          "+f"(d[10]), "+f"(d[11]), "+f"(d[12]), "+f"(d[13]), "+f"(d[14]), "+f"(d[15]), "+f"(d[16]), "+f"(d[17]), "+f"(d[18]), "+f"(d[19])
        : "r"(a[0]), "r"(a[1]), "r"(a[2]), "r"(a[3]), "l"(db), "r"(scale_d));
}
__device__ __forceinline__ void pu_mma(float (&o)[4], const float (&u)[20], const uint32_t (&pb)[5]) {
    float o2[4] = {0, 0, 0, 0};
    o[0] = o[1] = o[2] = o[3] = 0.f;
    mma_bf16(o, pack_bf16(u[0], u[1]), pack_bf16(u[2], u[3]), pack_bf16(u[4], u[5]), pack_bf16(u[6], u[7]), pb[0], pb[1]);
    mma_bf16(o2, pack_bf16(u[8], u[9]), pack_bf16(u[10], u[11]), pack_bf16(u[12], u[13]), pack_bf16(u[14], u[15]), pb[2], pb[3]);
    mma_bf16(o, pack_bf16(u[16], u[17]), pack_bf16(u[18], u[19]), 0u, 0u, pb[4], 0u);
    o[0] += o2[0]; o[1] += o2[1]; o[2] += o2[2]; o[3] += o2[3];
}
__device__ __forceinline__ void pu_store(const float (&o)[4], float2 inv, uint2 off, int lane, uint32_t tg) {
    unsigned char* pool = reinterpret_cast<unsigned char*>(g_pool) + lane * 8;
    st_relaxed2(pool + off.x, (__float_as_uint(o[0] * inv.x) & ~3u) | tg, (__float_as_uint(o[1] * inv.y) & ~3u) | tg);
    st_relaxed2(pool + off.y, (__float_as_uint(o[2] * inv.x) & ~3u) | tg, (__float_as_uint(o[3] * inv.y) & ~3u) | tg);
}
__device__ __forceinline__ float rcp_approx(float x) { float r; asm("rcp.approx.ftz.f32 %0, %1;" : "=f"(r) : "f"(x)); return r; }
template <int NT>
__device__ __forceinline__ void u_pass(unsigned char* smem, uint32_t sb, int s, uint32_t rank, int wg, int warp, int lane) {
    const int sl = s & 1;
#define NRS_V 6
    constexpr int NRS = NRS_V;
    uint32_t wa[NRS][4];
    {
        const int mi = lane >> 3, chunk = 2 * warp + (mi & 1);
        #pragma unroll
        for (int ks = 0; ks < NRS; ks++) {
            const int row = 16 * ks + (mi >> 1) * 8 + (lane & 7);
            ldsm4t(wa[ks], sb + SM_WO + (2 * wg) * 16384 + row * 128 + ((chunk ^ (row & 7)) << 4));
        }
    }
    if (rank < 2) { mbar_wait(sb + B_V + 8 * sl, (s >> 1) & 1); fence_async(); }
    if (wg == 0 && warp == 0) TR(4);
    float U0[20];
    wg_fence();
    #pragma unroll
    for (int ks = 0; ks < NRS; ks++)
        wgmma_n40_rs(U0, wa[ks], make_desc(sb + SM_VT + sl * 10240 + (ks >> 2) * 5120 + (ks & 3) * 32, 16, 1024), ks > 0);
    #pragma unroll
    for (int ks = NRS; ks < 8; ks++)
        wgmma_n40_tA(U0, make_desc(sb + SM_WO + (2 * wg) * 16384 + ks * 2048, 1024, 1024),
                     make_desc(sb + SM_VT + sl * 10240 + (ks >> 2) * 5120 + (ks & 3) * 32, 16, 1024), 1);
    wg_commit();
    const uint32_t tg = tag_of(s);
    uint32_t pb[5];
    float sm[4], sm2[4];
    auto get_p = [&]() {
        nbar_sync(9, 288);
        const uint32_t* pbs = reinterpret_cast<const uint32_t*>(smem + SM_PB);
        #pragma unroll
        for (int q = 0; q < 5; q++) pb[q] = pbs[q * 32 + lane];
        sm[0] = sm[1] = sm[2] = sm[3] = 0.f; sm2[0] = sm2[1] = sm2[2] = sm2[3] = 0.f;
        const uint32_t one = 0x3f803f80u;
        mma_bf16(sm, one, one, one, one, pb[0], pb[1]);
        mma_bf16(sm2, one, one, one, one, pb[2], pb[3]);
        mma_bf16(sm, one, one, 0u, 0u, pb[4], 0u);
    };
    const uint2* tpm = reinterpret_cast<const uint2*>(smem + SM_TPM) + (sl * 4 + 2 * wg) * 4 + warp;
    if (NT == 2) {
        wg_wait0();
        float U1[20];
        wg_fence();
        #pragma unroll
        for (int ks = 0; ks < 8; ks++)
            wgmma_n40_tA(U1, make_desc(sb + SM_WO + (2 * wg + 1) * 16384 + ks * 2048, 1024, 1024),
                         make_desc(sb + SM_VT + sl * 10240 + (ks >> 2) * 5120 + (ks & 3) * 32, 16, 1024), ks > 0);
        wg_commit();
        const uint2 off0 = tpm[0], off1 = tpm[4];
        get_p();
        float o0[4], o1[4];
        pu_mma(o0, U0, pb);
        wg_wait0();
        pu_mma(o1, U1, pb);
        const float2 inv = make_float2(rcp_approx(sm[0] + sm2[0]), rcp_approx(sm[1] + sm2[1]));
        if (wg == 0 && warp == 0) TR(8);
        pu_store(o0, inv, off0, lane, tg);
        pu_store(o1, inv, off1, lane, tg);
        if (wg == 0 && warp == 0) TR(6);
    } else {
        const uint2 off0 = tpm[0];
        wg_wait0();
        get_p();
        float o0[4];
        pu_mma(o0, U0, pb);
        const float2 inv = make_float2(rcp_approx(sm[0] + sm2[0]), rcp_approx(sm[1] + sm2[1]));
        pu_store(o0, inv, off0, lane, tg);
    }
}

__global__ void __cluster_dims__(3, 1, 1) __launch_bounds__(384, 1)
k_chain(const __grid_constant__ CUtensorMap xmap, const __grid_constant__ CUtensorMap wqmap, const __grid_constant__ CUtensorMap wkmap,
        const __grid_constant__ CUtensorMap wvmap, const __grid_constant__ CUtensorMap womap, const bf16* __restrict__ xptr, const bf16* __restrict__ mem0) {
    extern __shared__ __align__(1024) unsigned char smem[];
    const uint32_t sb = smem_u32(smem);
    const int tid = threadIdx.x, lane = tid & 31;
    const int wg = __shfl_sync(~0u, tid >> 7, 0), warp = __shfl_sync(~0u, (tid >> 5) & 3, 0);
    uint32_t rank; asm volatile("mov.u32 %0, %%cluster_ctarank;" : "=r"(rank));
    const int cta = blockIdx.x, h = cta / 3;
    asm volatile("griddepcontrol.launch_dependents;");
    if (tid == 0) {
        for (int i = 0; i < 2; i++) { mbar_init(sb + B_SC + 8 * i, rank < 2 ? 6 : 1); mbar_init(sb + B_V + 8 * i, 1); mbar_init(sb + B_X + 8 * i, 1); }
        mbar_init(sb + B_P, 1); mbar_init(sb + B_EXP, 1);
        asm volatile("fence.mbarrier_init.release.cluster;" ::: "memory");
    }
    if (tid < 80) asm volatile("prefetch.global.L2 [%0];" :: "l"(mem0 + tid * 64));
    if (h < 2) { for (int i = tid; i < 320; i += 384) asm volatile("prefetch.global.L2 [%0];" :: "l"(xptr + (size_t)h * 32 * DM + i * 64)); }
    {
        const int w12 = tid >> 5;
        if (lane == 0 && w12 < 7) {
            uint32_t* pp = (w12 < 6) ? g_pool + (size_t)(cta * 6 + w12) * 1024 + 512 : g_pool + (size_t)NPOOL * 1024 + (cta & 31) * 32 + (cta >> 5) * 8;
            const unsigned lat = probe_latency(pp, blockIdx.y);
            if (w12 < 6) g_cls[cta * 6 + w12] = lat > CAL_THR ? 1u : 0u; else g_side[cta] = lat > CAL_THR ? 1u : 0u;
        }
        __syncwarp();
        uint4* z = reinterpret_cast<uint4*>(g_pool + (size_t)cta * 6 * 1024);
        #pragma unroll
        for (int q = 0; q < 4; q++) z[tid + 384 * q] = make_uint4(0, 0, 0, 0);
        __threadfence();
        __syncwarp();
        if (lane == 0) atomicAdd(&g_calcnt, 1u);
    }
    __syncthreads();
    if (tid == 0) {
        const int ntile = (rank == 2) ? 4 : 3;
        const int tile0 = (rank == 2) ? 0 : (rank == 0 ? 4 : 7);
        mbar_expect_tx(sb + B_P, 163840 + ntile * 16384);
        const void* m0 = (rank == 2) ? &wvmap : &wqmap;
        const void* m1 = (rank == 2) ? &wvmap : &wkmap;
        const int c0 = h * DH + (rank == 1 ? 64 : 0), c1 = h * DH + (rank == 0 ? 0 : 64);
        for (int b = 0; b < 5; b++) {
            tma_load_2d(sb + b * 16384, m0, c0, b * 128, sb + B_P);
            tma_load_2d(sb + 81920 + b * 16384, m1, c1, b * 128, sb + B_P);
        }
        for (int lt = 0; lt < ntile; lt++) {
            tma_load_2d(sb + SM_WO + lt * 16384, &womap, (tile0 + lt) * 64, h * DH, sb + B_P);
            tma_load_2d(sb + SM_WO + lt * 16384 + 8192, &womap, (tile0 + lt) * 64, h * DH + 64, sb + B_P);
        }
    }
    {
        const int tile0 = (rank == 2) ? 0 : (rank == 0 ? 4 : 7);
        if (wg == 2) {
            const int ct = tid & 127;
            if (ct == 0) {
                const unsigned target = (*reinterpret_cast<volatile unsigned*>(&g_epoch) + 1u) * (96u * 12u);
                int guard = 0;
                while ((int)(ld_acquire(&g_calcnt) - target) < 0 && ++guard < (1 << 22)) {}
            }
            nbar_sync(4, 128);
            uint32_t* bm = reinterpret_cast<uint32_t*>(smem + SM_CAL);
            {
                unsigned v[5];
                #pragma unroll
                for (int q = 0; q < 5; q++) { const int b = ct + 128 * q; v[q] = (b < NPOOL) ? (__ldcg(&g_cls[b]) ^ __ldcg(&g_side[b / 6])) : 0u; }
                const unsigned sv = (ct < 96) ? __ldcg(&g_side[ct]) : 0u;
                #pragma unroll
                for (int q = 0; q < 5; q++) { const unsigned m = __ballot_sync(~0u, v[q] & 1u); if (lane == 0 && q * 4 + warp < 18) bm[q * 4 + warp] = m; }
                const unsigned m = __ballot_sync(~0u, sv & 1u);
                if (lane == 0 && warp < 3) bm[18 + warp] = m;
            }
            nbar_sync(4, 128);
            int nblk1 = 0;
            for (int i = 0; i < 18; i++) nblk1 += __popc(bm[i]);
            const unsigned red_last = (1u << (NRED - 64)) - 1u;
            const int nred1 = __popc(bm[18]) + __popc(bm[19]) + __popc(bm[20] & red_last);
            auto side_of = [&](int c) -> int { return (bm[18 + (c >> 5)] >> (c & 31)) & 1; };
            auto rank_of = [&](int c) -> int {
                int ones = 0;
                for (int i = 0; i < (c >> 5); i++) ones += __popc(bm[18 + i]);
                ones += __popc(bm[18 + (c >> 5)] & ((1u << (c & 31)) - 1u));
                return side_of(c) ? ones : c - ones;
            };
            auto nth = [&](int side, int idx) -> uint32_t {
                for (int i = 0; i < 18; i++) {
                    const unsigned m = side ? bm[i] : ~bm[i];
                    const int n = __popc(m);
                    if (idx < n) return (uint32_t)(i * 32 + __fns(m, 0, idx + 1));
                    idx -= n;
                }
                return 0u;
            };
            auto phys = [&](int side, int idx) -> uint32_t {
                const int c = side ? nblk1 : NPOOL - nblk1;
                return (idx < c) ? nth(side, idx) : nth(side ^ 1, (NPOOL - c) - 1 - (idx - c));
            };
            const int e = ct;
            if (e < 64) {
                const int slot = e >> 5, lt = (e >> 3) & 3, w = (e >> 1) & 3, hf = e & 1;
                const int tile = min(tile0 + lt, 9);
                const int r = 2 * (4 * tile + w) + hf;
                reinterpret_cast<uint32_t*>(smem + SM_TPM)[e] = phys(side_of(r), 4 * rank_of(r) + slot * 2 + (h >> 4)) * 4096u + (h & 15) * 256u;
            } else if (e < 68) {
                const int i = e - 64;
                reinterpret_cast<uint32_t*>(smem + SM_TRD)[i] = (cta < NRED) ? phys(side_of(cta), 4 * rank_of(cta) + i) * 4096u : 0u;
            } else if (e < 100) {
                const int i = e - 68, slot = i >> 3, rep = i & 7, side = (rep / RPS) & 1;
                reinterpret_cast<uint32_t*>(smem + SM_TPUB)[i] = phys(side, 4 * (side ? nred1 : NRED - nred1) + (slot * RPS + (rep % RPS)) * 3 + (cta >> 5)) * 4096u + (cta & 31) * 128u;
            } else if (e < 112) {
                const int i = e - 100, slot = i / 3, b = i % 3, side = side_of(cta);
                reinterpret_cast<uint32_t*>(smem + SM_TGAT)[slot * 4 + b] = phys(side, 4 * (side ? nred1 : NRED - nred1) + (slot * RPS + (h % RPS)) * 3 + b) * 4096u;
            }
        }
    }
    __syncthreads();
    mbar_wait_sleep(sb + B_P, 0);

    if (wg == 2) {
        asm volatile("setmaxnreg.dec.sync.aligned.u32 " COMM_REGS ";");
        const int ct = tid & 127;
        nbar_sync(5, 384);
        for (int c = ct; c < 640; c += 128) {
            int ks = c >> 4, hf = (c >> 3) & 1, r = c & 7;
            *reinterpret_cast<uint4*>(smem + SM_MEMB + c * 16) = *reinterpret_cast<const uint4*>(mem0 + r * DM + ks * 16 + hf * 8);
        }
        if (ct == 0) {
            for (int sg = 0; sg < 2; sg++) {
                mbar_expect_tx(sb + B_X + 8 * sg, 40960);
                tma_load_3d(sb + SM_XB + sg * 40960, &xmap, 0, sg * 32, 0, sb + B_X + 8 * sg);
            }
            mbar_expect_tx(sb + B_SC, rank < 2 ? 1280 : 2560);
            if (rank < 2) mbar_expect_tx(sb + B_V, 8192 + 2048);
        }
        nbar_sync(5, 384);
        cluster_sync_all();
        unsigned char* const pool = reinterpret_cast<unsigned char*>(g_pool);
        for (int s = 0; s < NSEG - 1; s++) {
            if (warp == 1) nbar_sync(12, 288);
            if (warp == 0) {
                const int g = lane >> 2, t = lane & 3;
                mbar_wait(sb + B_SC + 8 * (s & 1), (s >> 1) & 1);
                TR(5);
                const uint32_t sa = sb + SM_SC + (s & 1) * 2560 + (g * 40 + 2 * t) * 4;
                float v[5][2], u[5][2];
                #pragma unroll
                for (int q = 0; q < 5; q++) {
                    asm volatile("ld.shared.v2.f32 {%0,%1}, [%2];" : "=f"(v[q][0]), "=f"(v[q][1]) : "r"(sa + 32 * q) : "memory");
                    asm volatile("ld.shared.v2.f32 {%0,%1}, [%2];" : "=f"(u[q][0]), "=f"(u[q][1]) : "r"(sa + 1280 + 32 * q) : "memory");
                }
                float mx = -3.0e38f;
                #pragma unroll
                for (int q = 0; q < 5; q++) {
                    v[q][0] += u[q][0]; v[q][1] += u[q][1];
                    mx = fmaxf(mx, fmaxf(v[q][0], v[q][1]));
                }
                mx = fmaxf(mx, __shfl_xor_sync(~0u, mx, 1));
                mx = fmaxf(mx, __shfl_xor_sync(~0u, mx, 2));
                const float sc2 = 0.08838834764831845f * 1.4426950408889634f;
                const float mxs = mx * sc2;
                uint32_t* pbs = reinterpret_cast<uint32_t*>(smem + SM_PB);
                #pragma unroll
                for (int q = 0; q < 5; q++) {
                    const float e0 = ex2_approx(fmaf(v[q][0], sc2, -mxs)), e1 = ex2_approx(fmaf(v[q][1], sc2, -mxs));
                    pbs[q * 32 + lane] = pack_bf16(e0, e1);
                }
                __syncwarp();
                TR(0);
                nbar_arrive(9, 288);
            } else if (warp == 1 && lane == 0) {
                if (s + 1 < NSEG - 1) {
                    mbar_expect_tx(sb + B_SC + 8 * ((s + 1) & 1), rank < 2 ? 1280 : 2560);
                    if (rank < 2) mbar_expect_tx(sb + B_V + 8 * ((s + 1) & 1), 8192 + 2048);
                }
                if (s + 2 < NSEG) {
                    mbar_expect_tx(sb + B_X + 8 * (s & 1), 40960);
                    tma_load_3d(sb + SM_XB + (s & 1) * 40960, &xmap, 0, (s + 2) * 32, 0, sb + B_X + 8 * (s & 1));
                }
                export_issue(sb, s, h, rank);
                if (s >= NSEG - 4) export_signal(s, h);
            }
            __syncwarp();
            nbar_sync(3, 384);
            const uint32_t tg = tag_of(s);
            if (cta < NRED) {
                const unsigned char* base = pool + reinterpret_cast<const uint32_t*>(smem + SM_TRD)[(s & 1) * 2 + (warp >> 1)] + (warp & 1) * 2048 + lane * 16;
                uint4 v[4]; int guard = 0;
                #pragma unroll
                for (int j = 0; j < 4; j++) v[j] = make_uint4(0, 0, 0, 0);
                uint32_t pend = 0xF;
                do {
                    #pragma unroll
                    for (int j = 0; j < 4; j++) if (pend & (1u << j)) v[j] = ld_relaxed4(base + j * 512);
                    #pragma unroll
                    for (int j = 0; j < 4; j++)
                        if (((v[j].x & 3) == tg) && ((v[j].y & 3) == tg) && ((v[j].z & 3) == tg) && ((v[j].w & 3) == tg)) pend &= ~(1u << j);
                } while (__any_sync(~0u, pend != 0) && ++guard < (1 << 20));
                if (warp == 0) TR(9);
                float a0 = 0, a1 = 0, a2 = 0, a3 = 0;
                #pragma unroll
                for (int j = 0; j < 4; j++) { a0 += __uint_as_float(v[j].x); a1 += __uint_as_float(v[j].y); a2 += __uint_as_float(v[j].z); a3 += __uint_as_float(v[j].w); }
                a0 += __shfl_xor_sync(~0u, a0, 16); a1 += __shfl_xor_sync(~0u, a1, 16); a2 += __shfl_xor_sync(~0u, a2, 16); a3 += __shfl_xor_sync(~0u, a3, 16);
                float* cr = reinterpret_cast<float*>(smem + SM_CRED);
                if (lane < 16) *reinterpret_cast<float4*>(cr + warp * 64 + lane * 4) = make_float4(a0, a1, a2, a3);
                nbar_sync(4, 128);
                {
                    int rho = lane >> 2, pp = lane & 3;
                    int i0 = ((2 * pp) * 4 + (rho >> 1)) * 2 + (rho & 1), i1 = i0 + 8;
                    uint32_t wv = pack_bf16((cr[i0] + cr[64 + i0]) + (cr[128 + i0] + cr[192 + i0]), (cr[i1] + cr[64 + i1]) + (cr[128 + i1] + cr[192 + i1]));
                    if (wv == 0) wv = 0x8000u;
                    if (warp == 0) TR(10);
                    const uint32_t* tp = reinterpret_cast<const uint32_t*>(smem + SM_TPUB) + warp;
                    if (warp < 2 * RPS) st_relaxed1(pool + tp[((s + 1) & 3) * 8] + lane * 4, wv);
                    if (RPS == 4) st_relaxed1(pool + tp[((s + 1) & 3) * 8 + 4] + lane * 4, wv);
                    if (warp < 2 * RPS) st_relaxed1(pool + tp[(s & 3) * 8] + lane * 4, 0u);
                    if (RPS == 4) st_relaxed1(pool + tp[(s & 3) * 8 + 4] + lane * 4, 0u);
                }
            }
            {
                const int c0 = warp * 160 + lane;
                const uint32_t* tg3 = reinterpret_cast<const uint32_t*>(smem + SM_TGAT) + ((s + 1) & 3) * 4;
                const uint32_t g0 = tg3[0], g1 = tg3[1], g2 = tg3[2];
                uint4 v[5]; int guard = 0;
                #pragma unroll
                for (int j = 0; j < 5; j++) v[j] = make_uint4(0, 0, 0, 0);
                uint32_t pend = 0x1F;
                do {
                    #pragma unroll
                    for (int j = 0; j < 5; j++) {
                        const int c = c0 + 32 * j;
                        if (pend & (1u << j)) v[j] = ld_relaxed4(pool + ((c >> 8) == 0 ? g0 : ((c >> 8) == 1 ? g1 : g2)) + (c & 255) * 16);
                    }
                    #pragma unroll
                    for (int j = 0; j < 5; j++) if (v[j].x && v[j].y && v[j].z && v[j].w) pend &= ~(1u << j);
                } while (__any_sync(~0u, pend != 0) && ++guard < (1 << 20));
                #pragma unroll
                for (int j = 0; j < 5; j++) *reinterpret_cast<uint4*>(smem + SM_MEMB + (c0 + 32 * j) * 16) = v[j];
                if (warp == 0) TR(11);
                if (warp == 3) TR(12);
                nbar_arrive(warp < 2 ? 7 + warp : 8 + warp, 160);
            }
            if (warp == 1 && lane == 0 && s < NSEG - 4) export_signal(s, h);
            __syncwarp();
        }
        if (warp == 1) { nbar_sync(12, 288); if (lane == 0) { export_issue(sb, NSEG - 1, h, rank); export_signal(NSEG - 1, h); } }
        __syncwarp();
        nbar_sync(3, 384);
        __syncwarp();
        cluster_sync_all();
    } else {
        asm volatile("setmaxnreg.inc.sync.aligned.u32 232;");
        const int wtid = tid & 127;
        const int cw = wg * 4 + warp;
        uint32_t areg[2][20][4];
        #pragma unroll
        for (int mt = 0; mt < 2; mt++)
            #pragma unroll
            for (int kk = 0; kk < 20; kk++) {
                int mi = lane >> 3;
                int row = 16 * (20 * wg + kk) + (mi >> 1) * 8 + (lane & 7);
                int chunk = 2 * warp + (mi & 1);
                ldsm4t(areg[mt][kk], sb + mt * 81920 + row * 128 + ((chunk ^ (row & 7)) << 4));
            }
        nbar_sync(5, 384);
        nbar_sync(5, 384);
        cluster_sync_all();

        for (int s = -1; s < NSEG; s++) {
            const int sl = s & 1;
            if (s >= 0) {
            if (s > 0) nbar_sync(7 + 3 * wg, 160);
            float fin[4];
            {
                float acc[2][2][4];
                #pragma unroll
                for (int i = 0; i < 2; i++)
                    #pragma unroll
                    for (int j = 0; j < 2; j++) { acc[i][j][0] = acc[i][j][1] = acc[i][j][2] = acc[i][j][3] = 0.f; }
                uint32_t b[3][4];
                const uint32_t mb = sb + SM_MEMB + (20 * wg) * 256 + lane * 16;
                ldsm4(b[0], mb); ldsm4(b[1], mb + 512);
                #pragma unroll
                for (int kp = 0; kp < 10; kp++) {
                    if (kp == 3 && s > 0) nbar_sync(8 + 3 * wg, 160);
                    if (kp + 2 < 10) ldsm4(b[(kp + 2) % 3], mb + (kp + 2) * 512);
                    const uint32_t (&bb)[4] = b[kp % 3];
                    mma_bf16(acc[0][0], areg[0][2 * kp][0], areg[0][2 * kp][1], areg[0][2 * kp][2], areg[0][2 * kp][3], bb[0], bb[1]);
                    mma_bf16(acc[1][0], areg[1][2 * kp][0], areg[1][2 * kp][1], areg[1][2 * kp][2], areg[1][2 * kp][3], bb[0], bb[1]);
                    mma_bf16(acc[0][1], areg[0][2 * kp + 1][0], areg[0][2 * kp + 1][1], areg[0][2 * kp + 1][2], areg[0][2 * kp + 1][3], bb[2], bb[3]);
                    mma_bf16(acc[1][1], areg[1][2 * kp + 1][0], areg[1][2 * kp + 1][1], areg[1][2 * kp + 1][2], areg[1][2 * kp + 1][3], bb[2], bb[3]);
                }
                float4* red = reinterpret_cast<float4*>(smem + SM_RED);
                float m0[4], m1[4];
                #pragma unroll
                for (int i = 0; i < 4; i++) { m0[i] = acc[0][0][i] + acc[0][1][i]; m1[i] = acc[1][0][i] + acc[1][1][i]; }
                red[(wg ^ 1) * 128 + wtid] = wg == 0 ? make_float4(m1[0], m1[1], m1[2], m1[3]) : make_float4(m0[0], m0[1], m0[2], m0[3]);
                nbar_sync(1, 256);
                float4 r = red[wg * 128 + wtid];
                fin[0] = (wg == 0 ? m0[0] : m1[0]) + r.x; fin[1] = (wg == 0 ? m0[1] : m1[1]) + r.y;
                fin[2] = (wg == 0 ? m0[2] : m1[2]) + r.z; fin[3] = (wg == 0 ? m0[3] : m1[3]) + r.w;
            }
            if (cw == 0) TR(1);
            {
                uint32_t p0 = pack_bf16(fin[0], fin[1]), p1 = pack_bf16(fin[2], fin[3]);
                const uint32_t doff = (rank == 2) ? SM_VT + sl * 10240 + wg * 5120 : (wg == 0 ? SM_QS : SM_KT + sl * 5120);
                const int r = lane & 7, chunk = 2 * warp + ((lane >> 3) & 1);
                const uint32_t coff = doff + r * 128 + ((chunk ^ r) << 4);
                stsm2t(sb + coff, p0, p1);
                if (rank == 2 && s < NSEG - 1) {
                    __syncwarp();
                    const uint4 v = *reinterpret_cast<const uint4*>(smem + coff);
                    const uint32_t rb = mapa(sb, lane >> 4);
                    st_async4u(rb + coff, v, rb + B_V + 8 * sl);
                }
            }
            fence_async();
            nbar_sync(1, 256);
            nbar_arrive(12, 288);
            if (cw == 0) TR(2);
            if (rank < 2 && s < NSEG - 1) {
                if (wg == 1) score_tile(sb, sl, 1 + warp, lane, rank);
                else if (warp == 0) score_tile(sb, sl, 0, lane, rank);
            }
            if (s == NSEG - 1) break;
            if (cw == 0) TR(3);
            if (wg == 0 || rank == 2) u_pass<2>(smem, sb, s, rank, wg, warp, lane);
            else                      u_pass<1>(smem, sb, s, rank, wg, warp, lane);
            if (cw == 0) TR(7);
            nbar_arrive(3, 384);
            }
            {
                const int sn = s + 1, sln = sn & 1;
                mbar_wait(sb + B_X + 8 * sln, (sn >> 1) & 1);
                float acc[2][16];
                wg_fence();
                #pragma unroll
                for (int mt = 0; mt < 2; mt++)
                    #pragma unroll
                    for (int kk = 0; kk < 20; kk++) {
                        uint64_t db = make_desc(sb + SM_XB + sln * 40960 + (5 * wg + (kk >> 2)) * 4096 + (kk & 3) * 32, 16, 1024);
                        wgmma_n32_rs(acc[mt], areg[mt][kk], db, kk > 0);
                    }
                wg_commit();
                if (cw == 0 && s >= 0) TR(14);
                wg_wait0();
                if (cw == 0 && s >= 0) TR(15);
                float4* red = reinterpret_cast<float4*>(smem + SM_RED);
                #pragma unroll
                for (int j = 0; j < 4; j++) {
                    red[((wg ^ 1) * 4 + j) * 128 + wtid] = make_float4(wg == 0 ? acc[1][4 * j] : acc[0][4 * j], wg == 0 ? acc[1][4 * j + 1] : acc[0][4 * j + 1],
                                                                       wg == 0 ? acc[1][4 * j + 2] : acc[0][4 * j + 2], wg == 0 ? acc[1][4 * j + 3] : acc[0][4 * j + 3]);
                }
                if (s >= 0) mbar_wait(sb + B_EXP, s & 1);
                nbar_sync(1, 256);
                uint32_t pk[8];
                #pragma unroll
                for (int j = 0; j < 4; j++) {
                    float4 r = red[(wg * 4 + j) * 128 + wtid];
                    pk[2 * j] = pack_bf16((wg == 0 ? acc[0][4 * j] : acc[1][4 * j]) + r.x, (wg == 0 ? acc[0][4 * j + 1] : acc[1][4 * j + 1]) + r.y);
                    pk[2 * j + 1] = pack_bf16((wg == 0 ? acc[0][4 * j + 2] : acc[1][4 * j + 2]) + r.z, (wg == 0 ? acc[0][4 * j + 3] : acc[1][4 * j + 3]) + r.w);
                }
                const uint32_t dst = (rank == 2) ? sb + SM_VT + sln * 10240 + wg * 5120 + 1024 : (wg == 0 ? sb + SM_QT : sb + SM_KT + sln * 5120 + 1024);
                #pragma unroll
                for (int jj = 0; jj < 2; jj++) {
                    int mi = lane >> 3, tok = 8 * (2 * jj + (mi >> 1)) + (lane & 7), chunk = 2 * warp + (mi & 1);
                    stsm4t(dst + tok * 128 + ((chunk ^ (tok & 7)) << 4), pk[4 * jj], pk[4 * jj + 1], pk[4 * jj + 2], pk[4 * jj + 3]);
                }
                fence_async();
                nbar_sync(1, 256);
                if (rank == 2 && lane == 0 && cw < 4 && sn < NSEG - 1) {
                    const uint32_t off = SM_VT + sln * 10240 + (cw & 1) * 5120 + 1024;
                    const uint32_t rb = mapa(sb, cw >> 1);
                    bulk_s2c(rb + off, sb + off, 4096, rb + B_V + 8 * sln);
                }
                if (cw == 0 && s >= 0) TR(13);
            }
        }
        nbar_arrive(3, 384);
        __syncwarp();
        cluster_sync_all();
    }
}

#define NAUX 36
__device__ __align__(1024) bf16 g_Oimg[16 * 64 * 128 * 64];
__device__ float    g_part[4 * SEQ * DM];
__device__ float    g_part31[3 * 16 * 64 * DM];
__device__ unsigned g_ocnt[32];
__device__ unsigned g_gcnt[32][2];
__device__ unsigned g_ssmcnt, g_auxdone, g_taskctr, g_gemmctr;
#define NATT 8
#define ATR(i) do {} while (0)
#define ATRID(i, id) do {} while (0)

__device__ __forceinline__ void wait_counter(const unsigned* p, unsigned target) {
    int guard = 0;
    while ((int)(ld_acquire(p) - target) < 0 && ++guard < (1 << 22)) __nanosleep(64);
}
__device__ __forceinline__ void fence_async_all() { asm volatile("fence.proxy.async;" ::: "memory"); }
template <int OFF>
__device__ __forceinline__ void wgmma_n192_tB(float (&d)[160], uint64_t da, uint64_t db) {
    asm volatile("wgmma.mma_async.sync.aligned.m64n192k16.f32.bf16.bf16 {%0,%1,%2,%3,%4,%5,%6,%7,%8,%9,%10,%11,%12,%13,%14,%15,%16,%17,%18,%19,%20,%21,%22,%23,%24,%25,%26,%27,%28,%29,%30,%31,%32,%33,%34,%35,%36,%37,%38,%39,%40,%41,%42,%43,%44,%45,%46,%47,%48,%49,%50,%51,%52,%53,%54,%55,%56,%57,%58,%59,%60,%61,%62,%63,%64,%65,%66,%67,%68,%69,%70,%71,%72,%73,%74,%75,%76,%77,%78,%79,%80,%81,%82,%83,%84,%85,%86,%87,%88,%89,%90,%91,%92,%93,%94,%95}, %96, %97, 1, 1, 1, 0, 1;\n"
        : "+f"(d[OFF + 0]), "+f"(d[OFF + 1]), "+f"(d[OFF + 2]), "+f"(d[OFF + 3]), "+f"(d[OFF + 4]), "+f"(d[OFF + 5]), "+f"(d[OFF + 6]), "+f"(d[OFF + 7]), "+f"(d[OFF + 8]), "+f"(d[OFF + 9]), "+f"(d[OFF + 10]), "+f"(d[OFF + 11]), "+f"(d[OFF + 12]), "+f"(d[OFF + 13]), "+f"(d[OFF + 14]), "+f"(d[OFF + 15]), "+f"(d[OFF + 16]), "+f"(d[OFF + 17]), "+f"(d[OFF + 18]), "+f"(d[OFF + 19]), "+f"(d[OFF + 20]), "+f"(d[OFF + 21]), "+f"(d[OFF + 22]), "+f"(d[OFF + 23]), "+f"(d[OFF + 24]), "+f"(d[OFF + 25]), "+f"(d[OFF + 26]), "+f"(d[OFF + 27]), "+f"(d[OFF + 28]), "+f"(d[OFF + 29]), "+f"(d[OFF + 30]), "+f"(d[OFF + 31]), "+f"(d[OFF + 32]), "+f"(d[OFF + 33]), "+f"(d[OFF + 34]), "+f"(d[OFF + 35]), "+f"(d[OFF + 36]), "+f"(d[OFF + 37]), "+f"(d[OFF + 38]), "+f"(d[OFF + 39]), "+f"(d[OFF + 40]), "+f"(d[OFF + 41]), "+f"(d[OFF + 42]), "+f"(d[OFF + 43]), "+f"(d[OFF + 44]), "+f"(d[OFF + 45]), "+f"(d[OFF + 46]), "+f"(d[OFF + 47]), "+f"(d[OFF + 48]), "+f"(d[OFF + 49]), "+f"(d[OFF + 50]), "+f"(d[OFF + 51]), "+f"(d[OFF + 52]), "+f"(d[OFF + 53]), "+f"(d[OFF + 54]), "+f"(d[OFF + 55]), "+f"(d[OFF + 56]), "+f"(d[OFF + 57]), "+f"(d[OFF + 58]), "+f"(d[OFF + 59]), "+f"(d[OFF + 60]), "+f"(d[OFF + 61]), "+f"(d[OFF + 62]), "+f"(d[OFF + 63]), "+f"(d[OFF + 64]), "+f"(d[OFF + 65]), "+f"(d[OFF + 66]), "+f"(d[OFF + 67]), "+f"(d[OFF + 68]), "+f"(d[OFF + 69]), "+f"(d[OFF + 70]), "+f"(d[OFF + 71]), "+f"(d[OFF + 72]), "+f"(d[OFF + 73]), "+f"(d[OFF + 74]), "+f"(d[OFF + 75]), "+f"(d[OFF + 76]), "+f"(d[OFF + 77]), "+f"(d[OFF + 78]), "+f"(d[OFF + 79]), "+f"(d[OFF + 80]), "+f"(d[OFF + 81]), "+f"(d[OFF + 82]), "+f"(d[OFF + 83]), "+f"(d[OFF + 84]), "+f"(d[OFF + 85]), "+f"(d[OFF + 86]), "+f"(d[OFF + 87]), "+f"(d[OFF + 88]), "+f"(d[OFF + 89]), "+f"(d[OFF + 90]), "+f"(d[OFF + 91]), "+f"(d[OFF + 92]), "+f"(d[OFF + 93]), "+f"(d[OFF + 94]), "+f"(d[OFF + 95])
        : "l"(da), "l"(db));
}
template <int OFF>
__device__ __forceinline__ void wgmma_n128_tB(float (&d)[160], uint64_t da, uint64_t db) {
    asm volatile("wgmma.mma_async.sync.aligned.m64n128k16.f32.bf16.bf16 {%0,%1,%2,%3,%4,%5,%6,%7,%8,%9,%10,%11,%12,%13,%14,%15,%16,%17,%18,%19,%20,%21,%22,%23,%24,%25,%26,%27,%28,%29,%30,%31,%32,%33,%34,%35,%36,%37,%38,%39,%40,%41,%42,%43,%44,%45,%46,%47,%48,%49,%50,%51,%52,%53,%54,%55,%56,%57,%58,%59,%60,%61,%62,%63}, %64, %65, 1, 1, 1, 0, 1;\n"
        : "+f"(d[OFF + 0]), "+f"(d[OFF + 1]), "+f"(d[OFF + 2]), "+f"(d[OFF + 3]), "+f"(d[OFF + 4]), "+f"(d[OFF + 5]), "+f"(d[OFF + 6]), "+f"(d[OFF + 7]), "+f"(d[OFF + 8]), "+f"(d[OFF + 9]), "+f"(d[OFF + 10]), "+f"(d[OFF + 11]), "+f"(d[OFF + 12]), "+f"(d[OFF + 13]), "+f"(d[OFF + 14]), "+f"(d[OFF + 15]), "+f"(d[OFF + 16]), "+f"(d[OFF + 17]), "+f"(d[OFF + 18]), "+f"(d[OFF + 19]), "+f"(d[OFF + 20]), "+f"(d[OFF + 21]), "+f"(d[OFF + 22]), "+f"(d[OFF + 23]), "+f"(d[OFF + 24]), "+f"(d[OFF + 25]), "+f"(d[OFF + 26]), "+f"(d[OFF + 27]), "+f"(d[OFF + 28]), "+f"(d[OFF + 29]), "+f"(d[OFF + 30]), "+f"(d[OFF + 31]), "+f"(d[OFF + 32]), "+f"(d[OFF + 33]), "+f"(d[OFF + 34]), "+f"(d[OFF + 35]), "+f"(d[OFF + 36]), "+f"(d[OFF + 37]), "+f"(d[OFF + 38]), "+f"(d[OFF + 39]), "+f"(d[OFF + 40]), "+f"(d[OFF + 41]), "+f"(d[OFF + 42]), "+f"(d[OFF + 43]), "+f"(d[OFF + 44]), "+f"(d[OFF + 45]), "+f"(d[OFF + 46]), "+f"(d[OFF + 47]), "+f"(d[OFF + 48]), "+f"(d[OFF + 49]), "+f"(d[OFF + 50]), "+f"(d[OFF + 51]), "+f"(d[OFF + 52]), "+f"(d[OFF + 53]), "+f"(d[OFF + 54]), "+f"(d[OFF + 55]), "+f"(d[OFF + 56]), "+f"(d[OFF + 57]), "+f"(d[OFF + 58]), "+f"(d[OFF + 59]), "+f"(d[OFF + 60]), "+f"(d[OFF + 61]), "+f"(d[OFF + 62]), "+f"(d[OFF + 63])
        : "l"(da), "l"(db));
}
__device__ __forceinline__ void stsm4(uint32_t addr, uint32_t r0, uint32_t r1, uint32_t r2, uint32_t r3) {
    asm volatile("stmatrix.sync.aligned.m8n8.x4.shared.b16 [%0], {%1,%2,%3,%4};" :: "r"(addr), "r"(r0), "r"(r1), "r"(r2), "r"(r3) : "memory");
}

#define AX_BAR   0
#define NST_G 4
#define AX_EMPTY (AX_BAR + 16 + 8 * NST_G)
#define AX_DATA  1024
#define AX_UNIT  28672
#define AX_STAGE 57344
#define AX_TOTAL (AX_DATA + 8 * AX_UNIT)

__device__ __forceinline__ void attn_compute(unsigned char* smem, uint32_t sb, uint32_t buf, int warp, int lane);
__device__ __forceinline__ void attn_producer(unsigned char* smem, int hg, unsigned epoch) {
    const uint32_t sb = smem_u32(smem);
    const int lane = threadIdx.x & 31;
    {
        for (int s = 0; s < NSEG; s++) {
            const uint32_t buf = AX_DATA + (s & 1) * (4 * AX_UNIT), bar = sb + AX_BAR + 8 * (s & 1);
            if (lane < 4) wait_counter(&g_flag[s][4 * hg + lane], (epoch + 1) * 3u);
            if (lane == 4) mbar_wait_sleep(sb + AX_EMPTY + 8 * (s & 1), ((s >> 1) & 1) ^ 1);
            __syncwarp();
            if (lane == 0) mbar_expect_tx(bar, 4 * AX_UNIT);
            __syncwarp();
            if (lane < 24) {
                fence_async_all();
                const int u = lane / 6, r = lane % 6, hf = r & 1, kind = r >> 1;
                const uint32_t ub = sb + buf + u * AX_UNIT;
                const size_t img = ((size_t)(s * NH + 4 * hg + u) * 2) + hf;
                if (kind == 0) bulk_g2s(ub + hf * 4096, g_Qimg + img * 2048, 4096, bar);
                else if (kind == 1) bulk_g2s(ub + 8192 + hf * 5120, g_Kimg + img * 2560, 5120, bar);
                else bulk_g2s(ub + 18432 + hf * 5120, g_Vimg + img * 2560, 5120, bar);
            }
            __syncwarp();
        }
    }
}
__device__ __forceinline__ void attn_loop(unsigned char* smem, int hg, unsigned epoch) {
    const uint32_t sb = smem_u32(smem);
    const int tid = threadIdx.x, warp = tid >> 5, lane = tid & 31;
    for (int s = 0; s < NSEG; s++) {
        const uint32_t buf = AX_DATA + (s & 1) * (4 * AX_UNIT), bar = sb + AX_BAR + 8 * (s & 1);
        mbar_wait_sleep(bar, (s >> 1) & 1);
        if (s >= 36) ATR(2 + 2 * (s - 36));
        attn_compute(smem, sb, buf, warp, lane);
        if (s >= 36) ATR(3 + 2 * (s - 36));
        fence_async();
        __syncwarp();
        if (lane == 0) mbar_arrive(sb + AX_EMPTY + 16 + 8 * (s & 1));
    }
}
__device__ __forceinline__ void attn_storer(unsigned char* smem, int hg) {
    const uint32_t sb = smem_u32(smem);
    const int lane = threadIdx.x & 31;
    for (int s = 0; s < NSEG; s++) {
        const uint32_t buf = AX_DATA + (s & 1) * (4 * AX_UNIT);
        mbar_wait_sleep(sb + AX_EMPTY + 16 + 8 * (s & 1), (s >> 1) & 1);
        if (lane < 8) {
            const int uu = lane >> 1, hf = lane & 1, hh = 4 * hg + uu;
            bulk_s2g(g_Oimg + (((size_t)(s >> 2) * 64 + hh * 2 + hf) * 128 + (s & 3) * 32) * 64, sb + buf + uu * AX_UNIT + hf * 4096, 4096);
            bulk_commit();
            bulk_wait_read0();
            mbar_arrive(sb + AX_EMPTY + 8 * (s & 1));
            bulk_wait0();
            fence_async_all();
            __threadfence();
            atomicAdd(&g_ocnt[s >> 1], 1u);
        }
        __syncwarp();
    }
}
__device__ __forceinline__ void attn_compute(unsigned char* smem, uint32_t sb, uint32_t buf, int warp, int lane) {
    const int g = lane >> 2, t = lane & 3;
    const int u = warp >> 1, qh = warp & 1;
    const uint32_t ub = sb + buf + u * AX_UNIT;
    float sc[5][4];
    #pragma unroll
    for (int j = 0; j < 5; j++) { sc[j][0] = sc[j][1] = sc[j][2] = sc[j][3] = 0.f; }
    #pragma unroll
    for (int ks = 0; ks < 8; ks++) {
        const int hf = ks >> 2, c0 = (ks & 3) * 2;
        uint32_t a[4];
        { int mi = lane >> 3, row = 16 * qh + (mi & 1) * 8 + (lane & 7), chunk = c0 + (mi >> 1);
          ldsm4(a, ub + hf * 4096 + row * 128 + ((chunk ^ (row & 7)) << 4)); }
        #pragma unroll
        for (int jp = 0; jp < 3; jp++) {
            uint32_t b[4];
            int mi = lane >> 3, nt = 2 * jp + (mi >> 1); if (nt > 4) nt = 4;
            int row = 8 * nt + (lane & 7), chunk = c0 + (mi & 1);
            ldsm4(b, ub + 8192 + hf * 5120 + row * 128 + ((chunk ^ (row & 7)) << 4));
            mma_bf16(sc[2 * jp], a[0], a[1], a[2], a[3], b[0], b[1]);
            if (jp < 2) mma_bf16(sc[2 * jp + 1], a[0], a[1], a[2], a[3], b[2], b[3]);
        }
    }
    uint32_t pa[3][4];
    {
        const float sc2 = 0.08838834764831845f * 1.4426950408889634f;
        float mx0 = -3.0e38f, mx1 = -3.0e38f;
        const int q0 = 16 * qh + g, q1 = q0 + 8;
        #pragma unroll
        for (int j = 0; j < 5; j++)
            #pragma unroll
            for (int e = 0; e < 2; e++) {
                int key = 8 * j + 2 * t + e - 8;
                sc[j][e] = (key <= q0) ? sc[j][e] * sc2 : -3.0e38f;
                sc[j][2 + e] = (key <= q1) ? sc[j][2 + e] * sc2 : -3.0e38f;
                mx0 = fmaxf(mx0, sc[j][e]); mx1 = fmaxf(mx1, sc[j][2 + e]);
            }
        mx0 = fmaxf(mx0, __shfl_xor_sync(~0u, mx0, 1)); mx0 = fmaxf(mx0, __shfl_xor_sync(~0u, mx0, 2));
        mx1 = fmaxf(mx1, __shfl_xor_sync(~0u, mx1, 1)); mx1 = fmaxf(mx1, __shfl_xor_sync(~0u, mx1, 2));
        float s0 = 0.f, s1 = 0.f;
        #pragma unroll
        for (int j = 0; j < 5; j++)
            #pragma unroll
            for (int e = 0; e < 2; e++) {
                sc[j][e] = ex2_approx(sc[j][e] - mx0); sc[j][2 + e] = ex2_approx(sc[j][2 + e] - mx1);
                s0 += sc[j][e]; s1 += sc[j][2 + e];
            }
        s0 += __shfl_xor_sync(~0u, s0, 1); s0 += __shfl_xor_sync(~0u, s0, 2);
        s1 += __shfl_xor_sync(~0u, s1, 1); s1 += __shfl_xor_sync(~0u, s1, 2);
        const float i0 = __frcp_rn(s0), i1 = __frcp_rn(s1);
        #pragma unroll
        for (int k = 0; k < 3; k++) {
            pa[k][0] = pack_bf16(sc[2 * k][0] * i0, sc[2 * k][1] * i0);
            pa[k][1] = pack_bf16(sc[2 * k][2] * i1, sc[2 * k][3] * i1);
            if (k < 2) { pa[k][2] = pack_bf16(sc[2 * k + 1][0] * i0, sc[2 * k + 1][1] * i0); pa[k][3] = pack_bf16(sc[2 * k + 1][2] * i1, sc[2 * k + 1][3] * i1); }
            else { pa[k][2] = 0u; pa[k][3] = 0u; }
        }
    }
    __syncwarp();
    nbar_sync(5 + u, 64);
    #pragma unroll
    for (int np = 0; np < 8; np++) {
        const int hf = np >> 2, c0 = (np & 3) * 2;
        float o0[4] = {0, 0, 0, 0}, o1[4] = {0, 0, 0, 0};
        #pragma unroll
        for (int k = 0; k < 3; k++) {
            uint32_t b[4];
            int mi = lane >> 3;
            int row = 16 * k + (mi & 1) * 8 + (lane & 7); if (row > 39) row = 39 - 7 + (lane & 7);
            int chunk = c0 + (mi >> 1);
            ldsm4t(b, ub + 18432 + hf * 5120 + row * 128 + ((chunk ^ (row & 7)) << 4));
            mma_bf16(o0, pa[k][0], pa[k][1], pa[k][2], pa[k][3], b[0], k < 2 ? b[1] : 0u);
            mma_bf16(o1, pa[k][0], pa[k][1], pa[k][2], pa[k][3], b[2], k < 2 ? b[3] : 0u);
        }
        int mi = lane >> 3, row = 16 * qh + (mi & 1) * 8 + (lane & 7), chunk = c0 + (mi >> 1);
        stsm4(ub + hf * 4096 + row * 128 + ((chunk ^ (row & 7)) << 4), pack_bf16(o0[0], o0[1]), pack_bf16(o0[2], o0[3]), pack_bf16(o1[0], o1[1]), pack_bf16(o1[2], o1[3]));
    }
}

template <int V> struct IntC { static constexpr int value = V; };
struct Task { int type, rb, c, k0, nch, plane; };
#define NFINE 29
#define NKP 8
#define KPC (64 / NKP + (64 % NKP ? 1 : 0))
#define NGEMM (8 + 144 + 8 * 2 + 4 + 8 * 4 + 2 * NKP * 3 + 16 * 3)
__device__ __forceinline__ Task decode_task(int j) {
    Task t; t.type = 0; t.rb = 0; t.c = 0; t.k0 = 0; t.nch = 16; t.plane = 0;
    auto H = [&](int rb, int i) { t.type = 1; t.rb = rb; t.c = i & 1; t.plane = i >> 1; t.k0 = t.plane * 16; };
    auto CF = [&](int rb, int i) { t.type = 2; t.rb = rb; t.c = i & 1; t.k0 = rb * 64 + (i >> 1) * 16; t.nch = 16; };
    auto H13 = [&](int rb, int i) { t.type = 1; t.rb = rb; t.c = i & 1; t.plane = i >> 1; t.k0 = t.plane * KPC; t.nch = (t.plane == NKP - 1) ? 64 - (NKP - 1) * KPC : KPC; };
    auto C13 = [&](int rb, int i) { t.type = 2; t.rb = rb; t.c = i & 1; t.k0 = rb * 64 + (i >> 1) * 8; t.nch = 8; };
    if (j >= NGEMM) { t.type = 3; return t; }
    if (j < 8) { t.c = j & 1; t.plane = j >> 1; t.k0 = t.plane * 16; return t; }
    j -= 8;
    if (j < 144) {
        const int q = j / 12, r = j % 12;
        if (r < 8) { t.rb = 2 * (q + 1); t.c = r & 1; t.plane = r >> 1; t.k0 = t.plane * 16; }
        else { t.type = 2; t.rb = 2 * q + ((r - 8) >> 1); t.c = r & 1; t.k0 = t.rb * 64; t.nch = 64; }
        return t;
    }
    j -= 144;
    if (j < 8) { H(26, j); return t; }
    j -= 8;
    if (j < 8) { H(27, j); return t; }
    j -= 8;
    if (j < 4) { t.type = 2; t.rb = 24 + (j >> 1); t.c = j & 1; t.k0 = t.rb * 64; t.nch = 64; return t; }
    j -= 4;
    if (j < 8) { H(28, j); return t; }
    j -= 8;
    if (j < 8) { CF(26, j); return t; }
    j -= 8;
    if (j < 8) { CF(27, j); return t; }
    j -= 8;
    if (j < 2 * NKP) { H13(29, j); return t; }
    j -= 2 * NKP;
    if (j < 8) { CF(28, j); return t; }
    j -= 8;
    if (j < 2 * NKP) { H13(30, j); return t; }
    j -= 2 * NKP;
    if (j < 16) { C13(29, j); return t; }
    j -= 16;
    if (j < 2 * NKP) { H13(31, j); return t; }
    j -= 2 * NKP;
    if (j < 16) { C13(30, j); return t; }
    j -= 16;
    C13(31, j);
    return t;
}
__device__ __forceinline__ void gemm_producer(unsigned char* smem, const CUtensorMap* womap, unsigned epoch, volatile int* s_tasks) {
    const uint32_t sb = smem_u32(smem);
    uint32_t st = 0, ph = 1;
    for (int n = 0;; n++) {
        const int j = (int)(atomicAdd(&g_gemmctr, 1u) - epoch * (unsigned)(NGEMM + NAUX));
        const Task t = decode_task(j);
        if (t.type <= 1) {
            wait_counter(&g_ocnt[t.rb], (epoch + 1) * 128u);
            if (t.type == 0) wait_counter(&g_ocnt[t.rb + 1], (epoch + 1) * 128u);
            fence_async_all();
        } else if (t.type == 2) {
            wait_counter(&g_gcnt[t.rb][t.c], (epoch + 1) * (t.rb >= NFINE ? (unsigned)NKP : 4u));
            wait_counter(&g_ssmcnt, (epoch + 1) * 80u);
        }
        const int nch = (t.type <= 1) ? t.nch : 1;
        for (int kc = 0; kc < nch; kc++) {
            mbar_wait_sleep(sb + AX_EMPTY + 8 * st, ph);
            const uint32_t a = sb + AX_DATA + st * AX_STAGE, bar = sb + AX_BAR + 16 + 8 * st;
            if (kc == 0) s_tasks[n & 7] = j;
            if (t.type > 1) mbar_arrive(bar);
            else {
                const bf16* asrc = g_Oimg + ((size_t)(t.rb >> 1) * 64 + t.k0 + kc) * 8192 + (t.rb & 1) * 4096;
                if (t.type == 0) { mbar_expect_tx(bar, AX_STAGE); bulk_g2s(a, asrc, 8192, bar); bulk_g2s(a + 8192, asrc + 4096, 8192, bar); }
                else { mbar_expect_tx(bar, AX_STAGE - 8192); bulk_g2s(a, asrc, 8192, bar); }
                #pragma unroll
                for (int b = 0; b < 5; b++) tma_load_2d(a + 16384 + b * 8192, womap, t.c * 320 + b * 64, (t.k0 + kc) * 64, bar);
            }
            if (++st == NST_G) { st = 0; ph ^= 1; }
        }
        if (t.type == 3) break;
    }
}
__device__ __forceinline__ void gemm_signaller(volatile int* s_done) {
    for (int n = 0;; n++) {
        nbar_sync(2, 288);
        const int j = s_done[n & 7];
        if (j < 0) break;
        if ((threadIdx.x & 31) == 0) {
            const Task t = decode_task(j);
            __threadfence();
            atomicAdd(&g_gcnt[t.rb][t.c], 1u);
            if (t.type == 0) atomicAdd(&g_gcnt[t.rb + 1][t.c], 1u);
        }
        __syncwarp();
    }
}
__device__ __forceinline__ void gemm_consumer(unsigned char* smem, bf16* __restrict__ out, volatile int* s_tasks, volatile int* s_done) {
    const uint32_t sb = smem_u32(smem);
    const int tid = threadIdx.x, lane = tid & 31;
    const int wg = __shfl_sync(~0u, tid >> 7, 0), warp = __shfl_sync(~0u, (tid >> 5) & 3, 0);
    uint32_t st = 0, ph = 0;
    int ndone = 0;
    for (int n = 0;; n++) {
        mbar_wait_sleep(sb + AX_BAR + 16 + 8 * st, ph);
        const Task t = decode_task(__shfl_sync(~0u, s_tasks[n & 7], 0));
        if (t.type > 1) {
            nbar_sync(1, 256);
            if ((tid & 127) == 0) mbar_arrive(sb + AX_EMPTY + 8 * st);
            if (++st == NST_G) { st = 0; ph ^= 1; }
            if (t.type == 3) break;
            const int np = (t.rb >= NFINE) ? NKP : 4;
            const float* pbase = (t.rb >= NFINE) ? g_part31 + (size_t)(t.rb - NFINE) * NKP * 64 * DM - (size_t)t.rb * 64 * DM : g_part;
            const size_t pstride = (t.rb >= NFINE) ? (size_t)64 * DM : (size_t)SEQ * DM;
            auto combine = [&](int i, auto NP) {
                const int r = t.k0 + i / 80, cc = t.c * 320 + (i % 80) * 4;
                float4 v[NP.value];
                #pragma unroll
                for (int q = 0; q < NP.value; q++) v[q] = __ldcg(reinterpret_cast<const float4*>(pbase + q * pstride + (size_t)r * DM + cc));
                const float gt = __ldcg(g_g + r);
                const uint2 bb = __ldcg(reinterpret_cast<const uint2*>(g_b + (size_t)r * DM + cc));
                float4 a = v[0];
                #pragma unroll
                for (int q = 1; q < NP.value; q++) { a.x += v[q].x; a.y += v[q].y; a.z += v[q].z; a.w += v[q].w; }
                const float b0 = __uint_as_float(bb.x << 16), b1 = __uint_as_float(bb.x & 0xffff0000u), b2 = __uint_as_float(bb.y << 16), b3 = __uint_as_float(bb.y & 0xffff0000u);
                uint2 o; o.x = pack_bf16(gt * a.x + (1.f - gt) * b0, gt * a.y + (1.f - gt) * b1); o.y = pack_bf16(gt * a.z + (1.f - gt) * b2, gt * a.w + (1.f - gt) * b3);
                *reinterpret_cast<uint2*>(out + (size_t)r * DM + cc) = o;
            };
            if (np == 4) {
                const int nit = t.nch * 80 / 256;
                for (int it0 = 0; it0 < nit; it0 += 5) {
                    #pragma unroll
                    for (int it = 0; it < 5; it++) combine(tid + 256 * (it0 + it), IntC<4>());
                }
            } else {
                #pragma unroll
                for (int it = 0; it < 3; it++) { const int i = tid + 256 * it; if (i < 640) combine(i, IntC<NKP>()); }
            }
            if (n < 56 && (blockIdx.x >= NATT || n < 4)) ATRID((blockIdx.x >= NATT ? 6 : 58) + n, s_tasks[n & 7]);
            continue;
        }
        const int g = lane >> 2, tq = lane & 3;
        if (t.type == 0) {
            float acc[160];
            #pragma unroll
            for (int i = 0; i < 160; i++) acc[i] = 0.f;
            uint32_t prev = 0;
            for (int kc = 0; kc < 16; kc++) {
                mbar_wait(sb + AX_BAR + 16 + 8 * st, ph);
                const uint32_t a = sb + AX_DATA + st * AX_STAGE;
                const uint64_t da = make_desc(a + wg * 8192, 16, 1024), db = make_desc(a + 16384, 8192, 1024);
                wg_fence();
                #pragma unroll
                for (int ks = 0; ks < 4; ks++) {
                    wgmma_n192_tB<0>(acc, da + ks * 2, db + ks * 128);
                    wgmma_n128_tB<96>(acc, da + ks * 2, db + ks * 128 + 3 * 512);
                }
                wg_commit();
                asm volatile("wgmma.wait_group.sync.aligned 1;" ::: "memory");
                if (kc > 0 && (tid & 127) == 0) mbar_arrive(sb + AX_EMPTY + 8 * prev);
                prev = st;
                if (++st == NST_G) { st = 0; ph ^= 1; }
            }
            wg_wait0();
            if ((tid & 127) == 0) mbar_arrive(sb + AX_EMPTY + 8 * prev);
            float* base = g_part + ((size_t)t.plane * SEQ + t.rb * 64 + wg * 64 + warp * 16 + g) * DM + t.c * 320 + 2 * tq;
            #pragma unroll
            for (int q = 0; q < 40; q++) {
                *reinterpret_cast<float2*>(base + q * 8) = make_float2(acc[4 * q], acc[4 * q + 1]);
                *reinterpret_cast<float2*>(base + 8 * DM + q * 8) = make_float2(acc[4 * q + 2], acc[4 * q + 3]);
            }
        } else {
            float* base = (t.rb >= NFINE ? g_part31 + (size_t)((t.rb - NFINE) * NKP + t.plane) * 64 * DM : g_part + ((size_t)t.plane * SEQ + t.rb * 64) * DM) + (size_t)(warp * 16 + g) * DM + t.c * 320 + 2 * tq;
            if (wg == 0) {
                float acc[160];
                #pragma unroll
                for (int i = 0; i < 96; i++) acc[i] = 0.f;
                uint32_t prev = 0;
                for (int kc = 0; kc < t.nch; kc++) {
                    mbar_wait(sb + AX_BAR + 16 + 8 * st, ph);
                    const uint32_t a = sb + AX_DATA + st * AX_STAGE;
                    const uint64_t da = make_desc(a, 16, 1024), db = make_desc(a + 16384, 8192, 1024);
                    wg_fence();
                    #pragma unroll
                    for (int ks = 0; ks < 4; ks++) wgmma_n192_tB<0>(acc, da + ks * 2, db + ks * 128);
                    wg_commit();
                    asm volatile("wgmma.wait_group.sync.aligned 1;" ::: "memory");
                    if (kc > 0 && (tid & 127) == 0) mbar_arrive(sb + AX_EMPTY + 8 * prev);
                    prev = st;
                    if (++st == NST_G) { st = 0; ph ^= 1; }
                }
                wg_wait0();
                if ((tid & 127) == 0) mbar_arrive(sb + AX_EMPTY + 8 * prev);
                #pragma unroll
                for (int q = 0; q < 24; q++) {
                    *reinterpret_cast<float2*>(base + q * 8) = make_float2(acc[4 * q], acc[4 * q + 1]);
                    *reinterpret_cast<float2*>(base + 8 * DM + q * 8) = make_float2(acc[4 * q + 2], acc[4 * q + 3]);
                }
            } else {
                float acc[160];
                #pragma unroll
                for (int i = 96; i < 160; i++) acc[i] = 0.f;
                uint32_t prev = 0;
                for (int kc = 0; kc < t.nch; kc++) {
                    mbar_wait(sb + AX_BAR + 16 + 8 * st, ph);
                    const uint32_t a = sb + AX_DATA + st * AX_STAGE;
                    const uint64_t da = make_desc(a, 16, 1024), db = make_desc(a + 16384, 8192, 1024);
                    wg_fence();
                    #pragma unroll
                    for (int ks = 0; ks < 4; ks++) wgmma_n128_tB<96>(acc, da + ks * 2, db + ks * 128 + 3 * 512);
                    wg_commit();
                    asm volatile("wgmma.wait_group.sync.aligned 1;" ::: "memory");
                    if (kc > 0 && (tid & 127) == 0) mbar_arrive(sb + AX_EMPTY + 8 * prev);
                    prev = st;
                    if (++st == NST_G) { st = 0; ph ^= 1; }
                }
                wg_wait0();
                if ((tid & 127) == 0) mbar_arrive(sb + AX_EMPTY + 8 * prev);
                #pragma unroll
                for (int q = 24; q < 40; q++) {
                    *reinterpret_cast<float2*>(base + q * 8) = make_float2(acc[4 * q], acc[4 * q + 1]);
                    *reinterpret_cast<float2*>(base + 8 * DM + q * 8) = make_float2(acc[4 * q + 2], acc[4 * q + 3]);
                }
            }
        }
        if (tid == 0) s_done[ndone & 7] = s_tasks[n & 7];
        ndone++;
        nbar_arrive(2, 288);
        if (n < 56 && (blockIdx.x >= NATT || n < 4)) ATRID((blockIdx.x >= NATT ? 6 : 58) + n, s_tasks[n & 7]);
    }
    if (tid == 0) s_done[ndone & 7] = -1;
    nbar_arrive(2, 288);
}

__global__ void __launch_bounds__(384, 1)
k_aux(const __grid_constant__ CUtensorMap womap, const bf16* __restrict__ x, const bf16* __restrict__ A_re, const bf16* __restrict__ A_im,
      const bf16* __restrict__ B_re, const bf16* __restrict__ B_im, const bf16* __restrict__ C_re, const bf16* __restrict__ C_im,
      const bf16* __restrict__ log_dt, const bf16* __restrict__ Dskip, const bf16* __restrict__ gw, bf16* __restrict__ out) {
    extern __shared__ __align__(1024) unsigned char smem[];
    const uint32_t sb = smem_u32(smem);
    const int tid = threadIdx.x, warp = tid >> 5, lane = tid & 31;
    __shared__ unsigned s_epoch;
    __shared__ int s_task, s_tasks[8], s_done[8];
    if (tid == 0) {
        for (int i = 0; i < 2 + NST_G; i++) mbar_init(sb + AX_BAR + 8 * i, 1);
        for (int i = 0; i < NST_G; i++) mbar_init(sb + AX_EMPTY + 8 * i, blockIdx.x < NATT ? 8 : 2);
        asm volatile("fence.mbarrier_init.release.cluster;" ::: "memory");
        s_epoch = *reinterpret_cast<volatile unsigned*>(&g_epoch);
    }
    __syncthreads();
    const unsigned epoch = s_epoch;
    ATR(0);
    const int wg = __shfl_sync(~0u, tid >> 7, 0);
    if (wg == 2) {
        asm volatile("setmaxnreg.dec.sync.aligned.u32 40;");
        if (blockIdx.x < NATT) { if (warp == 8) attn_producer(smem, blockIdx.x, epoch); else if (warp == 9) attn_storer(smem, blockIdx.x); __syncwarp(); }
        nbar_sync(3, 384);
        nbar_sync(3, 384);
        if (warp == 8) { if (lane == 0) gemm_producer(smem, &womap, epoch, s_tasks); }
        else if (warp == 9) gemm_signaller(s_done);
        __syncwarp();
        nbar_sync(4, 384);
    } else {
        asm volatile("setmaxnreg.inc.sync.aligned.u32 232;");
        if (blockIdx.x < NATT) attn_loop(smem, blockIdx.x, epoch);
        else {
            int ntask = 0;
            for (;;) {
                nbar_sync(1, 256);
                if (tid == 0) s_task = (int)(atomicAdd(&g_taskctr, 1u) - epoch * (unsigned)(80 + NAUX - NATT));
                nbar_sync(1, 256);
                const int task = s_task;
                if (task >= 80) break;
                for (int r = task * 26 + warp; r < min(SEQ, task * 26 + 26); r += 8) {
                    float sum = 0.f;
                    for (int i = lane * 2; i < DM; i += 64) {
                        __nv_bfloat162 xv = *reinterpret_cast<const __nv_bfloat162*>(x + (size_t)r * DM + i), wv = *reinterpret_cast<const __nv_bfloat162*>(gw + i);
                        sum += bf2f(xv.x) * bf2f(wv.x) + bf2f(xv.y) * bf2f(wv.y);
                    }
                    #pragma unroll
                    for (int o = 16; o; o >>= 1) sum += __shfl_xor_sync(~0u, sum, o);
                    if (lane == 0) g_g[r] = 1.f / (1.f + expf(-sum));
                }
                ssm_group(smem + AX_DATA, task, x, A_re, A_im, B_re, B_im, C_re, C_im, log_dt, Dskip);
                nbar_sync(1, 256);
                if (tid == 0) { __threadfence(); atomicAdd(&g_ssmcnt, 1u); }
                if (ntask < 4) ATR(2 + ntask);
                ntask++;
            }
        }
        fence_async();
        nbar_sync(3, 384);
        if (tid == 0) {
            for (int i = 0; i < NST_G; i++) {
                asm volatile("mbarrier.inval.shared::cta.b64 [%0];" :: "r"(sb + AX_BAR + 16 + 8 * i) : "memory");
                asm volatile("mbarrier.inval.shared::cta.b64 [%0];" :: "r"(sb + AX_EMPTY + 8 * i) : "memory");
                mbar_init(sb + AX_BAR + 16 + 8 * i, 1); mbar_init(sb + AX_EMPTY + 8 * i, 2);
            }
            asm volatile("fence.mbarrier_init.release.cluster;" ::: "memory");
        }
        nbar_sync(3, 384);
        gemm_consumer(smem, out, s_tasks, s_done);
        nbar_sync(4, 384);
        if (tid == 0) {
            __threadfence();
            unsigned old = atomicAdd(&g_auxdone, 1u);
            if (old == NAUX - 1) { g_auxdone = 0; __threadfence(); atomicAdd(&g_epoch, 1u); }
        }
    }
    asm volatile("griddepcontrol.wait;" ::: "memory");
}

extern "C" void kernel_launch(void* const* d_in, const int* in_sizes, int n_in, void* d_out, int out_size) {
    const bf16* x = (const bf16*)d_in[0];
    const bf16* mem0 = (const bf16*)d_in[1];
    const bf16* Wq = (const bf16*)d_in[2];
    const bf16* Wk = (const bf16*)d_in[3];
    const bf16* Wv = (const bf16*)d_in[4];
    const bf16* Wo = (const bf16*)d_in[5];
    const bf16 *A_re = (const bf16*)d_in[8], *A_im = (const bf16*)d_in[9], *B_re = (const bf16*)d_in[10], *B_im = (const bf16*)d_in[11];
    const bf16 *C_re = (const bf16*)d_in[12], *C_im = (const bf16*)d_in[13], *log_dt = (const bf16*)d_in[14], *Dskip = (const bf16*)d_in[15];
    const bf16* gw = (const bf16*)d_in[16];
    bf16* out = (bf16*)d_out;
    cudaStream_t st = cudaStreamPerThread;
    static bool init = false;
    static CUtensorMap xmap, womap, wqmap, wkmap, wvmap;
    static const void* xmap_ptr = nullptr; static const void* womap_ptr = nullptr; static const void* w_ptr[3] = {nullptr, nullptr, nullptr};
    if (!init) {
        cudaFuncSetAttribute(k_chain, cudaFuncAttributeMaxDynamicSharedMemorySize, SM_TOTAL);
        cudaFuncSetAttribute(k_aux, cudaFuncAttributeMaxDynamicSharedMemorySize, AX_TOTAL);
        init = true;
    }
    if (xmap_ptr != (const void*)x || womap_ptr != (const void*)Wo || w_ptr[0] != Wq || w_ptr[1] != Wk || w_ptr[2] != Wv) {
        void* fn = nullptr; cudaDriverEntryPointQueryResult qres;
        cudaGetDriverEntryPoint("cuTensorMapEncodeTiled", &fn, cudaEnableDefault, &qres);
        typedef CUresult (*EncFn)(CUtensorMap*, CUtensorMapDataType, cuuint32_t, void*, const cuuint64_t*, const cuuint64_t*, const cuuint32_t*, const cuuint32_t*,
                                  CUtensorMapInterleave, CUtensorMapSwizzle, CUtensorMapL2promotion, CUtensorMapFloatOOBfill);
        cuuint32_t es[2] = {1, 1};
        {
          cuuint64_t dims[3] = {64, SEQ, 10}; cuuint64_t strides[2] = {DM * 2, 128}; cuuint32_t box[3] = {64, 32, 10}; cuuint32_t es3[3] = {1, 1, 1};
          ((EncFn)fn)(&xmap, CU_TENSOR_MAP_DATA_TYPE_BFLOAT16, 3, (void*)x, dims, strides, box, es3, CU_TENSOR_MAP_INTERLEAVE_NONE, CU_TENSOR_MAP_SWIZZLE_128B,
                      CU_TENSOR_MAP_L2_PROMOTION_L2_128B, CU_TENSOR_MAP_FLOAT_OOB_FILL_NONE); }
        { cuuint64_t dims[2] = {DM, HD}; cuuint64_t strides[1] = {DM * 2}; cuuint32_t box[2] = {64, 64};
          ((EncFn)fn)(&womap, CU_TENSOR_MAP_DATA_TYPE_BFLOAT16, 2, (void*)Wo, dims, strides, box, es, CU_TENSOR_MAP_INTERLEAVE_NONE, CU_TENSOR_MAP_SWIZZLE_128B,
                      CU_TENSOR_MAP_L2_PROMOTION_L2_128B, CU_TENSOR_MAP_FLOAT_OOB_FILL_NONE); }
        { cuuint64_t dims[2] = {HD, DM}; cuuint64_t strides[1] = {HD * 2}; cuuint32_t box[2] = {64, 128};
          const bf16* ws[3] = {Wq, Wk, Wv}; CUtensorMap* ms[3] = {&wqmap, &wkmap, &wvmap};
          for (int i = 0; i < 3; i++)
              ((EncFn)fn)(ms[i], CU_TENSOR_MAP_DATA_TYPE_BFLOAT16, 2, (void*)ws[i], dims, strides, box, es, CU_TENSOR_MAP_INTERLEAVE_NONE, CU_TENSOR_MAP_SWIZZLE_128B,
                          CU_TENSOR_MAP_L2_PROMOTION_L2_128B, CU_TENSOR_MAP_FLOAT_OOB_FILL_NONE); }
        xmap_ptr = (const void*)x; womap_ptr = (const void*)Wo; w_ptr[0] = Wq; w_ptr[1] = Wk; w_ptr[2] = Wv;
    }
    k_chain<<<96, 384, SM_TOTAL, st>>>(xmap, wqmap, wkmap, wvmap, womap, x, mem0);
    {
        cudaLaunchConfig_t cfg = {};
        cfg.gridDim = dim3(NAUX); cfg.blockDim = dim3(384); cfg.dynamicSmemBytes = AX_TOTAL; cfg.stream = st;
        cudaLaunchAttribute at[1];
        at[0].id = cudaLaunchAttributeProgrammaticStreamSerialization; at[0].val.programmaticStreamSerializationAllowed = 1;
        cfg.attrs = at; cfg.numAttrs = 1;
        cudaLaunchKernelEx(&cfg, k_aux, womap, x, A_re, A_im, B_re, B_im, C_re, C_im, log_dt, Dskip, gw, out);
    }
}
```

```cpp
#include <cuda_runtime.h>
#include <cuda_bf16.h>
#include <stdint.h>
#include <cuda.h>

typedef __nv_bfloat16 bf16;

#define SEQ 2048
#define DM 640
#define NH 32
#define DH 128
#define NM 8
#define SEG 32
#define NSEG 64
#define NST 128
#define HD 4096

__device__ bf16  g_b[SEQ * DM];
__device__ float g_g[SEQ];

__device__ __forceinline__ float bf2f(bf16 v) { return __bfloat162float(v); }
__device__ __forceinline__ uint32_t pack_bf16(float lo, float hi) {
    uint32_t r; asm("cvt.rn.bf16x2.f32 %0, %1, %2;" : "=r"(r) : "f"(hi), "f"(lo)); return r;
}
__device__ __forceinline__ uint32_t f2tf32(float x) { uint32_t r; asm("cvt.rna.tf32.f32 %0, %1;" : "=r"(r) : "f"(x)); return r; }
__device__ __forceinline__ void mma_tf32(float (&d)[4], uint32_t a0, uint32_t a1, uint32_t a2, uint32_t a3, uint32_t b0, uint32_t b1) {
    asm volatile("mma.sync.aligned.m16n8k8.row.col.f32.tf32.tf32.f32 {%0,%1,%2,%3}, {%4,%5,%6,%7}, {%8,%9}, {%0,%1,%2,%3};\n"
        : "+f"(d[0]), "+f"(d[1]), "+f"(d[2]), "+f"(d[3]) : "r"(a0), "r"(a1), "r"(a2), "r"(a3), "r"(b0), "r"(b1));
}
__device__ __forceinline__ void mma_bf16(float (&d)[4], uint32_t a0, uint32_t a1, uint32_t a2, uint32_t a3, uint32_t b0, uint32_t b1) {
    asm volatile("mma.sync.aligned.m16n8k16.row.col.f32.bf16.bf16.f32 {%0,%1,%2,%3}, {%4,%5,%6,%7}, {%8,%9}, {%0,%1,%2,%3};\n"
        : "+f"(d[0]), "+f"(d[1]), "+f"(d[2]), "+f"(d[3]) : "r"(a0), "r"(a1), "r"(a2), "r"(a3), "r"(b0), "r"(b1));
}
struct cf { float re, im; };
__device__ __forceinline__ cf cmul(cf a, cf b) { cf r; r.re = a.re * b.re - a.im * b.im; r.im = a.re * b.im + a.im * b.re; return r; }
__device__ __forceinline__ cf csq(cf a) { cf r; r.re = a.re * a.re - a.im * a.im; r.im = 2.f * a.re * a.im; return r; }
__device__ __forceinline__ cf cexpL(float zr, float zi, float L) {
    float e = __expf(zr * L);
    float ang = zi * L;
    float k = rintf(ang * 0.15915494309189535f);
    ang = fmaf(-k, 6.2831854820251465f, ang);
    ang = fmaf(-k, -1.7484555314695172e-07f, ang);
    cf r; r.re = e * __cosf(ang); r.im = e * __sinf(ang); return r;
}

#define SSM_CH 8
#define KC_PITCH 648
#define XS_PAD 128
#define XS_PITCH (XS_PAD + 2048 + 8)
#define YS_PITCH (2048 + 8)
#define KT_LEN (2048 + 48)
struct SsmSmem {
    float Kc[SSM_CH][KC_PITCH];
    bf16  xs[SSM_CH][XS_PITCH];
    union {
        bf16  KT[SSM_CH][2][KT_LEN];
        float st[SSM_CH][NST][8];
    } u;
    bf16  ys[SSM_CH][YS_PITCH];
    uint16_t kidx[2048];
};

__device__ __forceinline__ int kc_index(int l) {
    return l < 256 ? l : (l < 512 ? 256 + ((l - 256) >> 1) : (l < 1024 ? 384 + ((l - 512) >> 2) : 512 + ((l - 1024) >> 3)));
}

__device__ __forceinline__ void ssm_group(unsigned char* smem_raw, int grp, const bf16* __restrict__ x, const bf16* __restrict__ A_re, const bf16* __restrict__ A_im,
        const bf16* __restrict__ B_re, const bf16* __restrict__ B_im, const bf16* __restrict__ C_re, const bf16* __restrict__ C_im,
        const bf16* __restrict__ log_dt, const bf16* __restrict__ Dskip) {
    SsmSmem& S = *reinterpret_cast<SsmSmem*>(smem_raw);
    const int tid = threadIdx.x, w = tid >> 5, lane = tid & 31, g = lane >> 2, t = lane & 3;
    const int d0 = grp * SSM_CH;
    asm volatile("bar.sync 1, 256;" ::: "memory");
    #pragma unroll
    for (int it = 0; it < 8; it++) {
        const int l = tid + 256 * it;
        uint4 v = *reinterpret_cast<const uint4*>(x + (size_t)l * DM + d0);
        const bf16* p = reinterpret_cast<const bf16*>(&v);
        const int lr = (l & ~15) | (15 - (l & 15));
        #pragma unroll
        for (int c = 0; c < 8; c++) S.xs[c][XS_PAD + lr] = p[c];
        S.kidx[l] = (uint16_t)((int)bf2f(__float2bfloat16_rn((float)l)) == 2048 ? 640 : kc_index((int)bf2f(__float2bfloat16_rn((float)l))));
    }
    for (int i = tid; i < SSM_CH * XS_PAD / 2; i += 256) reinterpret_cast<uint32_t*>(&S.xs[i / (XS_PAD / 2)][0])[i % (XS_PAD / 2)] = 0u;
    {
        const int d = d0 + w;
        const float dt = bf2f(__float2bfloat16_rn(expf(bf2f(log_dt[d]))));
        #pragma unroll
        for (int i = 0; i < 4; i++) {
            const int n = lane + 32 * i;
            float zr = dt * bf2f(A_re[d * NST + n]), zi = dt * bf2f(A_im[d * NST + n]);
            cf dB; dB.re = dt * bf2f(B_re[d * NST + n]); dB.im = dt * bf2f(B_im[d * NST + n]);
            cf C; C.re = bf2f(C_re[d * NST + n]); C.im = bf2f(C_im[d * NST + n]);
            cf wv = cmul(C, dB);
            cf u8 = cexpL(zr, zi, 8.f), u128 = cexpL(zr, zi, 128.f);
            float* st = S.u.st[w][n];
            *reinterpret_cast<float4*>(st) = make_float4(zr, zi, wv.re, wv.im);
            *reinterpret_cast<float4*>(st + 4) = make_float4(u8.re, u8.im, u128.re, u128.im);
        }
        __syncwarp();
        float a0a[4] = {0, 0, 0, 0}, a0b[4] = {0, 0, 0, 0}, a1[4] = {0, 0, 0, 0}, a2a[4] = {0, 0, 0, 0}, a2b[4] = {0, 0, 0, 0};
        float k2048 = 0.f;
        const float Lg = (g < 4) ? (512.f + 4.f * g) : (g < 6 ? 1024.f + 8.f * (g - 4) : 1536.f + 8.f * (g - 6));
        #pragma unroll 4
        for (int kk = 0; kk < 32; kk++) {
            const float* st = S.u.st[w][4 * kk + t];
            float4 s0 = *reinterpret_cast<const float4*>(st), s1 = *reinterpret_cast<const float4*>(st + 4);
            cf wv; wv.re = s0.z; wv.im = s0.w;
            cf u8; u8.re = s1.x; u8.im = s1.y;
            cf u128; u128.re = s1.z; u128.im = s1.w;
            cf e1 = cexpL(s0.x, s0.y, (float)g);
            cf e23 = cexpL(s0.x, s0.y, Lg);
            cf e1b = cmul(e1, u8);
            cf e2 = csq(e1);
            cf p = csq(csq(csq(e2)));
            cf f0 = cmul(wv, p), f1 = cmul(f0, u128), f2 = cmul(f1, u128), f3 = cmul(f2, u128);
            uint32_t A00 = f2tf32(f0.re), A01 = f2tf32(f1.re), A02 = f2tf32(-f0.im), A03 = f2tf32(-f1.im);
            uint32_t A10 = f2tf32(f2.re), A11 = f2tf32(f3.re), A12 = f2tf32(-f2.im), A13 = f2tf32(-f3.im);
            mma_tf32(a0a, A00, A01, A02, A03, f2tf32(e1.re), f2tf32(e1.im));
            mma_tf32(a0b, A00, A01, A02, A03, f2tf32(e1b.re), f2tf32(e1b.im));
            mma_tf32(a1, A10, A11, A12, A13, f2tf32(e2.re), f2tf32(e2.im));
            uint32_t E0 = f2tf32(e23.re), E1 = f2tf32(e23.im);
            mma_tf32(a2a, A00, A01, A02, A03, E0, E1);
            mma_tf32(a2b, A10, A11, A12, A13, E0, E1);
            cf e2048 = csq(e23);
            k2048 += wv.re * e2048.re - wv.im * e2048.im;
        }
        k2048 += __shfl_xor_sync(~0u, k2048, 1);
        k2048 += __shfl_xor_sync(~0u, k2048, 2);
        float* Kc = S.Kc[w];
        Kc[16 * g + 2 * t] = a0a[0]; Kc[16 * g + 2 * t + 1] = a0a[1]; Kc[16 * (g + 8) + 2 * t] = a0a[2]; Kc[16 * (g + 8) + 2 * t + 1] = a0a[3];
        Kc[16 * g + 8 + 2 * t] = a0b[0]; Kc[16 * g + 8 + 2 * t + 1] = a0b[1]; Kc[16 * (g + 8) + 8 + 2 * t] = a0b[2]; Kc[16 * (g + 8) + 8 + 2 * t + 1] = a0b[3];
        Kc[256 + 8 * g + 2 * t] = a1[0]; Kc[256 + 8 * g + 2 * t + 1] = a1[1]; Kc[256 + 8 * (g + 8) + 2 * t] = a1[2]; Kc[256 + 8 * (g + 8) + 2 * t + 1] = a1[3];
        #pragma unroll
        for (int mt = 0; mt < 2; mt++) {
            #pragma unroll
            for (int e = 0; e < 4; e++) {
                int A = mt * 16 + g + (e >> 1) * 8, j = 2 * t + (e & 1);
                int Lj = (j < 4) ? 512 + 4 * j : (j < 6 ? 1024 + 8 * (j - 4) : 1536 + 8 * (j - 6));
                Kc[kc_index(Lj + 16 * A)] = mt ? a2b[e] : a2a[e];
            }
        }
        if (lane == 16) Kc[640] = k2048;
    }
    __syncwarp();
    {
        asm volatile("bar.sync 1, 256;" ::: "memory");
        bf16* k0 = S.u.KT[w][0];
        bf16* k1 = S.u.KT[w][1];
        const float* Kc = S.Kc[w];
        #pragma unroll 8
        for (int j = lane; j < 2048; j += 32) {
            const bf16 v = __float2bfloat16_rn(Kc[S.kidx[j]]);
            k0[16 + j] = v;
            k1[15 + j] = v;
        }
        if (lane < 16) { k0[lane] = __float2bfloat16_rn(0.f); if (lane < 15) k1[lane] = __float2bfloat16_rn(0.f); }
        k0[2064 + lane] = __float2bfloat16_rn(0.f); k1[2063 + lane] = __float2bfloat16_rn(0.f);
        __syncwarp();
    }
    {
        float acc[16][4];
        #pragma unroll
        for (int v = 0; v < 16; v++) { acc[v][0] = acc[v][1] = acc[v][2] = acc[v][3] = 0.f; }
        const bf16* kt = (g & 1) ? &S.u.KT[w][0][0] : &S.u.KT[w][1][0];
        const int ibase0 = g + 1 + 2 * t - ((g & 1) ? 0 : 1);
        #pragma unroll 1
        for (int r = 0; r < 8; r++) {
            uint32_t B[16][2];
            #pragma unroll
            for (int v = 0; v < 16; v++) {
                const bf16* p = &S.xs[w][XS_PAD + 16 * (8 * v + g - r) + 2 * t];
                B[v][0] = *reinterpret_cast<const uint32_t*>(p);
                B[v][1] = *reinterpret_cast<const uint32_t*>(p + 8);
            }
            #pragma unroll
            for (int q = 0; q < 16; q++) {
                const int i0 = ibase0 + 16 * r + 128 * q;
                const uint32_t A0 = *reinterpret_cast<const uint32_t*>(kt + i0);
                const uint32_t A1 = *reinterpret_cast<const uint32_t*>(kt + i0 + 8);
                const uint32_t A3 = *reinterpret_cast<const uint32_t*>(kt + i0 + 16);
                #pragma unroll
                for (int v = q; v < 16; v++) mma_bf16(acc[v], A0, A1, A1, A3, B[v - q][0], B[v - q][1]);
            }
        }
        bf16* ys = S.ys[w];
        #pragma unroll
        for (int v = 0; v < 16; v++) {
            const int a = 8 * v + 2 * t;
            ys[16 * a + g] = __float2bfloat16_rn(acc[v][0]); ys[16 * (a + 1) + g] = __float2bfloat16_rn(acc[v][1]);
            ys[16 * a + g + 8] = __float2bfloat16_rn(acc[v][2]); ys[16 * (a + 1) + g + 8] = __float2bfloat16_rn(acc[v][3]);
        }
    }
    asm volatile("bar.sync 1, 256;" ::: "memory");
    {
        float dsk[8];
        #pragma unroll
        for (int c = 0; c < 8; c++) dsk[c] = bf2f(Dskip[d0 + c]);
        #pragma unroll 2
        for (int it = 0; it < 8; it++) {
            const int l = tid + 256 * it;
            const int lr = XS_PAD + ((l & ~15) | (15 - (l & 15)));
            float o[8];
            #pragma unroll
            for (int c = 0; c < 8; c++) o[c] = bf2f(S.ys[c][l]) + bf2f(__float2bfloat16_rn(bf2f(S.xs[c][lr]) * dsk[c]));
            *reinterpret_cast<uint4*>(g_b + (size_t)l * DM + d0) = make_uint4(pack_bf16(o[0], o[1]), pack_bf16(o[2], o[3]), pack_bf16(o[4], o[5]), pack_bf16(o[6], o[7]));
        }
    }
}

__device__ __forceinline__ uint32_t smem_u32(const void* p) { return (uint32_t)__cvta_generic_to_shared(p); }
__device__ __forceinline__ void mbar_init(uint32_t bar, uint32_t cnt) { asm volatile("mbarrier.init.shared::cta.b64 [%0], %1;" :: "r"(bar), "r"(cnt) : "memory"); }
__device__ __forceinline__ void mbar_expect_tx(uint32_t bar, uint32_t bytes) { asm volatile("mbarrier.arrive.expect_tx.shared::cta.b64 _, [%0], %1;" :: "r"(bar), "r"(bytes) : "memory"); }
__device__ __forceinline__ void mbar_arrive(uint32_t bar) { asm volatile("mbarrier.arrive.shared::cta.b64 _, [%0];" :: "r"(bar) : "memory"); }
__device__ __forceinline__ void mbar_wait(uint32_t bar, uint32_t parity) {
    uint32_t ok; int guard = 0;
    do {
        asm volatile("{\n.reg .pred P1;\nmbarrier.test_wait.parity.shared::cta.b64 P1, [%1], %2;\nselp.u32 %0,1,0,P1;\n}" : "=r"(ok) : "r"(bar), "r"(parity) : "memory");
    } while (!ok && ++guard < (1 << 26));
}
__device__ __forceinline__ void mbar_wait_sleep(uint32_t bar, uint32_t parity) {
    uint32_t ok; int guard = 0;
    do {
        asm volatile("{\n.reg .pred P1;\nmbarrier.try_wait.parity.shared::cta.b64 P1, [%1], %2;\nselp.u32 %0,1,0,P1;\n}" : "=r"(ok) : "r"(bar), "r"(parity) : "memory");
    } while (!ok && ++guard < (1 << 22));
}
__device__ __forceinline__ uint32_t mapa(uint32_t addr, uint32_t rank) { uint32_t r; asm volatile("mapa.shared::cluster.u32 %0, %1, %2;" : "=r"(r) : "r"(addr), "r"(rank)); return r; }
__device__ __forceinline__ void st_async4(uint32_t addr, float a, float b, float c, float d, uint32_t bar) {
    asm volatile("st.async.weak.shared::cluster.mbarrier::complete_tx::bytes.v4.f32 [%0], {%1,%2,%3,%4}, [%5];" :: "r"(addr), "f"(a), "f"(b), "f"(c), "f"(d), "r"(bar) : "memory");
}
__device__ __forceinline__ void bulk_s2c(uint32_t dst, uint32_t src, uint32_t bytes, uint32_t bar) {
    asm volatile("cp.async.bulk.shared::cluster.shared::cta.mbarrier::complete_tx::bytes [%0], [%1], %2, [%3];" :: "r"(dst), "r"(src), "r"(bytes), "r"(bar) : "memory");
}
__device__ __forceinline__ void bulk_g2s(uint32_t dst, const void* src, uint32_t bytes, uint32_t bar) {
    asm volatile("cp.async.bulk.shared::cluster.global.mbarrier::complete_tx::bytes [%0], [%1], %2, [%3];" :: "r"(dst), "l"(src), "r"(bytes), "r"(bar) : "memory");
}
__device__ __forceinline__ void bulk_s2g(void* dst, uint32_t src, uint32_t bytes) {
    asm volatile("cp.async.bulk.global.shared::cta.bulk_group [%0], [%1], %2;" :: "l"(dst), "r"(src), "r"(bytes) : "memory");
}
__device__ __forceinline__ void bulk_commit() { asm volatile("cp.async.bulk.commit_group;" ::: "memory"); }
__device__ __forceinline__ void bulk_wait_read0() { asm volatile("cp.async.bulk.wait_group.read 0;" ::: "memory"); }
__device__ __forceinline__ void bulk_wait0() { asm volatile("cp.async.bulk.wait_group 0;" ::: "memory"); }
__device__ __forceinline__ void fence_async() { asm volatile("fence.proxy.async.shared::cta;" ::: "memory"); }
__device__ __forceinline__ void nbar_sync(int id, int n) { asm volatile("bar.sync %0, %1;" :: "r"(id), "r"(n) : "memory"); }
__device__ __forceinline__ void nbar_arrive(int id, int n) { asm volatile("bar.arrive %0, %1;" :: "r"(id), "r"(n) : "memory"); }
__device__ __forceinline__ void cp_async16(uint32_t dst, const void* src) { asm volatile("cp.async.cg.shared.global [%0], [%1], 16;" :: "r"(dst), "l"(src) : "memory"); }
__device__ __forceinline__ void cp_async_wait_all() { asm volatile("cp.async.wait_all;" ::: "memory"); }
__device__ __forceinline__ void ldsm4(uint32_t (&r)[4], uint32_t addr) {
    asm volatile("ldmatrix.sync.aligned.m8n8.x4.shared.b16 {%0,%1,%2,%3}, [%4];" : "=r"(r[0]), "=r"(r[1]), "=r"(r[2]), "=r"(r[3]) : "r"(addr) : "memory");
}
__device__ __forceinline__ void ldsm4t(uint32_t (&r)[4], uint32_t addr) {
    asm volatile("ldmatrix.sync.aligned.m8n8.x4.trans.shared.b16 {%0,%1,%2,%3}, [%4];" : "=r"(r[0]), "=r"(r[1]), "=r"(r[2]), "=r"(r[3]) : "r"(addr) : "memory");
}
__device__ __forceinline__ void stsm2t(uint32_t addr, uint32_t r0, uint32_t r1) {
    asm volatile("stmatrix.sync.aligned.m8n8.x2.trans.shared.b16 [%0], {%1,%2};" :: "r"(addr), "r"(r0), "r"(r1) : "memory");
}
__device__ __forceinline__ uint4 ld_relaxed4(const void* p) { uint4 v; asm volatile("ld.relaxed.gpu.global.v4.u32 {%0,%1,%2,%3}, [%4];" : "=r"(v.x), "=r"(v.y), "=r"(v.z), "=r"(v.w) : "l"(p) : "memory"); return v; }
__device__ __forceinline__ void st_relaxed2(void* p, uint32_t a, uint32_t b) { asm volatile("st.relaxed.gpu.global.v2.u32 [%0], {%1,%2};" :: "l"(p), "r"(a), "r"(b) : "memory"); }
__device__ __forceinline__ void st_relaxed1(void* p, uint32_t a) { asm volatile("st.relaxed.gpu.global.u32 [%0], %1;" :: "l"(p), "r"(a) : "memory"); }
__device__ __forceinline__ unsigned ld_acquire(const unsigned* p) { unsigned v; asm volatile("ld.acquire.gpu.global.u32 %0, [%1];" : "=r"(v) : "l"(p) : "memory"); return v; }
__device__ __forceinline__ float ex2_approx(float x) { float r; asm("ex2.approx.ftz.f32 %0, %1;" : "=f"(r) : "f"(x)); return r; }
__device__ __forceinline__ uint64_t make_desc(uint32_t saddr, uint32_t lbo, uint32_t sbo) {
    return (uint64_t)((saddr & 0x3FFFF) >> 4) | ((uint64_t)((lbo & 0x3FFFF) >> 4) << 16) | ((uint64_t)((sbo & 0x3FFFF) >> 4) << 32) | (1ull << 62);
}
__device__ __forceinline__ void wg_fence() { asm volatile("wgmma.fence.sync.aligned;" ::: "memory"); }
__device__ __forceinline__ void wg_commit() { asm volatile("wgmma.commit_group.sync.aligned;" ::: "memory"); }
__device__ __forceinline__ void wg_wait0() { asm volatile("wgmma.wait_group.sync.aligned 0;" ::: "memory"); }
__device__ __forceinline__ void wgmma_n40_tA(float (&d)[20], uint64_t da, uint64_t db, int scale_d) {
    asm volatile("{\n.reg .pred p;\nsetp.ne.b32 p, %22, 0;\n"
        "wgmma.mma_async.sync.aligned.m64n40k16.f32.bf16.bf16 {%0,%1,%2,%3,%4,%5,%6,%7,%8,%9,%10,%11,%12,%13,%14,%15,%16,%17,%18,%19}, %20, %21, p, 1, 1, 1, 0;\n}\n"
        : "+f"(d[0]), "+f"(d[1]), "+f"(d[2]), "+f"(d[3]), "+f"(d[4]), "+f"(d[5]), "+f"(d[6]), "+f"(d[7]), "+f"(d[8]), "+f"(d[9]),
          "+f"(d[10]), "+f"(d[11]), "+f"(d[12]), "+f"(d[13]), "+f"(d[14]), "+f"(d[15]), "+f"(d[16]), "+f"(d[17]), "+f"(d[18]), "+f"(d[19])
        : "l"(da), "l"(db), "r"(scale_d));
}

#define NRED 80
#define CAL_THR 410u
#define COMM_REGS "40"
#define NPOOL 576
#define RPS 1
__device__ __align__(4096) uint32_t g_pool[(NPOOL + 1) * 1024];
__device__ unsigned g_cls[NPOOL];
__device__ unsigned g_side[96];
__device__ unsigned g_calcnt;
__device__ unsigned g_epoch;
__device__ unsigned g_flag[NSEG][NH];
__device__ __align__(1024) bf16 g_Qimg[NSEG * NH * 2 * 32 * 64];
__device__ __align__(1024) bf16 g_Kimg[NSEG * NH * 2 * 40 * 64];
__device__ __align__(1024) bf16 g_Vimg[NSEG * NH * 2 * 40 * 64];

#define SM_XB    0
#define SM_VT    81920
#define SM_KT    (SM_VT + 20480)
#define SM_QT    (SM_KT + 10240)
#define SM_QS    (SM_QT + 4096)
#define SM_MEMB  (SM_QS + 1024)
#define SM_RED   (SM_MEMB + 10240)
#define SM_SC    (SM_RED + 16384)
#define SM_CRED  (SM_SC + 5120)
#define SM_PB    (SM_CRED + 1024)
#define SM_TRACE (SM_PB + 1024)
#define SM_WO    163840
#define SM_BAR   (SM_WO + 65536)
#define SM_TPM   (SM_BAR + 256)
#define SM_TRD   (SM_TPM + 256)
#define SM_TPUB  (SM_TRD + 16)
#define SM_TGAT  (SM_TPUB + 128)
#define SM_CAL   (SM_TGAT + 64)
#define SM_TOTAL (SM_CAL + 128)
#define B_SC   (SM_BAR + 0)
#define B_V    (SM_BAR + 16)
#define B_P    (SM_BAR + 48)
#define B_X    (SM_BAR + 56)
#define B_EXP  (SM_BAR + 72)

#define TR(ev) do {} while (0)
__device__ __forceinline__ uint32_t tag_of(int s) { return (uint32_t)(((s >> 1) & 1) + 1); }
__device__ __forceinline__ unsigned probe_latency(uint32_t* p, uint32_t zero) {
    uint32_t v, best = 0xffffffffu;
    asm volatile("atom.relaxed.gpu.global.add.u32 %0, [%1], 0;" : "=r"(v) : "l"(p) : "memory");
    #pragma unroll 1
    for (int r = 0; r < 4; r++) {
        uint32_t c0, c1;
        asm volatile("mov.u32 %0, %%clock;" : "=r"(c0) : "r"(v) : "memory");
        asm volatile("atom.relaxed.gpu.global.add.u32 %0, [%1], 0;" : "=r"(v) : "l"(p + ((v + c0) & zero)) : "memory");
        asm volatile("{\n.reg .u32 t;\nand.b32 t, %1, %2;\nmov.u32 %0, %%clock;\nadd.u32 %0, %0, t;\n}" : "=r"(c1) : "r"(v), "r"(zero) : "memory");
        best = min(best, c1 - c0);
    }
    return best;
}
__device__ __forceinline__ void cluster_sync_all() { asm volatile("barrier.cluster.arrive.release.aligned;\nbarrier.cluster.wait.acquire.aligned;" ::: "memory"); }
__device__ __forceinline__ void tma_load_2d(uint32_t dst, const void* map, int c0, int c1, uint32_t bar) {
    asm volatile("cp.async.bulk.tensor.2d.shared::cluster.global.mbarrier::complete_tx::bytes [%0], [%1, {%3, %4}], [%2];"
        :: "r"(dst), "l"(map), "r"(bar), "r"(c0), "r"(c1) : "memory");
}
__device__ __forceinline__ void tma_load_3d(uint32_t dst, const void* map, int c0, int c1, int c2, uint32_t bar) {
    asm volatile("cp.async.bulk.tensor.3d.shared::cluster.global.mbarrier::complete_tx::bytes [%0], [%1, {%3, %4, %5}], [%2];"
        :: "r"(dst), "l"(map), "r"(bar), "r"(c0), "r"(c1), "r"(c2) : "memory");
}
__device__ __forceinline__ void stsm4t(uint32_t addr, uint32_t r0, uint32_t r1, uint32_t r2, uint32_t r3) {
    asm volatile("stmatrix.sync.aligned.m8n8.x4.trans.shared.b16 [%0], {%1,%2,%3,%4};" :: "r"(addr), "r"(r0), "r"(r1), "r"(r2), "r"(r3) : "memory");
}
__device__ __forceinline__ void wgmma_n32_rs(float (&d)[16], const uint32_t (&a)[4], uint64_t db, int scale_d) {
    asm volatile("{\n.reg .pred p;\nsetp.ne.b32 p, %21, 0;\n"
        "wgmma.mma_async.sync.aligned.m64n32k16.f32.bf16.bf16 {%0,%1,%2,%3,%4,%5,%6,%7,%8,%9,%10,%11,%12,%13,%14,%15}, {%16,%17,%18,%19}, %20, p, 1, 1, 0;\n}\n"
        : "+f"(d[0]), "+f"(d[1]), "+f"(d[2]), "+f"(d[3]), "+f"(d[4]), "+f"(d[5]), "+f"(d[6]), "+f"(d[7]),
          "+f"(d[8]), "+f"(d[9]), "+f"(d[10]), "+f"(d[11]), "+f"(d[12]), "+f"(d[13]), "+f"(d[14]), "+f"(d[15])
        : "r"(a[0]), "r"(a[1]), "r"(a[2]), "r"(a[3]), "l"(db), "r"(scale_d));
}

__device__ __forceinline__ void st_async4u(uint32_t addr, uint4 v, uint32_t bar) {
    asm volatile("st.async.weak.shared::cluster.mbarrier::complete_tx::bytes.v4.u32 [%0], {%1,%2,%3,%4}, [%5];" :: "r"(addr), "r"(v.x), "r"(v.y), "r"(v.z), "r"(v.w), "r"(bar) : "memory");
}
__device__ __forceinline__ void export_issue(uint32_t sb, int s, int h, uint32_t rank) {
    const size_t img = (size_t)(s * NH + h) * 2;
    const int sl = s & 1;
    if (rank == 2) {
        bulk_s2g(g_Vimg + img * 2560, sb + SM_VT + sl * 10240, 5120);
        bulk_s2g(g_Vimg + (img + 1) * 2560, sb + SM_VT + sl * 10240 + 5120, 5120);
    } else {
        bulk_s2g(g_Qimg + (img + rank) * 2048, sb + SM_QT, 4096);
        bulk_s2g(g_Kimg + (img + rank) * 2560, sb + SM_KT + sl * 5120, 5120);
    }
    bulk_commit();
    bulk_wait_read0();
    mbar_arrive(sb + B_EXP);
}
__device__ __forceinline__ void export_signal(int s, int h) {
    bulk_wait0();
    asm volatile("fence.proxy.async;" ::: "memory");
    __threadfence();
    atomicAdd(&g_flag[s][h], 1u);
}

__device__ __forceinline__ void score_tile(uint32_t sb, int sl, int nt, int lane, uint32_t rank) {
    float sc[4] = {0, 0, 0, 0}, sd[4] = {0, 0, 0, 0};
    const int r = lane & 7;
    uint32_t qa[2][4], kb[2][4];
    #pragma unroll
    for (int j = 0; j < 2; j++) {
        const int chunk = (lane >> 3) + 4 * j;
        ldsm4(kb[j], sb + SM_KT + sl * 5120 + (8 * nt + r) * 128 + ((chunk ^ r) << 4));
        ldsm4(qa[j], sb + SM_QS + r * 128 + ((chunk ^ r) << 4));
    }
    mma_bf16(sc, qa[0][0], 0u, qa[0][1], 0u, kb[0][0], kb[0][1]);
    mma_bf16(sd, qa[1][0], 0u, qa[1][1], 0u, kb[1][0], kb[1][1]);
    mma_bf16(sc, qa[0][2], 0u, qa[0][3], 0u, kb[0][2], kb[0][3]);
    mma_bf16(sd, qa[1][2], 0u, qa[1][3], 0u, kb[1][2], kb[1][3]);
    sc[0] += sd[0]; sc[1] += sd[1];
    const float o0 = __shfl_down_sync(~0u, sc[0], 1), o1 = __shfl_down_sync(~0u, sc[1], 1);
    if ((lane & 1) == 0) {
        const uint32_t a = SM_SC + sl * 2560 + rank * 1280 + ((lane >> 2) * 40 + 8 * nt + 2 * (lane & 3)) * 4;
        const uint32_t bo = B_SC + 8 * sl;
        { const uint32_t rb = mapa(sb, 2); st_async4(rb + a, sc[0], sc[1], o0, o1, rb + bo); }
        { const uint32_t rb = mapa(sb, rank ^ 1); st_async4(rb + a, sc[0], sc[1], o0, o1, rb + bo); }
        asm volatile("st.shared.v4.f32 [%0], {%1,%2,%3,%4};" :: "r"(sb + a), "f"(sc[0]), "f"(sc[1]), "f"(o0), "f"(o1) : "memory");
    }
    __syncwarp();
    if (lane == 0) mbar_arrive(sb + B_SC + 8 * sl);
}
__device__ __forceinline__ void wgmma_n40_rs(float (&d)[20], const uint32_t (&a)[4], uint64_t db, int scale_d) {
    asm volatile("{\n.reg .pred p;\nsetp.ne.b32 p, %25, 0;\n"
        "wgmma.mma_async.sync.aligned.m64n40k16.f32.bf16.bf16 {%0,%1,%2,%3,%4,%5,%6,%7,%8,%9,%10,%11,%12,%13,%14,%15,%16,%17,%18,%19}, {%20,%21,%22,%23}, %24, p, 1, 1, 0;\n}\n"
        : "+f"(d[0]), "+f"(d[1]), "+f"(d[2]), "+f"(d[3]), "+f"(d[4]), "+f"(d[5]), "+f"(d[6]), "+f"(d[7]), "+f"(d[8]), "+f"(d[9]),
          "+f"(d[10]), "+f"(d[11]), "+f"(d[12]), "+f"(d[13]), "+f"(d[14]), "+f"(d[15]), "+f"(d[16]), "+f"(d[17]), "+f"(d[18]), "+f"(d[19])
        : "r"(a[0]), "r"(a[1]), "r"(a[2]), "r"(a[3]), "l"(db), "r"(scale_d));
}
__device__ __forceinline__ void pu_mma(float (&o)[4], const float (&u)[20], const uint32_t (&pb)[5]) {
    float o2[4] = {0, 0, 0, 0};
    o[0] = o[1] = o[2] = o[3] = 0.f;
    mma_bf16(o, pack_bf16(u[0], u[1]), pack_bf16(u[2], u[3]), pack_bf16(u[4], u[5]), pack_bf16(u[6], u[7]), pb[0], pb[1]);
    mma_bf16(o2, pack_bf16(u[8], u[9]), pack_bf16(u[10], u[11]), pack_bf16(u[12], u[13]), pack_bf16(u[14], u[15]), pb[2], pb[3]);
    mma_bf16(o, pack_bf16(u[16], u[17]), pack_bf16(u[18], u[19]), 0u, 0u, pb[4], 0u);
    o[0] += o2[0]; o[1] += o2[1]; o[2] += o2[2]; o[3] += o2[3];
}
__device__ __forceinline__ void pu_store(const float (&o)[4], float2 inv, uint2 off, int lane, uint32_t tg) {
    unsigned char* pool = reinterpret_cast<unsigned char*>(g_pool) + lane * 8;
    st_relaxed2(pool + off.x, (__float_as_uint(o[0] * inv.x) & ~3u) | tg, (__float_as_uint(o[1] * inv.y) & ~3u) | tg);
    st_relaxed2(pool + off.y, (__float_as_uint(o[2] * inv.x) & ~3u) | tg, (__float_as_uint(o[3] * inv.y) & ~3u) | tg);
}
__device__ __forceinline__ float rcp_approx(float x) { float r; asm("rcp.approx.ftz.f32 %0, %1;" : "=f"(r) : "f"(x)); return r; }
template <int NT>
__device__ __forceinline__ void u_pass(unsigned char* smem, uint32_t sb, int s, uint32_t rank, int wg, int warp, int lane) {
    const int sl = s & 1;
#define NRS_V 6
    constexpr int NRS = NRS_V;
    uint32_t wa[NRS][4];
    {
        const int mi = lane >> 3, chunk = 2 * warp + (mi & 1);
        #pragma unroll
        for (int ks = 0; ks < NRS; ks++) {
            const int row = 16 * ks + (mi >> 1) * 8 + (lane & 7);
            ldsm4t(wa[ks], sb + SM_WO + (2 * wg) * 16384 + row * 128 + ((chunk ^ (row & 7)) << 4));
        }
    }
    if (rank < 2) { mbar_wait(sb + B_V + 8 * sl, (s >> 1) & 1); fence_async(); }
    if (wg == 0 && warp == 0) TR(4);
    float U0[20];
    wg_fence();
    #pragma unroll
    for (int ks = 0; ks < NRS; ks++)
        wgmma_n40_rs(U0, wa[ks], make_desc(sb + SM_VT + sl * 10240 + (ks >> 2) * 5120 + (ks & 3) * 32, 16, 1024), ks > 0);
    #pragma unroll
    for (int ks = NRS; ks < 8; ks++)
        wgmma_n40_tA(U0, make_desc(sb + SM_WO + (2 * wg) * 16384 + ks * 2048, 1024, 1024),
                     make_desc(sb + SM_VT + sl * 10240 + (ks >> 2) * 5120 + (ks & 3) * 32, 16, 1024), 1);
    wg_commit();
    const uint32_t tg = tag_of(s);
    uint32_t pb[5];
    float sm[4], sm2[4];
    auto get_p = [&]() {
        nbar_sync(9, 288);
        const uint32_t* pbs = reinterpret_cast<const uint32_t*>(smem + SM_PB);
        #pragma unroll
        for (int q = 0; q < 5; q++) pb[q] = pbs[q * 32 + lane];
        sm[0] = sm[1] = sm[2] = sm[3] = 0.f; sm2[0] = sm2[1] = sm2[2] = sm2[3] = 0.f;
        const uint32_t one = 0x3f803f80u;
        mma_bf16(sm, one, one, one, one, pb[0], pb[1]);
        mma_bf16(sm2, one, one, one, one, pb[2], pb[3]);
        mma_bf16(sm, one, one, 0u, 0u, pb[4], 0u);
    };
    const uint2* tpm = reinterpret_cast<const uint2*>(smem + SM_TPM) + (sl * 4 + 2 * wg) * 4 + warp;
    if (NT == 2) {
        wg_wait0();
        float U1[20];
        wg_fence();
        #pragma unroll
        for (int ks = 0; ks < 8; ks++)
            wgmma_n40_tA(U1, make_desc(sb + SM_WO + (2 * wg + 1) * 16384 + ks * 2048, 1024, 1024),
                         make_desc(sb + SM_VT + sl * 10240 + (ks >> 2) * 5120 + (ks & 3) * 32, 16, 1024), ks > 0);
        wg_commit();
        const uint2 off0 = tpm[0], off1 = tpm[4];
        get_p();
        float o0[4], o1[4];
        pu_mma(o0, U0, pb);
        wg_wait0();
        pu_mma(o1, U1, pb);
        const float2 inv = make_float2(rcp_approx(sm[0] + sm2[0]), rcp_approx(sm[1] + sm2[1]));
        if (wg == 0 && warp == 0) TR(8);
        pu_store(o0, inv, off0, lane, tg);
        pu_store(o1, inv, off1, lane, tg);
        if (wg == 0 && warp == 0) TR(6);
    } else {
        const uint2 off0 = tpm[0];
        wg_wait0();
        get_p();
        float o0[4];
        pu_mma(o0, U0, pb);
        const float2 inv = make_float2(rcp_approx(sm[0] + sm2[0]), rcp_approx(sm[1] + sm2[1]));
        pu_store(o0, inv, off0, lane, tg);
    }
}

__global__ void __cluster_dims__(3, 1, 1) __launch_bounds__(384, 1)
k_chain(const __grid_constant__ CUtensorMap xmap, const __grid_constant__ CUtensorMap wqmap, const __grid_constant__ CUtensorMap wkmap,
        const __grid_constant__ CUtensorMap wvmap, const __grid_constant__ CUtensorMap womap, const bf16* __restrict__ xptr, const bf16* __restrict__ mem0) {
    extern __shared__ __align__(1024) unsigned char smem[];
    const uint32_t sb = smem_u32(smem);
    const int tid = threadIdx.x, lane = tid & 31;
    const int wg = __shfl_sync(~0u, tid >> 7, 0), warp = __shfl_sync(~0u, (tid >> 5) & 3, 0);
    uint32_t rank; asm volatile("mov.u32 %0, %%cluster_ctarank;" : "=r"(rank));
    const int cta = blockIdx.x, h = cta / 3;
    asm volatile("griddepcontrol.launch_dependents;");
    if (tid == 0) {
        for (int i = 0; i < 2; i++) { mbar_init(sb + B_SC + 8 * i, rank < 2 ? 6 : 1); mbar_init(sb + B_V + 8 * i, 1); mbar_init(sb + B_X + 8 * i, 1); }
        mbar_init(sb + B_P, 1); mbar_init(sb + B_EXP, 1);
        asm volatile("fence.mbarrier_init.release.cluster;" ::: "memory");
    }
    if (tid < 80) asm volatile("prefetch.global.L2 [%0];" :: "l"(mem0 + tid * 64));
    if (h < 2) { for (int i = tid; i < 320; i += 384) asm volatile("prefetch.global.L2 [%0];" :: "l"(xptr + (size_t)h * 32 * DM + i * 64)); }
    {
        const int w12 = tid >> 5;
        if (lane == 0 && w12 < 7) {
            uint32_t* pp = (w12 < 6) ? g_pool + (size_t)(cta * 6 + w12) * 1024 + 512 : g_pool + (size_t)NPOOL * 1024 + (cta & 31) * 32 + (cta >> 5) * 8;
            const unsigned lat = probe_latency(pp, blockIdx.y);
            if (w12 < 6) g_cls[cta * 6 + w12] = lat > CAL_THR ? 1u : 0u; else g_side[cta] = lat > CAL_THR ? 1u : 0u;
        }
        __syncwarp();
        uint4* z = reinterpret_cast<uint4*>(g_pool + (size_t)cta * 6 * 1024);
        #pragma unroll
        for (int q = 0; q < 4; q++) z[tid + 384 * q] = make_uint4(0, 0, 0, 0);
        __threadfence();
        __syncwarp();
        if (lane == 0) atomicAdd(&g_calcnt, 1u);
    }
    __syncthreads();
    if (tid == 0) {
        const int ntile = (rank == 2) ? 4 : 3;
        const int tile0 = (rank == 2) ? 0 : (rank == 0 ? 4 : 7);
        mbar_expect_tx(sb + B_P, 163840 + ntile * 16384);
        const void* m0 = (rank == 2) ? &wvmap : &wqmap;
        const void* m1 = (rank == 2) ? &wvmap : &wkmap;
        const int c0 = h * DH + (rank == 1 ? 64 : 0), c1 = h * DH + (rank == 0 ? 0 : 64);
        for (int b = 0; b < 5; b++) {
            tma_load_2d(sb + b * 16384, m0, c0, b * 128, sb + B_P);
            tma_load_2d(sb + 81920 + b * 16384, m1, c1, b * 128, sb + B_P);
        }
        for (int lt = 0; lt < ntile; lt++) {
            tma_load_2d(sb + SM_WO + lt * 16384, &womap, (tile0 + lt) * 64, h * DH, sb + B_P);
            tma_load_2d(sb + SM_WO + lt * 16384 + 8192, &womap, (tile0 + lt) * 64, h * DH + 64, sb + B_P);
        }
    }
    {
        const int tile0 = (rank == 2) ? 0 : (rank == 0 ? 4 : 7);
        if (wg == 2) {
            const int ct = tid & 127;
            if (ct == 0) {
                const unsigned target = (*reinterpret_cast<volatile unsigned*>(&g_epoch) + 1u) * (96u * 12u);
                int guard = 0;
                while ((int)(ld_acquire(&g_calcnt) - target) < 0 && ++guard < (1 << 22)) {}
            }
            nbar_sync(4, 128);
            uint32_t* bm = reinterpret_cast<uint32_t*>(smem + SM_CAL);
            {
                unsigned v[5];
                #pragma unroll
                for (int q = 0; q < 5; q++) { const int b = ct + 128 * q; v[q] = (b < NPOOL) ? (__ldcg(&g_cls[b]) ^ __ldcg(&g_side[b / 6])) : 0u; }
                const unsigned sv = (ct < 96) ? __ldcg(&g_side[ct]) : 0u;
                #pragma unroll
                for (int q = 0; q < 5; q++) { const unsigned m = __ballot_sync(~0u, v[q] & 1u); if (lane == 0 && q * 4 + warp < 18) bm[q * 4 + warp] = m; }
                const unsigned m = __ballot_sync(~0u, sv & 1u);
                if (lane == 0 && warp < 3) bm[18 + warp] = m;
            }
            nbar_sync(4, 128);
            int nblk1 = 0;
            for (int i = 0; i < 18; i++) nblk1 += __popc(bm[i]);
            const unsigned red_last = (1u << (NRED - 64)) - 1u;
            const int nred1 = __popc(bm[18]) + __popc(bm[19]) + __popc(bm[20] & red_last);
            auto side_of = [&](int c) -> int { return (bm[18 + (c >> 5)] >> (c & 31)) & 1; };
            auto rank_of = [&](int c) -> int {
                int ones = 0;
                for (int i = 0; i < (c >> 5); i++) ones += __popc(bm[18 + i]);
                ones += __popc(bm[18 + (c >> 5)] & ((1u << (c & 31)) - 1u));
                return side_of(c) ? ones : c - ones;
            };
            auto nth = [&](int side, int idx) -> uint32_t {
                for (int i = 0; i < 18; i++) {
                    const unsigned m = side ? bm[i] : ~bm[i];
                    const int n = __popc(m);
                    if (idx < n) return (uint32_t)(i * 32 + __fns(m, 0, idx + 1));
                    idx -= n;
                }
                return 0u;
            };
            auto phys = [&](int side, int idx) -> uint32_t {
                const int c = side ? nblk1 : NPOOL - nblk1;
                return (idx < c) ? nth(side, idx) : nth(side ^ 1, (NPOOL - c) - 1 - (idx - c));
            };
            const int e = ct;
            if (e < 64) {
                const int slot = e >> 5, lt = (e >> 3) & 3, w = (e >> 1) & 3, hf = e & 1;
                const int tile = min(tile0 + lt, 9);
                const int r = 2 * (4 * tile + w) + hf;
                reinterpret_cast<uint32_t*>(smem + SM_TPM)[e] = phys(side_of(r), 4 * rank_of(r) + slot * 2 + (h >> 4)) * 4096u + (h & 15) * 256u;
            } else if (e < 68) {
                const int i = e - 64;
                reinterpret_cast<uint32_t*>(smem + SM_TRD)[i] = (cta < NRED) ? phys(side_of(cta), 4 * rank_of(cta) + i) * 4096u : 0u;
            } else if (e < 100) {
                const int i = e - 68, slot = i >> 3, rep = i & 7, side = (rep / RPS) & 1;
                reinterpret_cast<uint32_t*>(smem + SM_TPUB)[i] = phys(side, 4 * (side ? nred1 : NRED - nred1) + (slot * RPS + (rep % RPS)) * 3 + (cta >> 5)) * 4096u + (cta & 31) * 128u;
            } else if (e < 112) {
                const int i = e - 100, slot = i / 3, b = i % 3, side = side_of(cta);
                reinterpret_cast<uint32_t*>(smem + SM_TGAT)[slot * 4 + b] = phys(side, 4 * (side ? nred1 : NRED - nred1) + (slot * RPS + (h % RPS)) * 3 + b) * 4096u;
            }
        }
    }
    __syncthreads();
    mbar_wait_sleep(sb + B_P, 0);

    if (wg == 2) {
        asm volatile("setmaxnreg.dec.sync.aligned.u32 " COMM_REGS ";");
        const int ct = tid & 127;
        nbar_sync(5, 384);
        for (int c = ct; c < 640; c += 128) {
            int ks = c >> 4, hf = (c >> 3) & 1, r = c & 7;
            *reinterpret_cast<uint4*>(smem + SM_MEMB + c * 16) = *reinterpret_cast<const uint4*>(mem0 + r * DM + ks * 16 + hf * 8);
        }
        if (ct == 0) {
            for (int sg = 0; sg < 2; sg++) {
                mbar_expect_tx(sb + B_X + 8 * sg, 40960);
                tma_load_3d(sb + SM_XB + sg * 40960, &xmap, 0, sg * 32, 0, sb + B_X + 8 * sg);
            }
            mbar_expect_tx(sb + B_SC, rank < 2 ? 1280 : 2560);
            if (rank < 2) mbar_expect_tx(sb + B_V, 8192 + 2048);
        }
        nbar_sync(5, 384);
        cluster_sync_all();
        unsigned char* const pool = reinterpret_cast<unsigned char*>(g_pool);
        for (int s = 0; s < NSEG - 1; s++) {
            if (warp == 1) nbar_sync(12, 288);
            if (warp == 0) {
                const int g = lane >> 2, t = lane & 3;
                mbar_wait(sb + B_SC + 8 * (s & 1), (s >> 1) & 1);
                TR(5);
                const uint32_t sa = sb + SM_SC + (s & 1) * 2560 + (g * 40 + 2 * t) * 4;
                float v[5][2], u[5][2];
                #pragma unroll
                for (int q = 0; q < 5; q++) {
                    asm volatile("ld.shared.v2.f32 {%0,%1}, [%2];" : "=f"(v[q][0]), "=f"(v[q][1]) : "r"(sa + 32 * q) : "memory");
                    asm volatile("ld.shared.v2.f32 {%0,%1}, [%2];" : "=f"(u[q][0]), "=f"(u[q][1]) : "r"(sa + 1280 + 32 * q) : "memory");
                }
                float mx = -3.0e38f;
                #pragma unroll
                for (int q = 0; q < 5; q++) {
                    v[q][0] += u[q][0]; v[q][1] += u[q][1];
                    mx = fmaxf(mx, fmaxf(v[q][0], v[q][1]));
                }
                mx = fmaxf(mx, __shfl_xor_sync(~0u, mx, 1));
                mx = fmaxf(mx, __shfl_xor_sync(~0u, mx, 2));
                const float sc2 = 0.08838834764831845f * 1.4426950408889634f;
                const float mxs = mx * sc2;
                uint32_t* pbs = reinterpret_cast<uint32_t*>(smem + SM_PB);
                #pragma unroll
                for (int q = 0; q < 5; q++) {
                    const float e0 = ex2_approx(fmaf(v[q][0], sc2, -mxs)), e1 = ex2_approx(fmaf(v[q][1], sc2, -mxs));
                    pbs[q * 32 + lane] = pack_bf16(e0, e1);
                }
                __syncwarp();
                TR(0);
                nbar_arrive(9, 288);
            } else if (warp == 1 && lane == 0) {
                if (s + 1 < NSEG - 1) {
                    mbar_expect_tx(sb + B_SC + 8 * ((s + 1) & 1), rank < 2 ? 1280 : 2560);
                    if (rank < 2) mbar_expect_tx(sb + B_V + 8 * ((s + 1) & 1), 8192 + 2048);
                }
                if (s + 2 < NSEG) {
                    mbar_expect_tx(sb + B_X + 8 * (s & 1), 40960);
                    tma_load_3d(sb + SM_XB + (s & 1) * 40960, &xmap, 0, (s + 2) * 32, 0, sb + B_X + 8 * (s & 1));
                }
                export_issue(sb, s, h, rank);
                if (s >= NSEG - 4) export_signal(s, h);
            }
            __syncwarp();
            nbar_sync(3, 384);
            const uint32_t tg = tag_of(s);
            if (cta < NRED) {
                const unsigned char* base = pool + reinterpret_cast<const uint32_t*>(smem + SM_TRD)[(s & 1) * 2 + (warp >> 1)] + (warp & 1) * 2048 + lane * 16;
                uint4 v[4]; int guard = 0;
                #pragma unroll
                for (int j = 0; j < 4; j++) v[j] = make_uint4(0, 0, 0, 0);
                uint32_t pend = 0xF;
                do {
                    #pragma unroll
                    for (int j = 0; j < 4; j++) if (pend & (1u << j)) v[j] = ld_relaxed4(base + j * 512);
                    #pragma unroll
                    for (int j = 0; j < 4; j++)
                        if (((v[j].x & 3) == tg) && ((v[j].y & 3) == tg) && ((v[j].z & 3) == tg) && ((v[j].w & 3) == tg)) pend &= ~(1u << j);
                } while (__any_sync(~0u, pend != 0) && ++guard < (1 << 20));
                if (warp == 0) TR(9);
                float a0 = 0, a1 = 0, a2 = 0, a3 = 0;
                #pragma unroll
                for (int j = 0; j < 4; j++) { a0 += __uint_as_float(v[j].x); a1 += __uint_as_float(v[j].y); a2 += __uint_as_float(v[j].z); a3 += __uint_as_float(v[j].w); }
                a0 += __shfl_xor_sync(~0u, a0, 16); a1 += __shfl_xor_sync(~0u, a1, 16); a2 += __shfl_xor_sync(~0u, a2, 16); a3 += __shfl_xor_sync(~0u, a3, 16);
                float* cr = reinterpret_cast<float*>(smem + SM_CRED);
                if (lane < 16) *reinterpret_cast<float4*>(cr + warp * 64 + lane * 4) = make_float4(a0, a1, a2, a3);
                nbar_sync(4, 128);
                {
                    int rho = lane >> 2, pp = lane & 3;
                    int i0 = ((2 * pp) * 4 + (rho >> 1)) * 2 + (rho & 1), i1 = i0 + 8;
                    uint32_t wv = pack_bf16((cr[i0] + cr[64 + i0]) + (cr[128 + i0] + cr[192 + i0]), (cr[i1] + cr[64 + i1]) + (cr[128 + i1] + cr[192 + i1]));
                    if (wv == 0) wv = 0x8000u;
                    if (warp == 0) TR(10);
                    const uint32_t* tp = reinterpret_cast<const uint32_t*>(smem + SM_TPUB) + warp;
                    if (warp < 2 * RPS) st_relaxed1(pool + tp[((s + 1) & 3) * 8] + lane * 4, wv);
                    if (RPS == 4) st_relaxed1(pool + tp[((s + 1) & 3) * 8 + 4] + lane * 4, wv);
                    if (warp < 2 * RPS) st_relaxed1(pool + tp[(s & 3) * 8] + lane * 4, 0u);
                    if (RPS == 4) st_relaxed1(pool + tp[(s & 3) * 8 + 4] + lane * 4, 0u);
                }
            }
            {
                const int c0 = warp * 160 + lane;
                const uint32_t* tg3 = reinterpret_cast<const uint32_t*>(smem + SM_TGAT) + ((s + 1) & 3) * 4;
                const uint32_t g0 = tg3[0], g1 = tg3[1], g2 = tg3[2];
                uint4 v[5]; int guard = 0;
                #pragma unroll
                for (int j = 0; j < 5; j++) v[j] = make_uint4(0, 0, 0, 0);
                uint32_t pend = 0x1F;
                do {
                    #pragma unroll
                    for (int j = 0; j < 5; j++) {
                        const int c = c0 + 32 * j;
                        if (pend & (1u << j)) v[j] = ld_relaxed4(pool + ((c >> 8) == 0 ? g0 : ((c >> 8) == 1 ? g1 : g2)) + (c & 255) * 16);
                    }
                    #pragma unroll
                    for (int j = 0; j < 5; j++) if (v[j].x && v[j].y && v[j].z && v[j].w) pend &= ~(1u << j);
                } while (__any_sync(~0u, pend != 0) && ++guard < (1 << 20));
                #pragma unroll
                for (int j = 0; j < 5; j++) *reinterpret_cast<uint4*>(smem + SM_MEMB + (c0 + 32 * j) * 16) = v[j];
                if (warp == 0) TR(11);
                if (warp == 3) TR(12);
                nbar_arrive(warp < 2 ? 7 + warp : 8 + warp, 160);
            }
            if (warp == 1 && lane == 0 && s < NSEG - 4) export_signal(s, h);
            __syncwarp();
        }
        if (warp == 1) { nbar_sync(12, 288); if (lane == 0) { export_issue(sb, NSEG - 1, h, rank); export_signal(NSEG - 1, h); } }
        __syncwarp();
        nbar_sync(3, 384);
        __syncwarp();
        cluster_sync_all();
    } else {
        asm volatile("setmaxnreg.inc.sync.aligned.u32 232;");
        const int wtid = tid & 127;
        const int cw = wg * 4 + warp;
        uint32_t areg[2][20][4];
        #pragma unroll
        for (int mt = 0; mt < 2; mt++)
            #pragma unroll
            for (int kk = 0; kk < 20; kk++) {
                int mi = lane >> 3;
                int row = 16 * (20 * wg + kk) + (mi >> 1) * 8 + (lane & 7);
                int chunk = 2 * warp + (mi & 1);
                ldsm4t(areg[mt][kk], sb + mt * 81920 + row * 128 + ((chunk ^ (row & 7)) << 4));
            }
        nbar_sync(5, 384);
        nbar_sync(5, 384);
        cluster_sync_all();

        for (int s = -1; s < NSEG; s++) {
            const int sl = s & 1;
            if (s >= 0) {
            if (s > 0) nbar_sync(7 + 3 * wg, 160);
            float fin[4];
            {
                float acc[2][2][4];
                #pragma unroll
                for (int i = 0; i < 2; i++)
                    #pragma unroll
                    for (int j = 0; j < 2; j++) { acc[i][j][0] = acc[i][j][1] = acc[i][j][2] = acc[i][j][3] = 0.f; }
                uint32_t b[3][4];
                const uint32_t mb = sb + SM_MEMB + (20 * wg) * 256 + lane * 16;
                ldsm4(b[0], mb); ldsm4(b[1], mb + 512);
                #pragma unroll
                for (int kp = 0; kp < 10; kp++) {
                    if (kp == 3 && s > 0) nbar_sync(8 + 3 * wg, 160);
                    if (kp + 2 < 10) ldsm4(b[(kp + 2) % 3], mb + (kp + 2) * 512);
                    const uint32_t (&bb)[4] = b[kp % 3];
                    mma_bf16(acc[0][0], areg[0][2 * kp][0], areg[0][2 * kp][1], areg[0][2 * kp][2], areg[0][2 * kp][3], bb[0], bb[1]);
                    mma_bf16(acc[1][0], areg[1][2 * kp][0], areg[1][2 * kp][1], areg[1][2 * kp][2], areg[1][2 * kp][3], bb[0], bb[1]);
                    mma_bf16(acc[0][1], areg[0][2 * kp + 1][0], areg[0][2 * kp + 1][1], areg[0][2 * kp + 1][2], areg[0][2 * kp + 1][3], bb[2], bb[3]);
                    mma_bf16(acc[1][1], areg[1][2 * kp + 1][0], areg[1][2 * kp + 1][1], areg[1][2 * kp + 1][2], areg[1][2 * kp + 1][3], bb[2], bb[3]);
                }
                float4* red = reinterpret_cast<float4*>(smem + SM_RED);
                float m0[4], m1[4];
                #pragma unroll
                for (int i = 0; i < 4; i++) { m0[i] = acc[0][0][i] + acc[0][1][i]; m1[i] = acc[1][0][i] + acc[1][1][i]; }
                red[(wg ^ 1) * 128 + wtid] = wg == 0 ? make_float4(m1[0], m1[1], m1[2], m1[3]) : make_float4(m0[0], m0[1], m0[2], m0[3]);
                nbar_sync(1, 256);
                float4 r = red[wg * 128 + wtid];
                fin[0] = (wg == 0 ? m0[0] : m1[0]) + r.x; fin[1] = (wg == 0 ? m0[1] : m1[1]) + r.y;
                fin[2] = (wg == 0 ? m0[2] : m1[2]) + r.z; fin[3] = (wg == 0 ? m0[3] : m1[3]) + r.w;
            }
            if (cw == 0) TR(1);
            {
                uint32_t p0 = pack_bf16(fin[0], fin[1]), p1 = pack_bf16(fin[2], fin[3]);
                const uint32_t doff = (rank == 2) ? SM_VT + sl * 10240 + wg * 5120 : (wg == 0 ? SM_QS : SM_KT + sl * 5120);
                const int r = lane & 7, chunk = 2 * warp + ((lane >> 3) & 1);
                const uint32_t coff = doff + r * 128 + ((chunk ^ r) << 4);
                stsm2t(sb + coff, p0, p1);
                if (rank == 2 && s < NSEG - 1) {
                    __syncwarp();
                    const uint4 v = *reinterpret_cast<const uint4*>(smem + coff);
                    const uint32_t rb = mapa(sb, lane >> 4);
                    st_async4u(rb + coff, v, rb + B_V + 8 * sl);
                }
            }
            fence_async();
            nbar_sync(1, 256);
            nbar_arrive(12, 288);
            if (cw == 0) TR(2);
            if (rank < 2 && s < NSEG - 1) {
                if (wg == 1) score_tile(sb, sl, 1 + warp, lane, rank);
                else if (warp == 0) score_tile(sb, sl, 0, lane, rank);
            }
            if (s == NSEG - 1) break;
            if (cw == 0) TR(3);
            if (wg == 0 || rank == 2) u_pass<2>(smem, sb, s, rank, wg, warp, lane);
            else                      u_pass<1>(smem, sb, s, rank, wg, warp, lane);
            if (cw == 0) TR(7);
            nbar_arrive(3, 384);
            }
            {
                const int sn = s + 1, sln = sn & 1;
                mbar_wait(sb + B_X + 8 * sln, (sn >> 1) & 1);
                float acc[2][16];
                wg_fence();
                #pragma unroll
                for (int mt = 0; mt < 2; mt++)
                    #pragma unroll
                    for (int kk = 0; kk < 20; kk++) {
                        uint64_t db = make_desc(sb + SM_XB + sln * 40960 + (5 * wg + (kk >> 2)) * 4096 + (kk & 3) * 32, 16, 1024);
                        wgmma_n32_rs(acc[mt], areg[mt][kk], db, kk > 0);
                    }
                wg_commit();
                if (cw == 0 && s >= 0) TR(14);
                wg_wait0();
                if (cw == 0 && s >= 0) TR(15);
                float4* red = reinterpret_cast<float4*>(smem + SM_RED);
                #pragma unroll
                for (int j = 0; j < 4; j++) {
                    red[((wg ^ 1) * 4 + j) * 128 + wtid] = make_float4(wg == 0 ? acc[1][4 * j] : acc[0][4 * j], wg == 0 ? acc[1][4 * j + 1] : acc[0][4 * j + 1],
                                                                       wg == 0 ? acc[1][4 * j + 2] : acc[0][4 * j + 2], wg == 0 ? acc[1][4 * j + 3] : acc[0][4 * j + 3]);
                }
                if (s >= 0) mbar_wait(sb + B_EXP, s & 1);
                nbar_sync(1, 256);
                uint32_t pk[8];
                #pragma unroll
                for (int j = 0; j < 4; j++) {
                    float4 r = red[(wg * 4 + j) * 128 + wtid];
                    pk[2 * j] = pack_bf16((wg == 0 ? acc[0][4 * j] : acc[1][4 * j]) + r.x, (wg == 0 ? acc[0][4 * j + 1] : acc[1][4 * j + 1]) + r.y);
                    pk[2 * j + 1] = pack_bf16((wg == 0 ? acc[0][4 * j + 2] : acc[1][4 * j + 2]) + r.z, (wg == 0 ? acc[0][4 * j + 3] : acc[1][4 * j + 3]) + r.w);
                }
                const uint32_t dst = (rank == 2) ? sb + SM_VT + sln * 10240 + wg * 5120 + 1024 : (wg == 0 ? sb + SM_QT : sb + SM_KT + sln * 5120 + 1024);
                #pragma unroll
                for (int jj = 0; jj < 2; jj++) {
                    int mi = lane >> 3, tok = 8 * (2 * jj + (mi >> 1)) + (lane & 7), chunk = 2 * warp + (mi & 1);
                    stsm4t(dst + tok * 128 + ((chunk ^ (tok & 7)) << 4), pk[4 * jj], pk[4 * jj + 1], pk[4 * jj + 2], pk[4 * jj + 3]);
                }
                fence_async();
                nbar_sync(1, 256);
                if (rank == 2 && lane == 0 && cw < 4 && sn < NSEG - 1) {
                    const uint32_t off = SM_VT + sln * 10240 + (cw & 1) * 5120 + 1024;
                    const uint32_t rb = mapa(sb, cw >> 1);
                    bulk_s2c(rb + off, sb + off, 4096, rb + B_V + 8 * sln);
                }
                if (cw == 0 && s >= 0) TR(13);
            }
        }
        nbar_arrive(3, 384);
        __syncwarp();
        cluster_sync_all();
    }
}

#define NAUX 36
__device__ __align__(1024) bf16 g_Oimg[16 * 64 * 128 * 64];
__device__ float    g_part[4 * SEQ * DM];
__device__ float    g_part31[3 * 16 * 64 * DM];
__device__ unsigned g_ocnt[32];
__device__ unsigned g_gcnt[32][2];
__device__ unsigned g_ssmcnt, g_auxdone, g_taskctr, g_gemmctr;
#define NATT 8
#define ATR(i) do {} while (0)
#define ATRID(i, id) do {} while (0)

__device__ __forceinline__ void wait_counter(const unsigned* p, unsigned target) {
    int guard = 0;
    while ((int)(ld_acquire(p) - target) < 0 && ++guard < (1 << 22)) __nanosleep(64);
}
__device__ __forceinline__ void fence_async_all() { asm volatile("fence.proxy.async;" ::: "memory"); }
template <int OFF>
__device__ __forceinline__ void wgmma_n192_tB(float (&d)[160], uint64_t da, uint64_t db) {
    asm volatile("wgmma.mma_async.sync.aligned.m64n192k16.f32.bf16.bf16 {%0,%1,%2,%3,%4,%5,%6,%7,%8,%9,%10,%11,%12,%13,%14,%15,%16,%17,%18,%19,%20,%21,%22,%23,%24,%25,%26,%27,%28,%29,%30,%31,%32,%33,%34,%35,%36,%37,%38,%39,%40,%41,%42,%43,%44,%45,%46,%47,%48,%49,%50,%51,%52,%53,%54,%55,%56,%57,%58,%59,%60,%61,%62,%63,%64,%65,%66,%67,%68,%69,%70,%71,%72,%73,%74,%75,%76,%77,%78,%79,%80,%81,%82,%83,%84,%85,%86,%87,%88,%89,%90,%91,%92,%93,%94,%95}, %96, %97, 1, 1, 1, 0, 1;\n"
        : "+f"(d[OFF + 0]), "+f"(d[OFF + 1]), "+f"(d[OFF + 2]), "+f"(d[OFF + 3]), "+f"(d[OFF + 4]), "+f"(d[OFF + 5]), "+f"(d[OFF + 6]), "+f"(d[OFF + 7]), "+f"(d[OFF + 8]), "+f"(d[OFF + 9]), "+f"(d[OFF + 10]), "+f"(d[OFF + 11]), "+f"(d[OFF + 12]), "+f"(d[OFF + 13]), "+f"(d[OFF + 14]), "+f"(d[OFF + 15]), "+f"(d[OFF + 16]), "+f"(d[OFF + 17]), "+f"(d[OFF + 18]), "+f"(d[OFF + 19]), "+f"(d[OFF + 20]), "+f"(d[OFF + 21]), "+f"(d[OFF + 22]), "+f"(d[OFF + 23]), "+f"(d[OFF + 24]), "+f"(d[OFF + 25]), "+f"(d[OFF + 26]), "+f"(d[OFF + 27]), "+f"(d[OFF + 28]), "+f"(d[OFF + 29]), "+f"(d[OFF + 30]), "+f"(d[OFF + 31]), "+f"(d[OFF + 32]), "+f"(d[OFF + 33]), "+f"(d[OFF + 34]), "+f"(d[OFF + 35]), "+f"(d[OFF + 36]), "+f"(d[OFF + 37]), "+f"(d[OFF + 38]), "+f"(d[OFF + 39]), "+f"(d[OFF + 40]), "+f"(d[OFF + 41]), "+f"(d[OFF + 42]), "+f"(d[OFF + 43]), "+f"(d[OFF + 44]), "+f"(d[OFF + 45]), "+f"(d[OFF + 46]), "+f"(d[OFF + 47]), "+f"(d[OFF + 48]), "+f"(d[OFF + 49]), "+f"(d[OFF + 50]), "+f"(d[OFF + 51]), "+f"(d[OFF + 52]), "+f"(d[OFF + 53]), "+f"(d[OFF + 54]), "+f"(d[OFF + 55]), "+f"(d[OFF + 56]), "+f"(d[OFF + 57]), "+f"(d[OFF + 58]), "+f"(d[OFF + 59]), "+f"(d[OFF + 60]), "+f"(d[OFF + 61]), "+f"(d[OFF + 62]), "+f"(d[OFF + 63]), "+f"(d[OFF + 64]), "+f"(d[OFF + 65]), "+f"(d[OFF + 66]), "+f"(d[OFF + 67]), "+f"(d[OFF + 68]), "+f"(d[OFF + 69]), "+f"(d[OFF + 70]), "+f"(d[OFF + 71]), "+f"(d[OFF + 72]), "+f"(d[OFF + 73]), "+f"(d[OFF + 74]), "+f"(d[OFF + 75]), "+f"(d[OFF + 76]), "+f"(d[OFF + 77]), "+f"(d[OFF + 78]), "+f"(d[OFF + 79]), "+f"(d[OFF + 80]), "+f"(d[OFF + 81]), "+f"(d[OFF + 82]), "+f"(d[OFF + 83]), "+f"(d[OFF + 84]), "+f"(d[OFF + 85]), "+f"(d[OFF + 86]), "+f"(d[OFF + 87]), "+f"(d[OFF + 88]), "+f"(d[OFF + 89]), "+f"(d[OFF + 90]), "+f"(d[OFF + 91]), "+f"(d[OFF + 92]), "+f"(d[OFF + 93]), "+f"(d[OFF + 94]), "+f"(d[OFF + 95])
        : "l"(da), "l"(db));
}
template <int OFF>
__device__ __forceinline__ void wgmma_n128_tB(float (&d)[160], uint64_t da, uint64_t db) {
    asm volatile("wgmma.mma_async.sync.aligned.m64n128k16.f32.bf16.bf16 {%0,%1,%2,%3,%4,%5,%6,%7,%8,%9,%10,%11,%12,%13,%14,%15,%16,%17,%18,%19,%20,%21,%22,%23,%24,%25,%26,%27,%28,%29,%30,%31,%32,%33,%34,%35,%36,%37,%38,%39,%40,%41,%42,%43,%44,%45,%46,%47,%48,%49,%50,%51,%52,%53,%54,%55,%56,%57,%58,%59,%60,%61,%62,%63}, %64, %65, 1, 1, 1, 0, 1;\n"
        : "+f"(d[OFF + 0]), "+f"(d[OFF + 1]), "+f"(d[OFF + 2]), "+f"(d[OFF + 3]), "+f"(d[OFF + 4]), "+f"(d[OFF + 5]), "+f"(d[OFF + 6]), "+f"(d[OFF + 7]), "+f"(d[OFF + 8]), "+f"(d[OFF + 9]), "+f"(d[OFF + 10]), "+f"(d[OFF + 11]), "+f"(d[OFF + 12]), "+f"(d[OFF + 13]), "+f"(d[OFF + 14]), "+f"(d[OFF + 15]), "+f"(d[OFF + 16]), "+f"(d[OFF + 17]), "+f"(d[OFF + 18]), "+f"(d[OFF + 19]), "+f"(d[OFF + 20]), "+f"(d[OFF + 21]), "+f"(d[OFF + 22]), "+f"(d[OFF + 23]), "+f"(d[OFF + 24]), "+f"(d[OFF + 25]), "+f"(d[OFF + 26]), "+f"(d[OFF + 27]), "+f"(d[OFF + 28]), "+f"(d[OFF + 29]), "+f"(d[OFF + 30]), "+f"(d[OFF + 31]), "+f"(d[OFF + 32]), "+f"(d[OFF + 33]), "+f"(d[OFF + 34]), "+f"(d[OFF + 35]), "+f"(d[OFF + 36]), "+f"(d[OFF + 37]), "+f"(d[OFF + 38]), "+f"(d[OFF + 39]), "+f"(d[OFF + 40]), "+f"(d[OFF + 41]), "+f"(d[OFF + 42]), "+f"(d[OFF + 43]), "+f"(d[OFF + 44]), "+f"(d[OFF + 45]), "+f"(d[OFF + 46]), "+f"(d[OFF + 47]), "+f"(d[OFF + 48]), "+f"(d[OFF + 49]), "+f"(d[OFF + 50]), "+f"(d[OFF + 51]), "+f"(d[OFF + 52]), "+f"(d[OFF + 53]), "+f"(d[OFF + 54]), "+f"(d[OFF + 55]), "+f"(d[OFF + 56]), "+f"(d[OFF + 57]), "+f"(d[OFF + 58]), "+f"(d[OFF + 59]), "+f"(d[OFF + 60]), "+f"(d[OFF + 61]), "+f"(d[OFF + 62]), "+f"(d[OFF + 63])
        : "l"(da), "l"(db));
}
__device__ __forceinline__ void stsm4(uint32_t addr, uint32_t r0, uint32_t r1, uint32_t r2, uint32_t r3) {
    asm volatile("stmatrix.sync.aligned.m8n8.x4.shared.b16 [%0], {%1,%2,%3,%4};" :: "r"(addr), "r"(r0), "r"(r1), "r"(r2), "r"(r3) : "memory");
}

#define AX_BAR   0
#define NST_G 4
#define AX_EMPTY (AX_BAR + 16 + 8 * NST_G)
#define AX_DONE  (AX_EMPTY + 8 * NST_G)
#define AX_DATA  1024
#define AX_UNIT  28672
#define AX_STAGE 57344
#define AX_TOTAL (AX_DATA + 8 * AX_UNIT)

__device__ __forceinline__ void attn_compute(unsigned char* smem, uint32_t sb, uint32_t buf, int warp, int lane);
__device__ __forceinline__ void attn_producer(unsigned char* smem, int hg, unsigned epoch) {
    const uint32_t sb = smem_u32(smem);
    const int lane = threadIdx.x & 31;
    {
        for (int s = 0; s < NSEG; s++) {
            const uint32_t buf = AX_DATA + (s & 1) * (4 * AX_UNIT), bar = sb + AX_BAR + 8 * (s & 1);
            if (lane < 4) wait_counter(&g_flag[s][4 * hg + lane], (epoch + 1) * 3u);
            if (lane == 4) mbar_wait_sleep(sb + AX_EMPTY + 8 * (s & 1), ((s >> 1) & 1) ^ 1);
            __syncwarp();
            if (lane == 0) mbar_expect_tx(bar, 4 * AX_UNIT);
            __syncwarp();
            if (lane < 24) {
                fence_async_all();
                const int u = lane / 6, r = lane % 6, hf = r & 1, kind = r >> 1;
                const uint32_t ub = sb + buf + u * AX_UNIT;
                const size_t img = ((size_t)(s * NH + 4 * hg + u) * 2) + hf;
                if (kind == 0) bulk_g2s(ub + hf * 4096, g_Qimg + img * 2048, 4096, bar);
                else if (kind == 1) bulk_g2s(ub + 8192 + hf * 5120, g_Kimg + img * 2560, 5120, bar);
                else bulk_g2s(ub + 18432 + hf * 5120, g_Vimg + img * 2560, 5120, bar);
            }
            __syncwarp();
        }
    }
}
__device__ __forceinline__ void attn_loop(unsigned char* smem, int hg, unsigned epoch) {
    const uint32_t sb = smem_u32(smem);
    const int tid = threadIdx.x, warp = tid >> 5, lane = tid & 31;
    for (int s = 0; s < NSEG; s++) {
        const uint32_t buf = AX_DATA + (s & 1) * (4 * AX_UNIT), bar = sb + AX_BAR + 8 * (s & 1);
        mbar_wait_sleep(bar, (s >> 1) & 1);
        if (s >= 36) ATR(2 + 2 * (s - 36));
        attn_compute(smem, sb, buf, warp, lane);
        if (s >= 36) ATR(3 + 2 * (s - 36));
        fence_async();
        __syncwarp();
        if (lane == 0) mbar_arrive(sb + AX_EMPTY + 16 + 8 * (s & 1));
    }
}
__device__ __forceinline__ void attn_storer(unsigned char* smem, int hg) {
    const uint32_t sb = smem_u32(smem);
    const int lane = threadIdx.x & 31;
    for (int s = 0; s < NSEG; s++) {
        const uint32_t buf = AX_DATA + (s & 1) * (4 * AX_UNIT);
        mbar_wait_sleep(sb + AX_EMPTY + 16 + 8 * (s & 1), (s >> 1) & 1);
        if (lane < 8) {
            const int uu = lane >> 1, hf = lane & 1, hh = 4 * hg + uu;
            bulk_s2g(g_Oimg + (((size_t)(s >> 2) * 64 + hh * 2 + hf) * 128 + (s & 3) * 32) * 64, sb + buf + uu * AX_UNIT + hf * 4096, 4096);
            bulk_commit();
            bulk_wait_read0();
            mbar_arrive(sb + AX_EMPTY + 8 * (s & 1));
            bulk_wait0();
            fence_async_all();
            __threadfence();
            atomicAdd(&g_ocnt[s >> 1], 1u);
        }
        __syncwarp();
    }
}
__device__ __forceinline__ void attn_compute(unsigned char* smem, uint32_t sb, uint32_t buf, int warp, int lane) {
    const int g = lane >> 2, t = lane & 3;
    const int u = warp >> 1, qh = warp & 1;
    const uint32_t ub = sb + buf + u * AX_UNIT;
    float sc[5][4];
    #pragma unroll
    for (int j = 0; j < 5; j++) { sc[j][0] = sc[j][1] = sc[j][2] = sc[j][3] = 0.f; }
    #pragma unroll
    for (int ks = 0; ks < 8; ks++) {
        const int hf = ks >> 2, c0 = (ks & 3) * 2;
        uint32_t a[4];
        { int mi = lane >> 3, row = 16 * qh + (mi & 1) * 8 + (lane & 7), chunk = c0 + (mi >> 1);
          ldsm4(a, ub + hf * 4096 + row * 128 + ((chunk ^ (row & 7)) << 4)); }
        #pragma unroll
        for (int jp = 0; jp < 3; jp++) {
            uint32_t b[4];
            int mi = lane >> 3, nt = 2 * jp + (mi >> 1); if (nt > 4) nt = 4;
            int row = 8 * nt + (lane & 7), chunk = c0 + (mi & 1);
            ldsm4(b, ub + 8192 + hf * 5120 + row * 128 + ((chunk ^ (row & 7)) << 4));
            mma_bf16(sc[2 * jp], a[0], a[1], a[2], a[3], b[0], b[1]);
            if (jp < 2) mma_bf16(sc[2 * jp + 1], a[0], a[1], a[2], a[3], b[2], b[3]);
        }
    }
    uint32_t pa[3][4];
    {
        const float sc2 = 0.08838834764831845f * 1.4426950408889634f;
        float mx0 = -3.0e38f, mx1 = -3.0e38f;
        const int q0 = 16 * qh + g, q1 = q0 + 8;
        #pragma unroll
        for (int j = 0; j < 5; j++)
            #pragma unroll
            for (int e = 0; e < 2; e++) {
                int key = 8 * j + 2 * t + e - 8;
                sc[j][e] = (key <= q0) ? sc[j][e] * sc2 : -3.0e38f;
                sc[j][2 + e] = (key <= q1) ? sc[j][2 + e] * sc2 : -3.0e38f;
                mx0 = fmaxf(mx0, sc[j][e]); mx1 = fmaxf(mx1, sc[j][2 + e]);
            }
        mx0 = fmaxf(mx0, __shfl_xor_sync(~0u, mx0, 1)); mx0 = fmaxf(mx0, __shfl_xor_sync(~0u, mx0, 2));
        mx1 = fmaxf(mx1, __shfl_xor_sync(~0u, mx1, 1)); mx1 = fmaxf(mx1, __shfl_xor_sync(~0u, mx1, 2));
        float s0 = 0.f, s1 = 0.f;
        #pragma unroll
        for (int j = 0; j < 5; j++)
            #pragma unroll
            for (int e = 0; e < 2; e++) {
                sc[j][e] = ex2_approx(sc[j][e] - mx0); sc[j][2 + e] = ex2_approx(sc[j][2 + e] - mx1);
                s0 += sc[j][e]; s1 += sc[j][2 + e];
            }
        s0 += __shfl_xor_sync(~0u, s0, 1); s0 += __shfl_xor_sync(~0u, s0, 2);
        s1 += __shfl_xor_sync(~0u, s1, 1); s1 += __shfl_xor_sync(~0u, s1, 2);
        const float i0 = __frcp_rn(s0), i1 = __frcp_rn(s1);
        #pragma unroll
        for (int k = 0; k < 3; k++) {
            pa[k][0] = pack_bf16(sc[2 * k][0] * i0, sc[2 * k][1] * i0);
            pa[k][1] = pack_bf16(sc[2 * k][2] * i1, sc[2 * k][3] * i1);
            if (k < 2) { pa[k][2] = pack_bf16(sc[2 * k + 1][0] * i0, sc[2 * k + 1][1] * i0); pa[k][3] = pack_bf16(sc[2 * k + 1][2] * i1, sc[2 * k + 1][3] * i1); }
            else { pa[k][2] = 0u; pa[k][3] = 0u; }
        }
    }
    __syncwarp();
    nbar_sync(5 + u, 64);
    #pragma unroll
    for (int np = 0; np < 8; np++) {
        const int hf = np >> 2, c0 = (np & 3) * 2;
        float o0[4] = {0, 0, 0, 0}, o1[4] = {0, 0, 0, 0};
        #pragma unroll
        for (int k = 0; k < 3; k++) {
            uint32_t b[4];
            int mi = lane >> 3;
            int row = 16 * k + (mi & 1) * 8 + (lane & 7); if (row > 39) row = 39 - 7 + (lane & 7);
            int chunk = c0 + (mi >> 1);
            ldsm4t(b, ub + 18432 + hf * 5120 + row * 128 + ((chunk ^ (row & 7)) << 4));
            mma_bf16(o0, pa[k][0], pa[k][1], pa[k][2], pa[k][3], b[0], k < 2 ? b[1] : 0u);
            mma_bf16(o1, pa[k][0], pa[k][1], pa[k][2], pa[k][3], b[2], k < 2 ? b[3] : 0u);
        }
        int mi = lane >> 3, row = 16 * qh + (mi & 1) * 8 + (lane & 7), chunk = c0 + (mi >> 1);
        stsm4(ub + hf * 4096 + row * 128 + ((chunk ^ (row & 7)) << 4), pack_bf16(o0[0], o0[1]), pack_bf16(o0[2], o0[3]), pack_bf16(o1[0], o1[1]), pack_bf16(o1[2], o1[3]));
    }
}

template <int V> struct IntC { static constexpr int value = V; };
struct Task { int type, rb, c, k0, nch, plane; };
#define NFINE 29
#define NKP 8
#define KPC (64 / NKP + (64 % NKP ? 1 : 0))
#define NGEMM (8 + 144 + 8 * 2 + 4 + 8 * 4 + 2 * NKP * 3 + 16 * 3)
__device__ __forceinline__ Task decode_task(int j) {
    Task t; t.type = 0; t.rb = 0; t.c = 0; t.k0 = 0; t.nch = 16; t.plane = 0;
    auto H = [&](int rb, int i) { t.type = 1; t.rb = rb; t.c = i & 1; t.plane = i >> 1; t.k0 = t.plane * 16; };
    auto CF = [&](int rb, int i) { t.type = 2; t.rb = rb; t.c = i & 1; t.k0 = rb * 64 + (i >> 1) * 16; t.nch = 16; };
    auto H13 = [&](int rb, int i) { t.type = 1; t.rb = rb; t.c = i & 1; t.plane = i >> 1; t.k0 = t.plane * KPC; t.nch = (t.plane == NKP - 1) ? 64 - (NKP - 1) * KPC : KPC; };
    auto C13 = [&](int rb, int i) { t.type = 2; t.rb = rb; t.c = i & 1; t.k0 = rb * 64 + (i >> 1) * 8; t.nch = 8; };
    if (j >= NGEMM) { t.type = 3; return t; }
    if (j < 8) { t.c = j & 1; t.plane = j >> 1; t.k0 = t.plane * 16; return t; }
    j -= 8;
    if (j < 144) {
        const int q = j / 12, r = j % 12;
        if (r < 8) { t.rb = 2 * (q + 1); t.c = r & 1; t.plane = r >> 1; t.k0 = t.plane * 16; }
        else { t.type = 2; t.rb = 2 * q + ((r - 8) >> 1); t.c = r & 1; t.k0 = t.rb * 64; t.nch = 64; }
        return t;
    }
    j -= 144;
    if (j < 8) { H(26, j); return t; }
    j -= 8;
    if (j < 8) { H(27, j); return t; }
    j -= 8;
    if (j < 4) { t.type = 2; t.rb = 24 + (j >> 1); t.c = j & 1; t.k0 = t.rb * 64; t.nch = 64; return t; }
    j -= 4;
    if (j < 8) { H(28, j); return t; }
    j -= 8;
    if (j < 8) { CF(26, j); return t; }
    j -= 8;
    if (j < 8) { CF(27, j); return t; }
    j -= 8;
    if (j < 2 * NKP) { H13(29, j); return t; }
    j -= 2 * NKP;
    if (j < 8) { CF(28, j); return t; }
    j -= 8;
    if (j < 2 * NKP) { H13(30, j); return t; }
    j -= 2 * NKP;
    if (j < 16) { C13(29, j); return t; }
    j -= 16;
    if (j < 2 * NKP) { H13(31, j); return t; }
    j -= 2 * NKP;
    if (j < 16) { C13(30, j); return t; }
    j -= 16;
    C13(31, j);
    return t;
}
__device__ __forceinline__ void gemm_producer(unsigned char* smem, const CUtensorMap* womap, unsigned epoch, volatile int* s_tasks) {
    const uint32_t sb = smem_u32(smem);
    uint32_t st = 0, ph = 1;
    for (int n = 0;; n++) {
        const int j = (int)(atomicAdd(&g_gemmctr, 1u) - epoch * (unsigned)(NGEMM + NAUX));
        const Task t = decode_task(j);
        if (t.type <= 1) {
            wait_counter(&g_ocnt[t.rb], (epoch + 1) * 128u);
            if (t.type == 0) wait_counter(&g_ocnt[t.rb + 1], (epoch + 1) * 128u);
            fence_async_all();
        } else if (t.type == 2) {
            wait_counter(&g_gcnt[t.rb][t.c], (epoch + 1) * (t.rb >= NFINE ? (unsigned)NKP : 4u));
            wait_counter(&g_ssmcnt, (epoch + 1) * 80u);
        }
        const int nch = (t.type <= 1) ? t.nch : 1;
        for (int kc = 0; kc < nch; kc++) {
            mbar_wait_sleep(sb + AX_EMPTY + 8 * st, ph);
            const uint32_t a = sb + AX_DATA + st * AX_STAGE, bar = sb + AX_BAR + 16 + 8 * st;
            if (kc == 0) s_tasks[n & 7] = j;
            if (t.type > 1) mbar_arrive(bar);
            else {
                const bf16* asrc = g_Oimg + ((size_t)(t.rb >> 1) * 64 + t.k0 + kc) * 8192 + (t.rb & 1) * 4096;
                if (t.type == 0) { mbar_expect_tx(bar, AX_STAGE); bulk_g2s(a, asrc, 8192, bar); bulk_g2s(a + 8192, asrc + 4096, 8192, bar); }
                else { mbar_expect_tx(bar, AX_STAGE - 8192); bulk_g2s(a, asrc, 8192, bar); }
                #pragma unroll
                for (int b = 0; b < 5; b++) tma_load_2d(a + 16384 + b * 8192, womap, t.c * 320 + b * 64, (t.k0 + kc) * 64, bar);
            }
            if (++st == NST_G) { st = 0; ph ^= 1; }
        }
        if (t.type == 3) break;
    }
}
__device__ __forceinline__ void gemm_signaller(unsigned char* smem, volatile int* s_done) {
    const uint32_t sb = smem_u32(smem);
    for (int n = 0;; n++) {
        mbar_wait_sleep(sb + AX_DONE + 8 * (n & 3), (n >> 2) & 1);
        const int j = s_done[n & 7];
        if (j < 0) break;
        if ((threadIdx.x & 31) == 0) {
            const Task t = decode_task(j);
            __threadfence();
            atomicAdd(&g_gcnt[t.rb][t.c], 1u);
            if (t.type == 0) atomicAdd(&g_gcnt[t.rb + 1][t.c], 1u);
        }
        __syncwarp();
    }
}
__device__ __forceinline__ void gemm_consumer(unsigned char* smem, bf16* __restrict__ out, volatile int* s_tasks, volatile int* s_done) {
    const uint32_t sb = smem_u32(smem);
    const int tid = threadIdx.x, lane = tid & 31;
    const int wg = __shfl_sync(~0u, tid >> 7, 0), warp = __shfl_sync(~0u, (tid >> 5) & 3, 0);
    uint32_t st = 0, ph = 0;
    int ndone = 0;
    for (int n = 0;; n++) {
        mbar_wait_sleep(sb + AX_BAR + 16 + 8 * st, ph);
        const Task t = decode_task(__shfl_sync(~0u, s_tasks[n & 7], 0));
        if (t.type > 1) {
            nbar_sync(1, 256);
            if ((tid & 127) == 0) mbar_arrive(sb + AX_EMPTY + 8 * st);
            if (++st == NST_G) { st = 0; ph ^= 1; }
            if (t.type == 3) break;
            const int np = (t.rb >= NFINE) ? NKP : 4;
            const float* pbase = (t.rb >= NFINE) ? g_part31 + (size_t)(t.rb - NFINE) * NKP * 64 * DM - (size_t)t.rb * 64 * DM : g_part;
            const size_t pstride = (t.rb >= NFINE) ? (size_t)64 * DM : (size_t)SEQ * DM;
            auto combine = [&](int i, auto NP) {
                const int r = t.k0 + i / 80, cc = t.c * 320 + (i % 80) * 4;
                float4 v[NP.value];
                #pragma unroll
                for (int q = 0; q < NP.value; q++) v[q] = __ldcg(reinterpret_cast<const float4*>(pbase + q * pstride + (size_t)r * DM + cc));
                const float gt = __ldcg(g_g + r);
                const uint2 bb = __ldcg(reinterpret_cast<const uint2*>(g_b + (size_t)r * DM + cc));
                float4 a = v[0];
                #pragma unroll
                for (int q = 1; q < NP.value; q++) { a.x += v[q].x; a.y += v[q].y; a.z += v[q].z; a.w += v[q].w; }
                const float b0 = __uint_as_float(bb.x << 16), b1 = __uint_as_float(bb.x & 0xffff0000u), b2 = __uint_as_float(bb.y << 16), b3 = __uint_as_float(bb.y & 0xffff0000u);
                uint2 o; o.x = pack_bf16(gt * a.x + (1.f - gt) * b0, gt * a.y + (1.f - gt) * b1); o.y = pack_bf16(gt * a.z + (1.f - gt) * b2, gt * a.w + (1.f - gt) * b3);
                *reinterpret_cast<uint2*>(out + (size_t)r * DM + cc) = o;
            };
            if (np == 4) {
                const int nit = t.nch * 80 / 256;
                for (int it0 = 0; it0 < nit; it0 += 5) {
                    #pragma unroll
                    for (int it = 0; it < 5; it++) combine(tid + 256 * (it0 + it), IntC<4>());
                }
            } else {
                #pragma unroll
                for (int it = 0; it < 3; it++) { const int i = tid + 256 * it; if (i < 640) combine(i, IntC<NKP>()); }
            }
            if (n < 56 && (blockIdx.x >= NATT || n < 4)) ATRID((blockIdx.x >= NATT ? 6 : 58) + n, s_tasks[n & 7]);
            continue;
        }
        const int g = lane >> 2, tq = lane & 3;
        if (t.type == 0) {
            float acc[160];
            #pragma unroll
            for (int i = 0; i < 160; i++) acc[i] = 0.f;
            uint32_t prev = 0;
            for (int kc = 0; kc < 16; kc++) {
                mbar_wait(sb + AX_BAR + 16 + 8 * st, ph);
                const uint32_t a = sb + AX_DATA + st * AX_STAGE;
                const uint64_t da = make_desc(a + wg * 8192, 16, 1024), db = make_desc(a + 16384, 8192, 1024);
                wg_fence();
                #pragma unroll
                for (int ks = 0; ks < 4; ks++) {
                    wgmma_n192_tB<0>(acc, da + ks * 2, db + ks * 128);
                    wgmma_n128_tB<96>(acc, da + ks * 2, db + ks * 128 + 3 * 512);
                }
                wg_commit();
                asm volatile("wgmma.wait_group.sync.aligned 1;" ::: "memory");
                if (kc > 0 && (tid & 127) == 0) mbar_arrive(sb + AX_EMPTY + 8 * prev);
                prev = st;
                if (++st == NST_G) { st = 0; ph ^= 1; }
            }
            wg_wait0();
            if ((tid & 127) == 0) mbar_arrive(sb + AX_EMPTY + 8 * prev);
            float* base = g_part + ((size_t)t.plane * SEQ + t.rb * 64 + wg * 64 + warp * 16 + g) * DM + t.c * 320 + 2 * tq;
            #pragma unroll
            for (int q = 0; q < 40; q++) {
                *reinterpret_cast<float2*>(base + q * 8) = make_float2(acc[4 * q], acc[4 * q + 1]);
                *reinterpret_cast<float2*>(base + 8 * DM + q * 8) = make_float2(acc[4 * q + 2], acc[4 * q + 3]);
            }
        } else {
            float* base = (t.rb >= NFINE ? g_part31 + (size_t)((t.rb - NFINE) * NKP + t.plane) * 64 * DM : g_part + ((size_t)t.plane * SEQ + t.rb * 64) * DM) + (size_t)(warp * 16 + g) * DM + t.c * 320 + 2 * tq;
            if (wg == 0) {
                float acc[160];
                #pragma unroll
                for (int i = 0; i < 96; i++) acc[i] = 0.f;
                uint32_t prev = 0;
                for (int kc = 0; kc < t.nch; kc++) {
                    mbar_wait(sb + AX_BAR + 16 + 8 * st, ph);
                    const uint32_t a = sb + AX_DATA + st * AX_STAGE;
                    const uint64_t da = make_desc(a, 16, 1024), db = make_desc(a + 16384, 8192, 1024);
                    wg_fence();
                    #pragma unroll
                    for (int ks = 0; ks < 4; ks++) wgmma_n192_tB<0>(acc, da + ks * 2, db + ks * 128);
                    wg_commit();
                    asm volatile("wgmma.wait_group.sync.aligned 1;" ::: "memory");
                    if (kc > 0 && (tid & 127) == 0) mbar_arrive(sb + AX_EMPTY + 8 * prev);
                    prev = st;
                    if (++st == NST_G) { st = 0; ph ^= 1; }
                }
                wg_wait0();
                if ((tid & 127) == 0) mbar_arrive(sb + AX_EMPTY + 8 * prev);
                #pragma unroll
                for (int q = 0; q < 24; q++) {
                    *reinterpret_cast<float2*>(base + q * 8) = make_float2(acc[4 * q], acc[4 * q + 1]);
                    *reinterpret_cast<float2*>(base + 8 * DM + q * 8) = make_float2(acc[4 * q + 2], acc[4 * q + 3]);
                }
            } else {
                float acc[160];
                #pragma unroll
                for (int i = 96; i < 160; i++) acc[i] = 0.f;
                uint32_t prev = 0;
                for (int kc = 0; kc < t.nch; kc++) {
                    mbar_wait(sb + AX_BAR + 16 + 8 * st, ph);
                    const uint32_t a = sb + AX_DATA + st * AX_STAGE;
                    const uint64_t da = make_desc(a, 16, 1024), db = make_desc(a + 16384, 8192, 1024);
                    wg_fence();
                    #pragma unroll
                    for (int ks = 0; ks < 4; ks++) wgmma_n128_tB<96>(acc, da + ks * 2, db + ks * 128 + 3 * 512);
                    wg_commit();
                    asm volatile("wgmma.wait_group.sync.aligned 1;" ::: "memory");
                    if (kc > 0 && (tid & 127) == 0) mbar_arrive(sb + AX_EMPTY + 8 * prev);
                    prev = st;
                    if (++st == NST_G) { st = 0; ph ^= 1; }
                }
                wg_wait0();
                if ((tid & 127) == 0) mbar_arrive(sb + AX_EMPTY + 8 * prev);
                #pragma unroll
                for (int q = 24; q < 40; q++) {
                    *reinterpret_cast<float2*>(base + q * 8) = make_float2(acc[4 * q], acc[4 * q + 1]);
                    *reinterpret_cast<float2*>(base + 8 * DM + q * 8) = make_float2(acc[4 * q + 2], acc[4 * q + 3]);
                }
            }
        }
        if (tid == 0) s_done[ndone & 7] = s_tasks[n & 7];
        __syncwarp();
        if (lane == 0) mbar_arrive(sb + AX_DONE + 8 * (ndone & 3));
        ndone++;
        if (n < 56 && (blockIdx.x >= NATT || n < 4)) ATRID((blockIdx.x >= NATT ? 6 : 58) + n, s_tasks[n & 7]);
    }
    if (tid == 0) s_done[ndone & 7] = -1;
    __syncwarp();
    if (lane == 0) mbar_arrive(sb + AX_DONE + 8 * (ndone & 3));
}

__global__ void __launch_bounds__(384, 1)
k_aux(const __grid_constant__ CUtensorMap womap, const bf16* __restrict__ x, const bf16* __restrict__ A_re, const bf16* __restrict__ A_im,
      const bf16* __restrict__ B_re, const bf16* __restrict__ B_im, const bf16* __restrict__ C_re, const bf16* __restrict__ C_im,
      const bf16* __restrict__ log_dt, const bf16* __restrict__ Dskip, const bf16* __restrict__ gw, bf16* __restrict__ out) {
    extern __shared__ __align__(1024) unsigned char smem[];
    const uint32_t sb = smem_u32(smem);
    const int tid = threadIdx.x, warp = tid >> 5, lane = tid & 31;
    __shared__ unsigned s_epoch;
    __shared__ int s_task, s_tasks[8], s_done[8];
    if (tid == 0) {
        for (int i = 0; i < 2 + NST_G; i++) mbar_init(sb + AX_BAR + 8 * i, 1);
        for (int i = 0; i < NST_G; i++) mbar_init(sb + AX_EMPTY + 8 * i, blockIdx.x < NATT ? 8 : 2);
        asm volatile("fence.mbarrier_init.release.cluster;" ::: "memory");
        s_epoch = *reinterpret_cast<volatile unsigned*>(&g_epoch);
    }
    __syncthreads();
    const unsigned epoch = s_epoch;
    ATR(0);
    const int wg = __shfl_sync(~0u, tid >> 7, 0);
    if (wg == 2) {
        asm volatile("setmaxnreg.dec.sync.aligned.u32 40;");
        if (blockIdx.x < NATT) { if (warp == 8) attn_producer(smem, blockIdx.x, epoch); else if (warp == 9) attn_storer(smem, blockIdx.x); __syncwarp(); }
        nbar_sync(3, 384);
        nbar_sync(3, 384);
        if (warp == 8) { if (lane == 0) gemm_producer(smem, &womap, epoch, s_tasks); }
        else if (warp == 9) gemm_signaller(smem, s_done);
        __syncwarp();
        nbar_sync(4, 384);
    } else {
        asm volatile("setmaxnreg.inc.sync.aligned.u32 232;");
        if (blockIdx.x < NATT) attn_loop(smem, blockIdx.x, epoch);
        else {
            int ntask = 0;
            for (;;) {
                nbar_sync(1, 256);
                if (tid == 0) s_task = (int)(atomicAdd(&g_taskctr, 1u) - epoch * (unsigned)(80 + NAUX - NATT));
                nbar_sync(1, 256);
                const int task = s_task;
                if (task >= 80) break;
                for (int r = task * 26 + warp; r < min(SEQ, task * 26 + 26); r += 8) {
                    float sum = 0.f;
                    for (int i = lane * 2; i < DM; i += 64) {
                        __nv_bfloat162 xv = *reinterpret_cast<const __nv_bfloat162*>(x + (size_t)r * DM + i), wv = *reinterpret_cast<const __nv_bfloat162*>(gw + i);
                        sum += bf2f(xv.x) * bf2f(wv.x) + bf2f(xv.y) * bf2f(wv.y);
                    }
                    #pragma unroll
                    for (int o = 16; o; o >>= 1) sum += __shfl_xor_sync(~0u, sum, o);
                    if (lane == 0) g_g[r] = 1.f / (1.f + expf(-sum));
                }
                ssm_group(smem + AX_DATA, task, x, A_re, A_im, B_re, B_im, C_re, C_im, log_dt, Dskip);
                nbar_sync(1, 256);
                if (tid == 0) { __threadfence(); atomicAdd(&g_ssmcnt, 1u); }
                if (ntask < 4) ATR(2 + ntask);
                ntask++;
            }
        }
        fence_async();
        nbar_sync(3, 384);
        if (tid == 0) {
            for (int i = 0; i < NST_G; i++) {
                asm volatile("mbarrier.inval.shared::cta.b64 [%0];" :: "r"(sb + AX_BAR + 16 + 8 * i) : "memory");
                asm volatile("mbarrier.inval.shared::cta.b64 [%0];" :: "r"(sb + AX_EMPTY + 8 * i) : "memory");
                mbar_init(sb + AX_BAR + 16 + 8 * i, 1); mbar_init(sb + AX_EMPTY + 8 * i, 2);
            }
            for (int i = 0; i < 4; i++) mbar_init(sb + AX_DONE + 8 * i, 8);
            asm volatile("fence.mbarrier_init.release.cluster;" ::: "memory");
        }
        nbar_sync(3, 384);
        gemm_consumer(smem, out, s_tasks, s_done);
        nbar_sync(4, 384);
        if (tid == 0) {
            __threadfence();
            unsigned old = atomicAdd(&g_auxdone, 1u);
            if (old == NAUX - 1) { g_auxdone = 0; __threadfence(); atomicAdd(&g_epoch, 1u); }
        }
    }
    asm volatile("griddepcontrol.wait;" ::: "memory");
}

extern "C" void kernel_launch(void* const* d_in, const int* in_sizes, int n_in, void* d_out, int out_size) {
    const bf16* x = (const bf16*)d_in[0];
    const bf16* mem0 = (const bf16*)d_in[1];
    const bf16* Wq = (const bf16*)d_in[2];
    const bf16* Wk = (const bf16*)d_in[3];
    const bf16* Wv = (const bf16*)d_in[4];
    const bf16* Wo = (const bf16*)d_in[5];
    const bf16 *A_re = (const bf16*)d_in[8], *A_im = (const bf16*)d_in[9], *B_re = (const bf16*)d_in[10], *B_im = (const bf16*)d_in[11];
    const bf16 *C_re = (const bf16*)d_in[12], *C_im = (const bf16*)d_in[13], *log_dt = (const bf16*)d_in[14], *Dskip = (const bf16*)d_in[15];
    const bf16* gw = (const bf16*)d_in[16];
    bf16* out = (bf16*)d_out;
    cudaStream_t st = cudaStreamPerThread;
    static bool init = false;
    static CUtensorMap xmap, womap, wqmap, wkmap, wvmap;
    static const void* xmap_ptr = nullptr; static const void* womap_ptr = nullptr; static const void* w_ptr[3] = {nullptr, nullptr, nullptr};
    if (!init) {
        cudaFuncSetAttribute(k_chain, cudaFuncAttributeMaxDynamicSharedMemorySize, SM_TOTAL);
        cudaFuncSetAttribute(k_aux, cudaFuncAttributeMaxDynamicSharedMemorySize, AX_TOTAL);
        init = true;
    }
    if (xmap_ptr != (const void*)x || womap_ptr != (const void*)Wo || w_ptr[0] != Wq || w_ptr[1] != Wk || w_ptr[2] != Wv) {
        void* fn = nullptr; cudaDriverEntryPointQueryResult qres;
        cudaGetDriverEntryPoint("cuTensorMapEncodeTiled", &fn, cudaEnableDefault, &qres);
        typedef CUresult (*EncFn)(CUtensorMap*, CUtensorMapDataType, cuuint32_t, void*, const cuuint64_t*, const cuuint64_t*, const cuuint32_t*, const cuuint32_t*,
                                  CUtensorMapInterleave, CUtensorMapSwizzle, CUtensorMapL2promotion, CUtensorMapFloatOOBfill);
        cuuint32_t es[2] = {1, 1};
        {
          cuuint64_t dims[3] = {64, SEQ, 10}; cuuint64_t strides[2] = {DM * 2, 128}; cuuint32_t box[3] = {64, 32, 10}; cuuint32_t es3[3] = {1, 1, 1};
          ((EncFn)fn)(&xmap, CU_TENSOR_MAP_DATA_TYPE_BFLOAT16, 3, (void*)x, dims, strides, box, es3, CU_TENSOR_MAP_INTERLEAVE_NONE, CU_TENSOR_MAP_SWIZZLE_128B,
                      CU_TENSOR_MAP_L2_PROMOTION_L2_128B, CU_TENSOR_MAP_FLOAT_OOB_FILL_NONE); }
        { cuuint64_t dims[2] = {DM, HD}; cuuint64_t strides[1] = {DM * 2}; cuuint32_t box[2] = {64, 64};
          ((EncFn)fn)(&womap, CU_TENSOR_MAP_DATA_TYPE_BFLOAT16, 2, (void*)Wo, dims, strides, box, es, CU_TENSOR_MAP_INTERLEAVE_NONE, CU_TENSOR_MAP_SWIZZLE_128B,
                      CU_TENSOR_MAP_L2_PROMOTION_L2_128B, CU_TENSOR_MAP_FLOAT_OOB_FILL_NONE); }
        { cuuint64_t dims[2] = {HD, DM}; cuuint64_t strides[1] = {HD * 2}; cuuint32_t box[2] = {64, 128};
          const bf16* ws[3] = {Wq, Wk, Wv}; CUtensorMap* ms[3] = {&wqmap, &wkmap, &wvmap};
          for (int i = 0; i < 3; i++)
              ((EncFn)fn)(ms[i], CU_TENSOR_MAP_DATA_TYPE_BFLOAT16, 2, (void*)ws[i], dims, strides, box, es, CU_TENSOR_MAP_INTERLEAVE_NONE, CU_TENSOR_MAP_SWIZZLE_128B,
                          CU_TENSOR_MAP_L2_PROMOTION_L2_128B, CU_TENSOR_MAP_FLOAT_OOB_FILL_NONE); }
        xmap_ptr = (const void*)x; womap_ptr = (const void*)Wo; w_ptr[0] = Wq; w_ptr[1] = Wk; w_ptr[2] = Wv;
    }
    k_chain<<<96, 384, SM_TOTAL, st>>>(xmap, wqmap, wkmap, wvmap, womap, x, mem0);
    {
        cudaLaunchConfig_t cfg = {};
        cfg.gridDim = dim3(NAUX); cfg.blockDim = dim3(384); cfg.dynamicSmemBytes = AX_TOTAL; cfg.stream = st;
        cudaLaunchAttribute at[1];
        at[0].id = cudaLaunchAttributeProgrammaticStreamSerialization; at[0].val.programmaticStreamSerializationAllowed = 1;
        cfg.attrs = at; cfg.numAttrs = 1;
        cudaLaunchKernelEx(&cfg, k_aux, womap, x, A_re, A_im, B_re, B_im, C_re, C_im, log_dt, Dskip, gw, out);
    }
}
```

```cpp
#include <cuda_runtime.h>
#include <cuda_bf16.h>
#include <stdint.h>
#include <cuda.h>

typedef __nv_bfloat16 bf16;

#define SEQ 2048
#define DM 640
#define NH 32
#define DH 128
#define NM 8
#define SEG 32
#define NSEG 64
#define NST 128
#define HD 4096

__device__ bf16  g_b[SEQ * DM];
__device__ float g_g[SEQ];

__device__ __forceinline__ float bf2f(bf16 v) { return __bfloat162float(v); }
__device__ __forceinline__ uint32_t pack_bf16(float lo, float hi) {
    uint32_t r; asm("cvt.rn.bf16x2.f32 %0, %1, %2;" : "=r"(r) : "f"(hi), "f"(lo)); return r;
}
__device__ __forceinline__ uint32_t f2tf32(float x) { uint32_t r; asm("cvt.rna.tf32.f32 %0, %1;" : "=r"(r) : "f"(x)); return r; }
__device__ __forceinline__ void mma_tf32(float (&d)[4], uint32_t a0, uint32_t a1, uint32_t a2, uint32_t a3, uint32_t b0, uint32_t b1) {
    asm volatile("mma.sync.aligned.m16n8k8.row.col.f32.tf32.tf32.f32 {%0,%1,%2,%3}, {%4,%5,%6,%7}, {%8,%9}, {%0,%1,%2,%3};\n"
        : "+f"(d[0]), "+f"(d[1]), "+f"(d[2]), "+f"(d[3]) : "r"(a0), "r"(a1), "r"(a2), "r"(a3), "r"(b0), "r"(b1));
}
__device__ __forceinline__ void mma_bf16(float (&d)[4], uint32_t a0, uint32_t a1, uint32_t a2, uint32_t a3, uint32_t b0, uint32_t b1) {
    asm volatile("mma.sync.aligned.m16n8k16.row.col.f32.bf16.bf16.f32 {%0,%1,%2,%3}, {%4,%5,%6,%7}, {%8,%9}, {%0,%1,%2,%3};\n"
        : "+f"(d[0]), "+f"(d[1]), "+f"(d[2]), "+f"(d[3]) : "r"(a0), "r"(a1), "r"(a2), "r"(a3), "r"(b0), "r"(b1));
}
struct cf { float re, im; };
__device__ __forceinline__ cf cmul(cf a, cf b) { cf r; r.re = a.re * b.re - a.im * b.im; r.im = a.re * b.im + a.im * b.re; return r; }
__device__ __forceinline__ cf csq(cf a) { cf r; r.re = a.re * a.re - a.im * a.im; r.im = 2.f * a.re * a.im; return r; }
__device__ __forceinline__ cf cexpL(float zr, float zi, float L) {
    float e = __expf(zr * L);
    float ang = zi * L;
    float k = rintf(ang * 0.15915494309189535f);
    ang = fmaf(-k, 6.2831854820251465f, ang);
    ang = fmaf(-k, -1.7484555314695172e-07f, ang);
    cf r; r.re = e * __cosf(ang); r.im = e * __sinf(ang); return r;
}

#define SSM_CH 8
#define KC_PITCH 648
#define XS_PAD 128
#define XS_PITCH (XS_PAD + 2048 + 8)
#define YS_PITCH (2048 + 8)
#define KT_LEN (2048 + 48)
struct SsmSmem {
    float Kc[SSM_CH][KC_PITCH];
    bf16  xs[SSM_CH][XS_PITCH];
    union {
        bf16  KT[SSM_CH][2][KT_LEN];
        float st[SSM_CH][NST][8];
    } u;
    bf16  ys[SSM_CH][YS_PITCH];
    uint16_t kidx[2048];
};

__device__ __forceinline__ int kc_index(int l) {
    return l < 256 ? l : (l < 512 ? 256 + ((l - 256) >> 1) : (l < 1024 ? 384 + ((l - 512) >> 2) : 512 + ((l - 1024) >> 3)));
}

__device__ __forceinline__ void ssm_group(unsigned char* smem_raw, int grp, const bf16* __restrict__ x, const bf16* __restrict__ A_re, const bf16* __restrict__ A_im,
        const bf16* __restrict__ B_re, const bf16* __restrict__ B_im, const bf16* __restrict__ C_re, const bf16* __restrict__ C_im,
        const bf16* __restrict__ log_dt, const bf16* __restrict__ Dskip) {
    SsmSmem& S = *reinterpret_cast<SsmSmem*>(smem_raw);
    const int tid = threadIdx.x, w = tid >> 5, lane = tid & 31, g = lane >> 2, t = lane & 3;
    const int d0 = grp * SSM_CH;
    asm volatile("bar.sync 1, 256;" ::: "memory");
    #pragma unroll
    for (int it = 0; it < 8; it++) {
        const int l = tid + 256 * it;
        uint4 v = *reinterpret_cast<const uint4*>(x + (size_t)l * DM + d0);
        const bf16* p = reinterpret_cast<const bf16*>(&v);
        const int lr = (l & ~15) | (15 - (l & 15));
        #pragma unroll
        for (int c = 0; c < 8; c++) S.xs[c][XS_PAD + lr] = p[c];
        S.kidx[l] = (uint16_t)((int)bf2f(__float2bfloat16_rn((float)l)) == 2048 ? 640 : kc_index((int)bf2f(__float2bfloat16_rn((float)l))));
    }
    for (int i = tid; i < SSM_CH * XS_PAD / 2; i += 256) reinterpret_cast<uint32_t*>(&S.xs[i / (XS_PAD / 2)][0])[i % (XS_PAD / 2)] = 0u;
    {
        const int d = d0 + w;
        const float dt = bf2f(__float2bfloat16_rn(expf(bf2f(log_dt[d]))));
        #pragma unroll
        for (int i = 0; i < 4; i++) {
            const int n = lane + 32 * i;
            float zr = dt * bf2f(A_re[d * NST + n]), zi = dt * bf2f(A_im[d * NST + n]);
            cf dB; dB.re = dt * bf2f(B_re[d * NST + n]); dB.im = dt * bf2f(B_im[d * NST + n]);
            cf C; C.re = bf2f(C_re[d * NST + n]); C.im = bf2f(C_im[d * NST + n]);
            cf wv = cmul(C, dB);
            cf u8 = cexpL(zr, zi, 8.f), u128 = cexpL(zr, zi, 128.f);
            float* st = S.u.st[w][n];
            *reinterpret_cast<float4*>(st) = make_float4(zr, zi, wv.re, wv.im);
            *reinterpret_cast<float4*>(st + 4) = make_float4(u8.re, u8.im, u128.re, u128.im);
        }
        __syncwarp();
        float a0a[4] = {0, 0, 0, 0}, a0b[4] = {0, 0, 0, 0}, a1[4] = {0, 0, 0, 0}, a2a[4] = {0, 0, 0, 0}, a2b[4] = {0, 0, 0, 0};
        float k2048 = 0.f;
        const float Lg = (g < 4) ? (512.f + 4.f * g) : (g < 6 ? 1024.f + 8.f * (g - 4) : 1536.f + 8.f * (g - 6));
        #pragma unroll 4
        for (int kk = 0; kk < 32; kk++) {
            const float* st = S.u.st[w][4 * kk + t];
            float4 s0 = *reinterpret_cast<const float4*>(st), s1 = *reinterpret_cast<const float4*>(st + 4);
            cf wv; wv.re = s0.z; wv.im = s0.w;
            cf u8; u8.re = s1.x; u8.im = s1.y;
            cf u128; u128.re = s1.z; u128.im = s1.w;
            cf e1 = cexpL(s0.x, s0.y, (float)g);
            cf e23 = cexpL(s0.x, s0.y, Lg);
            cf e1b = cmul(e1, u8);
            cf e2 = csq(e1);
            cf p = csq(csq(csq(e2)));
            cf f0 = cmul(wv, p), f1 = cmul(f0, u128), f2 = cmul(f1, u128), f3 = cmul(f2, u128);
            uint32_t A00 = f2tf32(f0.re), A01 = f2tf32(f1.re), A02 = f2tf32(-f0.im), A03 = f2tf32(-f1.im);
            uint32_t A10 = f2tf32(f2.re), A11 = f2tf32(f3.re), A12 = f2tf32(-f2.im), A13 = f2tf32(-f3.im);
            mma_tf32(a0a, A00, A01, A02, A03, f2tf32(e1.re), f2tf32(e1.im));
            mma_tf32(a0b, A00, A01, A02, A03, f2tf32(e1b.re), f2tf32(e1b.im));
            mma_tf32(a1, A10, A11, A12, A13, f2tf32(e2.re), f2tf32(e2.im));
            uint32_t E0 = f2tf32(e23.re), E1 = f2tf32(e23.im);
            mma_tf32(a2a, A00, A01, A02, A03, E0, E1);
            mma_tf32(a2b, A10, A11, A12, A13, E0, E1);
            cf e2048 = csq(e23);
            k2048 += wv.re * e2048.re - wv.im * e2048.im;
        }
        k2048 += __shfl_xor_sync(~0u, k2048, 1);
        k2048 += __shfl_xor_sync(~0u, k2048, 2);
        float* Kc = S.Kc[w];
        Kc[16 * g + 2 * t] = a0a[0]; Kc[16 * g + 2 * t + 1] = a0a[1]; Kc[16 * (g + 8) + 2 * t] = a0a[2]; Kc[16 * (g + 8) + 2 * t + 1] = a0a[3];
        Kc[16 * g + 8 + 2 * t] = a0b[0]; Kc[16 * g + 8 + 2 * t + 1] = a0b[1]; Kc[16 * (g + 8) + 8 + 2 * t] = a0b[2]; Kc[16 * (g + 8) + 8 + 2 * t + 1] = a0b[3];
        Kc[256 + 8 * g + 2 * t] = a1[0]; Kc[256 + 8 * g + 2 * t + 1] = a1[1]; Kc[256 + 8 * (g + 8) + 2 * t] = a1[2]; Kc[256 + 8 * (g + 8) + 2 * t + 1] = a1[3];
        #pragma unroll
        for (int mt = 0; mt < 2; mt++) {
            #pragma unroll
            for (int e = 0; e < 4; e++) {
                int A = mt * 16 + g + (e >> 1) * 8, j = 2 * t + (e & 1);
                int Lj = (j < 4) ? 512 + 4 * j : (j < 6 ? 1024 + 8 * (j - 4) : 1536 + 8 * (j - 6));
                Kc[kc_index(Lj + 16 * A)] = mt ? a2b[e] : a2a[e];
            }
        }
        if (lane == 16) Kc[640] = k2048;
    }
    __syncwarp();
    {
        asm volatile("bar.sync 1, 256;" ::: "memory");
        bf16* k0 = S.u.KT[w][0];
        bf16* k1 = S.u.KT[w][1];
        const float* Kc = S.Kc[w];
        #pragma unroll 8
        for (int j = lane; j < 2048; j += 32) {
            const bf16 v = __float2bfloat16_rn(Kc[S.kidx[j]]);
            k0[16 + j] = v;
            k1[15 + j] = v;
        }
        if (lane < 16) { k0[lane] = __float2bfloat16_rn(0.f); if (lane < 15) k1[lane] = __float2bfloat16_rn(0.f); }
        k0[2064 + lane] = __float2bfloat16_rn(0.f); k1[2063 + lane] = __float2bfloat16_rn(0.f);
        __syncwarp();
    }
    {
        float acc[16][4];
        #pragma unroll
        for (int v = 0; v < 16; v++) { acc[v][0] = acc[v][1] = acc[v][2] = acc[v][3] = 0.f; }
        const bf16* kt = (g & 1) ? &S.u.KT[w][0][0] : &S.u.KT[w][1][0];
        const int ibase0 = g + 1 + 2 * t - ((g & 1) ? 0 : 1);
        #pragma unroll 1
        for (int r = 0; r < 8; r++) {
            uint32_t B[16][2];
            #pragma unroll
            for (int v = 0; v < 16; v++) {
                const bf16* p = &S.xs[w][XS_PAD + 16 * (8 * v + g - r) + 2 * t];
                B[v][0] = *reinterpret_cast<const uint32_t*>(p);
                B[v][1] = *reinterpret_cast<const uint32_t*>(p + 8);
            }
            #pragma unroll
            for (int q = 0; q < 16; q++) {
                const int i0 = ibase0 + 16 * r + 128 * q;
                const uint32_t A0 = *reinterpret_cast<const uint32_t*>(kt + i0);
                const uint32_t A1 = *reinterpret_cast<const uint32_t*>(kt + i0 + 8);
                const uint32_t A3 = *reinterpret_cast<const uint32_t*>(kt + i0 + 16);
                #pragma unroll
                for (int v = q; v < 16; v++) mma_bf16(acc[v], A0, A1, A1, A3, B[v - q][0], B[v - q][1]);
            }
        }
        bf16* ys = S.ys[w];
        #pragma unroll
        for (int v = 0; v < 16; v++) {
            const int a = 8 * v + 2 * t;
            ys[16 * a + g] = __float2bfloat16_rn(acc[v][0]); ys[16 * (a + 1) + g] = __float2bfloat16_rn(acc[v][1]);
            ys[16 * a + g + 8] = __float2bfloat16_rn(acc[v][2]); ys[16 * (a + 1) + g + 8] = __float2bfloat16_rn(acc[v][3]);
        }
    }
    asm volatile("bar.sync 1, 256;" ::: "memory");
    {
        float dsk[8];
        #pragma unroll
        for (int c = 0; c < 8; c++) dsk[c] = bf2f(Dskip[d0 + c]);
        #pragma unroll 2
        for (int it = 0; it < 8; it++) {
            const int l = tid + 256 * it;
            const int lr = XS_PAD + ((l & ~15) | (15 - (l & 15)));
            float o[8];
            #pragma unroll
            for (int c = 0; c < 8; c++) o[c] = bf2f(S.ys[c][l]) + bf2f(__float2bfloat16_rn(bf2f(S.xs[c][lr]) * dsk[c]));
            *reinterpret_cast<uint4*>(g_b + (size_t)l * DM + d0) = make_uint4(pack_bf16(o[0], o[1]), pack_bf16(o[2], o[3]), pack_bf16(o[4], o[5]), pack_bf16(o[6], o[7]));
        }
    }
}

__device__ __forceinline__ uint32_t smem_u32(const void* p) { return (uint32_t)__cvta_generic_to_shared(p); }
__device__ __forceinline__ void mbar_init(uint32_t bar, uint32_t cnt) { asm volatile("mbarrier.init.shared::cta.b64 [%0], %1;" :: "r"(bar), "r"(cnt) : "memory"); }
__device__ __forceinline__ void mbar_expect_tx(uint32_t bar, uint32_t bytes) { asm volatile("mbarrier.arrive.expect_tx.shared::cta.b64 _, [%0], %1;" :: "r"(bar), "r"(bytes) : "memory"); }
__device__ __forceinline__ void mbar_arrive(uint32_t bar) { asm volatile("mbarrier.arrive.shared::cta.b64 _, [%0];" :: "r"(bar) : "memory"); }
__device__ __forceinline__ void mbar_wait(uint32_t bar, uint32_t parity) {
    uint32_t ok; int guard = 0;
    do {
        asm volatile("{\n.reg .pred P1;\nmbarrier.test_wait.parity.shared::cta.b64 P1, [%1], %2;\nselp.u32 %0,1,0,P1;\n}" : "=r"(ok) : "r"(bar), "r"(parity) : "memory");
    } while (!ok && ++guard < (1 << 24));
}
__device__ __forceinline__ void mbar_wait_sleep(uint32_t bar, uint32_t parity) {
    uint32_t ok; int guard = 0;
    do {
        asm volatile("{\n.reg .pred P1;\nmbarrier.try_wait.parity.shared::cta.b64 P1, [%1], %2;\nselp.u32 %0,1,0,P1;\n}" : "=r"(ok) : "r"(bar), "r"(parity) : "memory");
    } while (!ok && ++guard < (1 << 22));
}
__device__ __forceinline__ uint32_t mapa(uint32_t addr, uint32_t rank) { uint32_t r; asm volatile("mapa.shared::cluster.u32 %0, %1, %2;" : "=r"(r) : "r"(addr), "r"(rank)); return r; }
__device__ __forceinline__ void st_async4(uint32_t addr, float a, float b, float c, float d, uint32_t bar) {
    asm volatile("st.async.weak.shared::cluster.mbarrier::complete_tx::bytes.v4.f32 [%0], {%1,%2,%3,%4}, [%5];" :: "r"(addr), "f"(a), "f"(b), "f"(c), "f"(d), "r"(bar) : "memory");
}
__device__ __forceinline__ void bulk_s2c(uint32_t dst, uint32_t src, uint32_t bytes, uint32_t bar) {
    asm volatile("cp.async.bulk.shared::cluster.shared::cta.mbarrier::complete_tx::bytes [%0], [%1], %2, [%3];" :: "r"(dst), "r"(src), "r"(bytes), "r"(bar) : "memory");
}
__device__ __forceinline__ void bulk_g2s(uint32_t dst, const void* src, uint32_t bytes, uint32_t bar) {
    asm volatile("cp.async.bulk.shared::cluster.global.mbarrier::complete_tx::bytes [%0], [%1], %2, [%3];" :: "r"(dst), "l"(src), "r"(bytes), "r"(bar) : "memory");
}
__device__ __forceinline__ void bulk_s2g(void* dst, uint32_t src, uint32_t bytes) {
    asm volatile("cp.async.bulk.global.shared::cta.bulk_group [%0], [%1], %2;" :: "l"(dst), "r"(src), "r"(bytes) : "memory");
}
__device__ __forceinline__ void bulk_commit() { asm volatile("cp.async.bulk.commit_group;" ::: "memory"); }
__device__ __forceinline__ void bulk_wait_read0() { asm volatile("cp.async.bulk.wait_group.read 0;" ::: "memory"); }
__device__ __forceinline__ void bulk_wait0() { asm volatile("cp.async.bulk.wait_group 0;" ::: "memory"); }
__device__ __forceinline__ void fence_async() { asm volatile("fence.proxy.async.shared::cta;" ::: "memory"); }
__device__ __forceinline__ void nbar_sync(int id, int n) { asm volatile("bar.sync %0, %1;" :: "r"(id), "r"(n) : "memory"); }
__device__ __forceinline__ void nbar_arrive(int id, int n) { asm volatile("bar.arrive %0, %1;" :: "r"(id), "r"(n) : "memory"); }
__device__ __forceinline__ void cp_async16(uint32_t dst, const void* src) { asm volatile("cp.async.cg.shared.global [%0], [%1], 16;" :: "r"(dst), "l"(src) : "memory"); }
__device__ __forceinline__ void cp_async_wait_all() { asm volatile("cp.async.wait_all;" ::: "memory"); }
__device__ __forceinline__ void ldsm4(uint32_t (&r)[4], uint32_t addr) {
    asm volatile("ldmatrix.sync.aligned.m8n8.x4.shared.b16 {%0,%1,%2,%3}, [%4];" : "=r"(r[0]), "=r"(r[1]), "=r"(r[2]), "=r"(r[3]) : "r"(addr) : "memory");
}
__device__ __forceinline__ void ldsm4t(uint32_t (&r)[4], uint32_t addr) {
    asm volatile("ldmatrix.sync.aligned.m8n8.x4.trans.shared.b16 {%0,%1,%2,%3}, [%4];" : "=r"(r[0]), "=r"(r[1]), "=r"(r[2]), "=r"(r[3]) : "r"(addr) : "memory");
}
__device__ __forceinline__ void stsm2t(uint32_t addr, uint32_t r0, uint32_t r1) {
    asm volatile("stmatrix.sync.aligned.m8n8.x2.trans.shared.b16 [%0], {%1,%2};" :: "r"(addr), "r"(r0), "r"(r1) : "memory");
}
__device__ __forceinline__ uint4 ld_relaxed4(const void* p) { uint4 v; asm volatile("ld.relaxed.gpu.global.v4.u32 {%0,%1,%2,%3}, [%4];" : "=r"(v.x), "=r"(v.y), "=r"(v.z), "=r"(v.w) : "l"(p) : "memory"); return v; }
__device__ __forceinline__ void st_relaxed2(void* p, uint32_t a, uint32_t b) { asm volatile("st.relaxed.gpu.global.v2.u32 [%0], {%1,%2};" :: "l"(p), "r"(a), "r"(b) : "memory"); }
__device__ __forceinline__ void st_relaxed1(void* p, uint32_t a) { asm volatile("st.relaxed.gpu.global.u32 [%0], %1;" :: "l"(p), "r"(a) : "memory"); }
__device__ __forceinline__ unsigned ld_acquire(const unsigned* p) { unsigned v; asm volatile("ld.acquire.gpu.global.u32 %0, [%1];" : "=r"(v) : "l"(p) : "memory"); return v; }
__device__ __forceinline__ float ex2_approx(float x) { float r; asm("ex2.approx.ftz.f32 %0, %1;" : "=f"(r) : "f"(x)); return r; }
__device__ __forceinline__ uint64_t make_desc(uint32_t saddr, uint32_t lbo, uint32_t sbo) {
    return (uint64_t)((saddr & 0x3FFFF) >> 4) | ((uint64_t)((lbo & 0x3FFFF) >> 4) << 16) | ((uint64_t)((sbo & 0x3FFFF) >> 4) << 32) | (1ull << 62);
}
__device__ __forceinline__ void wg_fence() { asm volatile("wgmma.fence.sync.aligned;" ::: "memory"); }
__device__ __forceinline__ void wg_commit() { asm volatile("wgmma.commit_group.sync.aligned;" ::: "memory"); }
__device__ __forceinline__ void wg_wait0() { asm volatile("wgmma.wait_group.sync.aligned 0;" ::: "memory"); }
__device__ __forceinline__ void wgmma_n40_tA(float (&d)[20], uint64_t da, uint64_t db, int scale_d) {
    asm volatile("{\n.reg .pred p;\nsetp.ne.b32 p, %22, 0;\n"
        "wgmma.mma_async.sync.aligned.m64n40k16.f32.bf16.bf16 {%0,%1,%2,%3,%4,%5,%6,%7,%8,%9,%10,%11,%12,%13,%14,%15,%16,%17,%18,%19}, %20, %21, p, 1, 1, 1, 0;\n}\n"
        : "+f"(d[0]), "+f"(d[1]), "+f"(d[2]), "+f"(d[3]), "+f"(d[4]), "+f"(d[5]), "+f"(d[6]), "+f"(d[7]), "+f"(d[8]), "+f"(d[9]),
          "+f"(d[10]), "+f"(d[11]), "+f"(d[12]), "+f"(d[13]), "+f"(d[14]), "+f"(d[15]), "+f"(d[16]), "+f"(d[17]), "+f"(d[18]), "+f"(d[19])
        : "l"(da), "l"(db), "r"(scale_d));
}

#define NRED 80
#define CAL_THR 410u
#define COMM_REGS "40"
#define NPOOL 576
#define RPS 1
__device__ __align__(4096) uint32_t g_pool[(NPOOL + 1) * 1024];
__device__ unsigned g_cls[NPOOL];
__device__ unsigned g_side[96];
__device__ unsigned g_calcnt;
__device__ unsigned g_epoch;
__device__ unsigned g_flag[NSEG][NH];
__device__ __align__(1024) bf16 g_Qimg[NSEG * NH * 2 * 32 * 64];
__device__ __align__(1024) bf16 g_Kimg[NSEG * NH * 2 * 40 * 64];
__device__ __align__(1024) bf16 g_Vimg[NSEG * NH * 2 * 40 * 64];

#define SM_XB    0
#define SM_VT    81920
#define SM_KT    (SM_VT + 20480)
#define SM_QT    (SM_KT + 10240)
#define SM_QS    (SM_QT + 4096)
#define SM_MEMB  (SM_QS + 1024)
#define SM_RED   (SM_MEMB + 10240)
#define SM_SC    (SM_RED + 16384)
#define SM_CRED  (SM_SC + 5120)
#define SM_PB    (SM_CRED + 1024)
#define SM_TRACE (SM_PB + 1024)
#define SM_WO    163840
#define SM_BAR   (SM_WO + 65536)
#define SM_TPM   (SM_BAR + 256)
#define SM_TRD   (SM_TPM + 256)
#define SM_TPUB  (SM_TRD + 16)
#define SM_TGAT  (SM_TPUB + 128)
#define SM_CAL   (SM_TGAT + 64)
#define SM_TOTAL (SM_CAL + 128)
#define B_SC   (SM_BAR + 0)
#define B_V    (SM_BAR + 16)
#define B_P    (SM_BAR + 48)
#define B_X    (SM_BAR + 56)
#define B_EXP  (SM_BAR + 72)

#define TR(ev) do {} while (0)
__device__ __forceinline__ uint32_t tag_of(int s) { return (uint32_t)(((s >> 1) & 1) + 1); }
__device__ __forceinline__ unsigned probe_latency(uint32_t* p, uint32_t zero) {
    uint32_t v, best = 0xffffffffu;
    asm volatile("atom.relaxed.gpu.global.add.u32 %0, [%1], 0;" : "=r"(v) : "l"(p) : "memory");
    #pragma unroll 1
#define NPROBE 4
    for (int r = 0; r < NPROBE; r++) {
        uint32_t c0, c1;
        asm volatile("mov.u32 %0, %%clock;" : "=r"(c0) : "r"(v) : "memory");
        asm volatile("atom.relaxed.gpu.global.add.u32 %0, [%1], 0;" : "=r"(v) : "l"(p + ((v + c0) & zero)) : "memory");
        asm volatile("{\n.reg .u32 t;\nand.b32 t, %1, %2;\nmov.u32 %0, %%clock;\nadd.u32 %0, %0, t;\n}" : "=r"(c1) : "r"(v), "r"(zero) : "memory");
        best = min(best, c1 - c0);
    }
    return best;
}
__device__ __forceinline__ void cluster_sync_all() { asm volatile("barrier.cluster.arrive.release.aligned;\nbarrier.cluster.wait.acquire.aligned;" ::: "memory"); }
__device__ __forceinline__ void tma_load_2d(uint32_t dst, const void* map, int c0, int c1, uint32_t bar) {
    asm volatile("cp.async.bulk.tensor.2d.shared::cluster.global.mbarrier::complete_tx::bytes [%0], [%1, {%3, %4}], [%2];"
        :: "r"(dst), "l"(map), "r"(bar), "r"(c0), "r"(c1) : "memory");
}
__device__ __forceinline__ void tma_load_3d(uint32_t dst, const void* map, int c0, int c1, int c2, uint32_t bar) {
    asm volatile("cp.async.bulk.tensor.3d.shared::cluster.global.mbarrier::complete_tx::bytes [%0], [%1, {%3, %4, %5}], [%2];"
        :: "r"(dst), "l"(map), "r"(bar), "r"(c0), "r"(c1), "r"(c2) : "memory");
}
__device__ __forceinline__ void stsm4t(uint32_t addr, uint32_t r0, uint32_t r1, uint32_t r2, uint32_t r3) {
    asm volatile("stmatrix.sync.aligned.m8n8.x4.trans.shared.b16 [%0], {%1,%2,%3,%4};" :: "r"(addr), "r"(r0), "r"(r1), "r"(r2), "r"(r3) : "memory");
}
__device__ __forceinline__ void wgmma_n32_rs(float (&d)[16], const uint32_t (&a)[4], uint64_t db, int scale_d) {
    asm volatile("{\n.reg .pred p;\nsetp.ne.b32 p, %21, 0;\n"
        "wgmma.mma_async.sync.aligned.m64n32k16.f32.bf16.bf16 {%0,%1,%2,%3,%4,%5,%6,%7,%8,%9,%10,%11,%12,%13,%14,%15}, {%16,%17,%18,%19}, %20, p, 1, 1, 0;\n}\n"
        : "+f"(d[0]), "+f"(d[1]), "+f"(d[2]), "+f"(d[3]), "+f"(d[4]), "+f"(d[5]), "+f"(d[6]), "+f"(d[7]),
          "+f"(d[8]), "+f"(d[9]), "+f"(d[10]), "+f"(d[11]), "+f"(d[12]), "+f"(d[13]), "+f"(d[14]), "+f"(d[15])
        : "r"(a[0]), "r"(a[1]), "r"(a[2]), "r"(a[3]), "l"(db), "r"(scale_d));
}

__device__ __forceinline__ void st_async4u(uint32_t addr, uint4 v, uint32_t bar) {
    asm volatile("st.async.weak.shared::cluster.mbarrier::complete_tx::bytes.v4.u32 [%0], {%1,%2,%3,%4}, [%5];" :: "r"(addr), "r"(v.x), "r"(v.y), "r"(v.z), "r"(v.w), "r"(bar) : "memory");
}
__device__ __forceinline__ void export_issue(uint32_t sb, int s, int h, uint32_t rank) {
    const size_t img = (size_t)(s * NH + h) * 2;
    const int sl = s & 1;
    if (rank == 2) {
        bulk_s2g(g_Vimg + img * 2560, sb + SM_VT + sl * 10240, 5120);
        bulk_s2g(g_Vimg + (img + 1) * 2560, sb + SM_VT + sl * 10240 + 5120, 5120);
    } else {
        bulk_s2g(g_Qimg + (img + rank) * 2048, sb + SM_QT, 4096);
        bulk_s2g(g_Kimg + (img + rank) * 2560, sb + SM_KT + sl * 5120, 5120);
    }
    bulk_commit();
    bulk_wait_read0();
    mbar_arrive(sb + B_EXP);
}
__device__ __forceinline__ void export_signal(int s, int h) {
    bulk_wait0();
    asm volatile("fence.proxy.async;" ::: "memory");
    __threadfence();
    atomicAdd(&g_flag[s][h], 1u);
}

__device__ __forceinline__ void score_tile(uint32_t sb, int sl, int nt, int lane, uint32_t rank) {
    float sc[4] = {0, 0, 0, 0}, sd[4] = {0, 0, 0, 0};
    const int r = lane & 7;
    uint32_t qa[2][4], kb[2][4];
    #pragma unroll
    for (int j = 0; j < 2; j++) {
        const int chunk = (lane >> 3) + 4 * j;
        ldsm4(kb[j], sb + SM_KT + sl * 5120 + (8 * nt + r) * 128 + ((chunk ^ r) << 4));
        ldsm4(qa[j], sb + SM_QS + r * 128 + ((chunk ^ r) << 4));
    }
    mma_bf16(sc, qa[0][0], 0u, qa[0][1], 0u, kb[0][0], kb[0][1]);
    mma_bf16(sd, qa[1][0], 0u, qa[1][1], 0u, kb[1][0], kb[1][1]);
    mma_bf16(sc, qa[0][2], 0u, qa[0][3], 0u, kb[0][2], kb[0][3]);
    mma_bf16(sd, qa[1][2], 0u, qa[1][3], 0u, kb[1][2], kb[1][3]);
    sc[0] += sd[0]; sc[1] += sd[1];
    const float o0 = __shfl_down_sync(~0u, sc[0], 1), o1 = __shfl_down_sync(~0u, sc[1], 1);
    if ((lane & 1) == 0) {
        const uint32_t a = SM_SC + sl * 2560 + rank * 1280 + ((lane >> 2) * 40 + 8 * nt + 2 * (lane & 3)) * 4;
        const uint32_t bo = B_SC + 8 * sl;
        { const uint32_t rb = mapa(sb, 2); st_async4(rb + a, sc[0], sc[1], o0, o1, rb + bo); }
        { const uint32_t rb = mapa(sb, rank ^ 1); st_async4(rb + a, sc[0], sc[1], o0, o1, rb + bo); }
        asm volatile("st.shared.v4.f32 [%0], {%1,%2,%3,%4};" :: "r"(sb + a), "f"(sc[0]), "f"(sc[1]), "f"(o0), "f"(o1) : "memory");
    }
    __syncwarp();
    if (lane == 0) mbar_arrive(sb + B_SC + 8 * sl);
}
__device__ __forceinline__ void wgmma_n40_rs(float (&d)[20], const uint32_t (&a)[4], uint64_t db, int scale_d) {
    asm volatile("{\n.reg .pred p;\nsetp.ne.b32 p, %25, 0;\n"
        "wgmma.mma_async.sync.aligned.m64n40k16.f32.bf16.bf16 {%0,%1,%2,%3,%4,%5,%6,%7,%8,%9,%10,%11,%12,%13,%14,%15,%16,%17,%18,%19}, {%20,%21,%22,%23}, %24, p, 1, 1, 0;\n}\n"
        : "+f"(d[0]), "+f"(d[1]), "+f"(d[2]), "+f"(d[3]), "+f"(d[4]), "+f"(d[5]), "+f"(d[6]), "+f"(d[7]), "+f"(d[8]), "+f"(d[9]),
          "+f"(d[10]), "+f"(d[11]), "+f"(d[12]), "+f"(d[13]), "+f"(d[14]), "+f"(d[15]), "+f"(d[16]), "+f"(d[17]), "+f"(d[18]), "+f"(d[19])
        : "r"(a[0]), "r"(a[1]), "r"(a[2]), "r"(a[3]), "l"(db), "r"(scale_d));
}
__device__ __forceinline__ void pu_mma(float (&o)[4], const float (&u)[20], const uint32_t (&pb)[5]) {
    float o2[4] = {0, 0, 0, 0};
    o[0] = o[1] = o[2] = o[3] = 0.f;
    mma_bf16(o, pack_bf16(u[0], u[1]), pack_bf16(u[2], u[3]), pack_bf16(u[4], u[5]), pack_bf16(u[6], u[7]), pb[0], pb[1]);
    mma_bf16(o2, pack_bf16(u[8], u[9]), pack_bf16(u[10], u[11]), pack_bf16(u[12], u[13]), pack_bf16(u[14], u[15]), pb[2], pb[3]);
    mma_bf16(o, pack_bf16(u[16], u[17]), pack_bf16(u[18], u[19]), 0u, 0u, pb[4], 0u);
    o[0] += o2[0]; o[1] += o2[1]; o[2] += o2[2]; o[3] += o2[3];
}
__device__ __forceinline__ void pu_store(const float (&o)[4], float2 inv, uint2 off, int lane, uint32_t tg) {
    unsigned char* pool = reinterpret_cast<unsigned char*>(g_pool) + lane * 8;
    st_relaxed2(pool + off.x, (__float_as_uint(o[0] * inv.x) & ~3u) | tg, (__float_as_uint(o[1] * inv.y) & ~3u) | tg);
    st_relaxed2(pool + off.y, (__float_as_uint(o[2] * inv.x) & ~3u) | tg, (__float_as_uint(o[3] * inv.y) & ~3u) | tg);
}
__device__ __forceinline__ float rcp_approx(float x) { float r; asm("rcp.approx.ftz.f32 %0, %1;" : "=f"(r) : "f"(x)); return r; }
template <int NT>
__device__ __forceinline__ void u_pass(unsigned char* smem, uint32_t sb, int s, uint32_t rank, int wg, int warp, int lane) {
    const int sl = s & 1;
#define NRS_V 6
    constexpr int NRS = NRS_V;
    uint32_t wa[NRS][4];
    {
        const int mi = lane >> 3, chunk = 2 * warp + (mi & 1);
        #pragma unroll
        for (int ks = 0; ks < NRS; ks++) {
            const int row = 16 * ks + (mi >> 1) * 8 + (lane & 7);
            ldsm4t(wa[ks], sb + SM_WO + (2 * wg) * 16384 + row * 128 + ((chunk ^ (row & 7)) << 4));
        }
    }
    if (rank < 2) { mbar_wait(sb + B_V + 8 * sl, (s >> 1) & 1); fence_async(); }
    if (wg == 0 && warp == 0) TR(4);
    float U0[20];
    wg_fence();
    #pragma unroll
    for (int ks = 0; ks < NRS; ks++)
        wgmma_n40_rs(U0, wa[ks], make_desc(sb + SM_VT + sl * 10240 + (ks >> 2) * 5120 + (ks & 3) * 32, 16, 1024), ks > 0);
    #pragma unroll
    for (int ks = NRS; ks < 8; ks++)
        wgmma_n40_tA(U0, make_desc(sb + SM_WO + (2 * wg) * 16384 + ks * 2048, 1024, 1024),
                     make_desc(sb + SM_VT + sl * 10240 + (ks >> 2) * 5120 + (ks & 3) * 32, 16, 1024), 1);
    wg_commit();
    const uint32_t tg = tag_of(s);
    uint32_t pb[5];
    float sm[4], sm2[4];
    auto get_p = [&]() {
        nbar_sync(9, 288);
        const uint32_t* pbs = reinterpret_cast<const uint32_t*>(smem + SM_PB);
        #pragma unroll
        for (int q = 0; q < 5; q++) pb[q] = pbs[q * 32 + lane];
        sm[0] = sm[1] = sm[2] = sm[3] = 0.f; sm2[0] = sm2[1] = sm2[2] = sm2[3] = 0.f;
        const uint32_t one = 0x3f803f80u;
        mma_bf16(sm, one, one, one, one, pb[0], pb[1]);
        mma_bf16(sm2, one, one, one, one, pb[2], pb[3]);
        mma_bf16(sm, one, one, 0u, 0u, pb[4], 0u);
    };
    const uint2* tpm = reinterpret_cast<const uint2*>(smem + SM_TPM) + (sl * 4 + 2 * wg) * 4 + warp;
    if (NT == 2) {
        wg_wait0();
        float U1[20];
        wg_fence();
        #pragma unroll
        for (int ks = 0; ks < 8; ks++)
            wgmma_n40_tA(U1, make_desc(sb + SM_WO + (2 * wg + 1) * 16384 + ks * 2048, 1024, 1024),
                         make_desc(sb + SM_VT + sl * 10240 + (ks >> 2) * 5120 + (ks & 3) * 32, 16, 1024), ks > 0);
        wg_commit();
        const uint2 off0 = tpm[0], off1 = tpm[4];
        get_p();
        float o0[4], o1[4];
        pu_mma(o0, U0, pb);
        wg_wait0();
        pu_mma(o1, U1, pb);
        const float2 inv = make_float2(rcp_approx(sm[0] + sm2[0]), rcp_approx(sm[1] + sm2[1]));
        if (wg == 0 && warp == 0) TR(8);
        pu_store(o0, inv, off0, lane, tg);
        pu_store(o1, inv, off1, lane, tg);
        if (wg == 0 && warp == 0) TR(6);
    } else {
        const uint2 off0 = tpm[0];
        wg_wait0();
        get_p();
        float o0[4];
        pu_mma(o0, U0, pb);
        const float2 inv = make_float2(rcp_approx(sm[0] + sm2[0]), rcp_approx(sm[1] + sm2[1]));
        pu_store(o0, inv, off0, lane, tg);
    }
}

__global__ void __cluster_dims__(3, 1, 1) __launch_bounds__(384, 1)
k_chain(const __grid_constant__ CUtensorMap xmap, const __grid_constant__ CUtensorMap wqmap, const __grid_constant__ CUtensorMap wkmap,
        const __grid_constant__ CUtensorMap wvmap, const __grid_constant__ CUtensorMap womap, const bf16* __restrict__ xptr, const bf16* __restrict__ mem0) {
    extern __shared__ __align__(1024) unsigned char smem[];
    const uint32_t sb = smem_u32(smem);
    const int tid = threadIdx.x, lane = tid & 31;
    const int wg = __shfl_sync(~0u, tid >> 7, 0), warp = __shfl_sync(~0u, (tid >> 5) & 3, 0);
    uint32_t rank; asm volatile("mov.u32 %0, %%cluster_ctarank;" : "=r"(rank));
    const int cta = blockIdx.x, h = cta / 3;
    asm volatile("griddepcontrol.launch_dependents;");
    if (tid == 0) {
        for (int i = 0; i < 2; i++) { mbar_init(sb + B_SC + 8 * i, rank < 2 ? 6 : 1); mbar_init(sb + B_V + 8 * i, 1); mbar_init(sb + B_X + 8 * i, 1); }
        mbar_init(sb + B_P, 1); mbar_init(sb + B_EXP, 1);
        asm volatile("fence.mbarrier_init.release.cluster;" ::: "memory");
    }
    if (tid < 80) asm volatile("prefetch.global.L2 [%0];" :: "l"(mem0 + tid * 64));
    if (h < 2) { for (int i = tid; i < 320; i += 384) asm volatile("prefetch.global.L2 [%0];" :: "l"(xptr + (size_t)h * 32 * DM + i * 64)); }
    {
        uint4* z = reinterpret_cast<uint4*>(g_pool + (size_t)cta * 6 * 1024);
        #pragma unroll
        for (int q = 0; q < 4; q++) z[tid + 384 * q] = make_uint4(0, 0, 0, 0);
        if (tid < 2) reinterpret_cast<uint4*>(g_pool + (size_t)NPOOL * 1024 + (cta & 31) * 32 + (cta >> 5) * 8)[tid] = make_uint4(0, 0, 0, 0);
    }
    __syncthreads();
    {
        const int w12 = tid >> 5;
        if (lane == 0 && w12 < 7) {
            uint32_t* pp = (w12 < 6) ? g_pool + (size_t)(cta * 6 + w12) * 1024 + 512 : g_pool + (size_t)NPOOL * 1024 + (cta & 31) * 32 + (cta >> 5) * 8;
            const unsigned lat = probe_latency(pp, blockIdx.y);
            if (w12 < 6) g_cls[cta * 6 + w12] = lat > CAL_THR ? 1u : 0u; else g_side[cta] = lat > CAL_THR ? 1u : 0u;
        }
        __syncwarp();
        __threadfence();
        __syncwarp();
        if (lane == 0) atomicAdd(&g_calcnt, 1u);
    }
    __syncthreads();
    if (tid == 0) {
        const int ntile = (rank == 2) ? 4 : 3;
        const int tile0 = (rank == 2) ? 0 : (rank == 0 ? 4 : 7);
        mbar_expect_tx(sb + B_P, 163840 + ntile * 16384);
        const void* m0 = (rank == 2) ? &wvmap : &wqmap;
        const void* m1 = (rank == 2) ? &wvmap : &wkmap;
        const int c0 = h * DH + (rank == 1 ? 64 : 0), c1 = h * DH + (rank == 0 ? 0 : 64);
        for (int b = 0; b < 5; b++) {
            tma_load_2d(sb + b * 16384, m0, c0, b * 128, sb + B_P);
            tma_load_2d(sb + 81920 + b * 16384, m1, c1, b * 128, sb + B_P);
        }
        for (int lt = 0; lt < ntile; lt++) {
            tma_load_2d(sb + SM_WO + lt * 16384, &womap, (tile0 + lt) * 64, h * DH, sb + B_P);
            tma_load_2d(sb + SM_WO + lt * 16384 + 8192, &womap, (tile0 + lt) * 64, h * DH + 64, sb + B_P);
        }
    }
    {
        const int tile0 = (rank == 2) ? 0 : (rank == 0 ? 4 : 7);
        if (wg == 2) {
            const int ct = tid & 127;
            if (ct == 0) {
                const unsigned target = (*reinterpret_cast<volatile unsigned*>(&g_epoch) + 1u) * (96u * 12u);
                int guard = 0;
                while ((int)(ld_acquire(&g_calcnt) - target) < 0 && ++guard < (1 << 22)) {}
            }
            nbar_sync(4, 128);
            uint32_t* bm = reinterpret_cast<uint32_t*>(smem + SM_CAL);
            {
                unsigned v[5];
                #pragma unroll
                for (int q = 0; q < 5; q++) { const int b = ct + 128 * q; v[q] = (b < NPOOL) ? (__ldcg(&g_cls[b]) ^ __ldcg(&g_side[b / 6])) : 0u; }
                const unsigned sv = (ct < 96) ? __ldcg(&g_side[ct]) : 0u;
                #pragma unroll
                for (int q = 0; q < 5; q++) { const unsigned m = __ballot_sync(~0u, v[q] & 1u); if (lane == 0 && q * 4 + warp < 18) bm[q * 4 + warp] = m; }
                const unsigned m = __ballot_sync(~0u, sv & 1u);
                if (lane == 0 && warp < 3) bm[18 + warp] = m;
            }
            nbar_sync(4, 128);
            int nblk1 = 0;
            for (int i = 0; i < 18; i++) nblk1 += __popc(bm[i]);
            const unsigned red_last = (1u << (NRED - 64)) - 1u;
            const int nred1 = __popc(bm[18]) + __popc(bm[19]) + __popc(bm[20] & red_last);
            auto side_of = [&](int c) -> int { return (bm[18 + (c >> 5)] >> (c & 31)) & 1; };
            auto rank_of = [&](int c) -> int {
                int ones = 0;
                for (int i = 0; i < (c >> 5); i++) ones += __popc(bm[18 + i]);
                ones += __popc(bm[18 + (c >> 5)] & ((1u << (c & 31)) - 1u));
                return side_of(c) ? ones : c - ones;
            };
            auto nth = [&](int side, int idx) -> uint32_t {
                for (int i = 0; i < 18; i++) {
                    const unsigned m = side ? bm[i] : ~bm[i];
                    const int n = __popc(m);
                    if (idx < n) return (uint32_t)(i * 32 + __fns(m, 0, idx + 1));
                    idx -= n;
                }
                return 0u;
            };
            auto phys = [&](int side, int idx) -> uint32_t {
                const int c = side ? nblk1 : NPOOL - nblk1;
                return (idx < c) ? nth(side, idx) : nth(side ^ 1, (NPOOL - c) - 1 - (idx - c));
            };
            const int e = ct;
            if (e < 64) {
                const int slot = e >> 5, lt = (e >> 3) & 3, w = (e >> 1) & 3, hf = e & 1;
                const int tile = min(tile0 + lt, 9);
                const int r = 2 * (4 * tile + w) + hf;
                reinterpret_cast<uint32_t*>(smem + SM_TPM)[e] = phys(side_of(r), 4 * rank_of(r) + slot * 2 + (h >> 4)) * 4096u + (h & 15) * 256u;
            } else if (e < 68) {
                const int i = e - 64;
                reinterpret_cast<uint32_t*>(smem + SM_TRD)[i] = (cta < NRED) ? phys(side_of(cta), 4 * rank_of(cta) + i) * 4096u : 0u;
            } else if (e < 100) {
                const int i = e - 68, slot = i >> 3, rep = i & 7, side = (rep / RPS) & 1;
                reinterpret_cast<uint32_t*>(smem + SM_TPUB)[i] = phys(side, 4 * (side ? nred1 : NRED - nred1) + (slot * RPS + (rep % RPS)) * 3 + (cta >> 5)) * 4096u + (cta & 31) * 128u;
            } else if (e < 112) {
                const int i = e - 100, slot = i / 3, b = i % 3, side = side_of(cta);
                reinterpret_cast<uint32_t*>(smem + SM_TGAT)[slot * 4 + b] = phys(side, 4 * (side ? nred1 : NRED - nred1) + (slot * RPS + (h % RPS)) * 3 + b) * 4096u;
            }
        }
    }
    __syncthreads();
    mbar_wait_sleep(sb + B_P, 0);

    if (wg == 2) {
        asm volatile("setmaxnreg.dec.sync.aligned.u32 " COMM_REGS ";");
        const int ct = tid & 127;
        nbar_sync(5, 384);
        for (int c = ct; c < 640; c += 128) {
            int ks = c >> 4, hf = (c >> 3) & 1, r = c & 7;
            *reinterpret_cast<uint4*>(smem + SM_MEMB + c * 16) = *reinterpret_cast<const uint4*>(mem0 + r * DM + ks * 16 + hf * 8);
        }
        if (ct == 0) {
            for (int sg = 0; sg < 2; sg++) {
                mbar_expect_tx(sb + B_X + 8 * sg, 40960);
                tma_load_3d(sb + SM_XB + sg * 40960, &xmap, 0, sg * 32, 0, sb + B_X + 8 * sg);
            }
            mbar_expect_tx(sb + B_SC, rank < 2 ? 1280 : 2560);
            if (rank < 2) mbar_expect_tx(sb + B_V, 8192 + 2048);
        }
        nbar_sync(5, 384);
        cluster_sync_all();
        unsigned char* const pool = reinterpret_cast<unsigned char*>(g_pool);
        for (int s = 0; s < NSEG - 1; s++) {
            if (warp == 1) nbar_sync(12, 288);
            if (warp == 0) {
                const int g = lane >> 2, t = lane & 3;
                mbar_wait(sb + B_SC + 8 * (s & 1), (s >> 1) & 1);
                TR(5);
                const uint32_t sa = sb + SM_SC + (s & 1) * 2560 + (g * 40 + 2 * t) * 4;
                float v[5][2], u[5][2];
                #pragma unroll
                for (int q = 0; q < 5; q++) {
                    asm volatile("ld.shared.v2.f32 {%0,%1}, [%2];" : "=f"(v[q][0]), "=f"(v[q][1]) : "r"(sa + 32 * q) : "memory");
                    asm volatile("ld.shared.v2.f32 {%0,%1}, [%2];" : "=f"(u[q][0]), "=f"(u[q][1]) : "r"(sa + 1280 + 32 * q) : "memory");
                }
                float mx = -3.0e38f;
                #pragma unroll
                for (int q = 0; q < 5; q++) {
                    v[q][0] += u[q][0]; v[q][1] += u[q][1];
                    mx = fmaxf(mx, fmaxf(v[q][0], v[q][1]));
                }
                mx = fmaxf(mx, __shfl_xor_sync(~0u, mx, 1));
                mx = fmaxf(mx, __shfl_xor_sync(~0u, mx, 2));
                const float sc2 = 0.08838834764831845f * 1.4426950408889634f;
                const float mxs = mx * sc2;
                uint32_t* pbs = reinterpret_cast<uint32_t*>(smem + SM_PB);
                #pragma unroll
                for (int q = 0; q < 5; q++) {
                    const float e0 = ex2_approx(fmaf(v[q][0], sc2, -mxs)), e1 = ex2_approx(fmaf(v[q][1], sc2, -mxs));
                    pbs[q * 32 + lane] = pack_bf16(e0, e1);
                }
                __syncwarp();
                TR(0);
                nbar_arrive(9, 288);
            } else if (warp == 1 && lane == 0) {
                if (s + 1 < NSEG - 1) {
                    mbar_expect_tx(sb + B_SC + 8 * ((s + 1) & 1), rank < 2 ? 1280 : 2560);
                    if (rank < 2) mbar_expect_tx(sb + B_V + 8 * ((s + 1) & 1), 8192 + 2048);
                }
                if (s + 2 < NSEG) {
                    mbar_expect_tx(sb + B_X + 8 * (s & 1), 40960);
                    tma_load_3d(sb + SM_XB + (s & 1) * 40960, &xmap, 0, (s + 2) * 32, 0, sb + B_X + 8 * (s & 1));
                }
                export_issue(sb, s, h, rank);
                if (s >= NSEG - 4) export_signal(s, h);
            }
            __syncwarp();
            nbar_sync(3, 384);
            const uint32_t tg = tag_of(s);
            if (cta < NRED) {
                const unsigned char* base = pool + reinterpret_cast<const uint32_t*>(smem + SM_TRD)[(s & 1) * 2 + (warp >> 1)] + (warp & 1) * 2048 + lane * 16;
                uint4 v[4]; int guard = 0;
                #pragma unroll
                for (int j = 0; j < 4; j++) v[j] = make_uint4(0, 0, 0, 0);
                uint32_t pend = 0xF;
                do {
                    #pragma unroll
                    for (int j = 0; j < 4; j++) if (pend & (1u << j)) v[j] = ld_relaxed4(base + j * 512);
                    #pragma unroll
                    for (int j = 0; j < 4; j++)
                        if (((v[j].x & 3) == tg) && ((v[j].y & 3) == tg) && ((v[j].z & 3) == tg) && ((v[j].w & 3) == tg)) pend &= ~(1u << j);
                } while (__any_sync(~0u, pend != 0) && ++guard < (1 << 20));
                if (warp == 0) TR(9);
                float a0 = 0, a1 = 0, a2 = 0, a3 = 0;
                #pragma unroll
                for (int j = 0; j < 4; j++) { a0 += __uint_as_float(v[j].x); a1 += __uint_as_float(v[j].y); a2 += __uint_as_float(v[j].z); a3 += __uint_as_float(v[j].w); }
                a0 += __shfl_xor_sync(~0u, a0, 16); a1 += __shfl_xor_sync(~0u, a1, 16); a2 += __shfl_xor_sync(~0u, a2, 16); a3 += __shfl_xor_sync(~0u, a3, 16);
                float* cr = reinterpret_cast<float*>(smem + SM_CRED);
                if (lane < 16) *reinterpret_cast<float4*>(cr + warp * 64 + lane * 4) = make_float4(a0, a1, a2, a3);
                nbar_sync(4, 128);
                {
                    int rho = lane >> 2, pp = lane & 3;
                    int i0 = ((2 * pp) * 4 + (rho >> 1)) * 2 + (rho & 1), i1 = i0 + 8;
                    uint32_t wv = pack_bf16((cr[i0] + cr[64 + i0]) + (cr[128 + i0] + cr[192 + i0]), (cr[i1] + cr[64 + i1]) + (cr[128 + i1] + cr[192 + i1]));
                    if (wv == 0) wv = 0x8000u;
                    if (warp == 0) TR(10);
                    const uint32_t* tp = reinterpret_cast<const uint32_t*>(smem + SM_TPUB) + warp;
                    if (warp < 2 * RPS) st_relaxed1(pool + tp[((s + 1) & 3) * 8] + lane * 4, wv);
                    if (RPS == 4) st_relaxed1(pool + tp[((s + 1) & 3) * 8 + 4] + lane * 4, wv);
                    if (warp < 2 * RPS) st_relaxed1(pool + tp[(s & 3) * 8] + lane * 4, 0u);
                    if (RPS == 4) st_relaxed1(pool + tp[(s & 3) * 8 + 4] + lane * 4, 0u);
                }
            }
            {
                const int c0 = warp * 160 + lane;
                const uint32_t* tg3 = reinterpret_cast<const uint32_t*>(smem + SM_TGAT) + ((s + 1) & 3) * 4;
                const uint32_t g0 = tg3[0], g1 = tg3[1], g2 = tg3[2];
                uint4 v[5]; int guard = 0;
                #pragma unroll
                for (int j = 0; j < 5; j++) v[j] = make_uint4(0, 0, 0, 0);
                uint32_t pend = 0x1F;
                do {
                    #pragma unroll
                    for (int j = 0; j < 5; j++) {
                        const int c = c0 + 32 * j;
                        if (pend & (1u << j)) v[j] = ld_relaxed4(pool + ((c >> 8) == 0 ? g0 : ((c >> 8) == 1 ? g1 : g2)) + (c & 255) * 16);
                    }
                    #pragma unroll
                    for (int j = 0; j < 5; j++) if (v[j].x && v[j].y && v[j].z && v[j].w) pend &= ~(1u << j);
                } while (__any_sync(~0u, pend != 0) && ++guard < (1 << 20));
                #pragma unroll
                for (int j = 0; j < 5; j++) *reinterpret_cast<uint4*>(smem + SM_MEMB + (c0 + 32 * j) * 16) = v[j];
                if (warp == 0) TR(11);
                if (warp == 3) TR(12);
                nbar_arrive(warp < 2 ? 7 + warp : 8 + warp, 160);
            }
            if (warp == 1 && lane == 0 && s < NSEG - 4) export_signal(s, h);
            __syncwarp();
        }
        if (warp == 1) { nbar_sync(12, 288); if (lane == 0) { export_issue(sb, NSEG - 1, h, rank); export_signal(NSEG - 1, h); } }
        __syncwarp();
        nbar_sync(3, 384);
        __syncwarp();
        cluster_sync_all();
    } else {
        asm volatile("setmaxnreg.inc.sync.aligned.u32 232;");
        const int wtid = tid & 127;
        const int cw = wg * 4 + warp;
        uint32_t areg[2][20][4];
        #pragma unroll
        for (int mt = 0; mt < 2; mt++)
            #pragma unroll
            for (int kk = 0; kk < 20; kk++) {
                int mi = lane >> 3;
                int row = 16 * (20 * wg + kk) + (mi >> 1) * 8 + (lane & 7);
                int chunk = 2 * warp + (mi & 1);
                ldsm4t(areg[mt][kk], sb + mt * 81920 + row * 128 + ((chunk ^ (row & 7)) << 4));
            }
        nbar_sync(5, 384);
        nbar_sync(5, 384);
        cluster_sync_all();

        for (int s = -1; s < NSEG; s++) {
            const int sl = s & 1;
            if (s >= 0) {
            if (s > 0) nbar_sync(7 + 3 * wg, 160);
            float fin[4];
            {
                float acc[2][2][4];
                #pragma unroll
                for (int i = 0; i < 2; i++)
                    #pragma unroll
                    for (int j = 0; j < 2; j++) { acc[i][j][0] = acc[i][j][1] = acc[i][j][2] = acc[i][j][3] = 0.f; }
                uint32_t b[3][4];
                const uint32_t mb = sb + SM_MEMB + (20 * wg) * 256 + lane * 16;
                ldsm4(b[0], mb); ldsm4(b[1], mb + 512);
                #pragma unroll
                for (int kp = 0; kp < 10; kp++) {
                    if (kp == 3 && s > 0) nbar_sync(8 + 3 * wg, 160);
                    if (kp + 2 < 10) ldsm4(b[(kp + 2) % 3], mb + (kp + 2) * 512);
                    const uint32_t (&bb)[4] = b[kp % 3];
                    mma_bf16(acc[0][0], areg[0][2 * kp][0], areg[0][2 * kp][1], areg[0][2 * kp][2], areg[0][2 * kp][3], bb[0], bb[1]);
                    mma_bf16(acc[1][0], areg[1][2 * kp][0], areg[1][2 * kp][1], areg[1][2 * kp][2], areg[1][2 * kp][3], bb[0], bb[1]);
                    mma_bf16(acc[0][1], areg[0][2 * kp + 1][0], areg[0][2 * kp + 1][1], areg[0][2 * kp + 1][2], areg[0][2 * kp + 1][3], bb[2], bb[3]);
                    mma_bf16(acc[1][1], areg[1][2 * kp + 1][0], areg[1][2 * kp + 1][1], areg[1][2 * kp + 1][2], areg[1][2 * kp + 1][3], bb[2], bb[3]);
                }
                float4* red = reinterpret_cast<float4*>(smem + SM_RED);
                float m0[4], m1[4];
                #pragma unroll
                for (int i = 0; i < 4; i++) { m0[i] = acc[0][0][i] + acc[0][1][i]; m1[i] = acc[1][0][i] + acc[1][1][i]; }
                red[(wg ^ 1) * 128 + wtid] = wg == 0 ? make_float4(m1[0], m1[1], m1[2], m1[3]) : make_float4(m0[0], m0[1], m0[2], m0[3]);
                nbar_sync(1, 256);
                float4 r = red[wg * 128 + wtid];
                fin[0] = (wg == 0 ? m0[0] : m1[0]) + r.x; fin[1] = (wg == 0 ? m0[1] : m1[1]) + r.y;
                fin[2] = (wg == 0 ? m0[2] : m1[2]) + r.z; fin[3] = (wg == 0 ? m0[3] : m1[3]) + r.w;
            }
            if (cw == 0) TR(1);
            {
                uint32_t p0 = pack_bf16(fin[0], fin[1]), p1 = pack_bf16(fin[2], fin[3]);
                const uint32_t doff = (rank == 2) ? SM_VT + sl * 10240 + wg * 5120 : (wg == 0 ? SM_QS : SM_KT + sl * 5120);
                const int r = lane & 7, chunk = 2 * warp + ((lane >> 3) & 1);
                const uint32_t coff = doff + r * 128 + ((chunk ^ r) << 4);
                stsm2t(sb + coff, p0, p1);
                if (rank == 2 && s < NSEG - 1) {
                    __syncwarp();
                    const uint4 v = *reinterpret_cast<const uint4*>(smem + coff);
                    const uint32_t rb = mapa(sb, lane >> 4);
                    st_async4u(rb + coff, v, rb + B_V + 8 * sl);
                }
            }
            fence_async();
            nbar_sync(1, 256);
            nbar_arrive(12, 288);
            if (cw == 0) TR(2);
            if (rank < 2 && s < NSEG - 1) {
                if (wg == 1) score_tile(sb, sl, 1 + warp, lane, rank);
                else if (warp == 0) score_tile(sb, sl, 0, lane, rank);
            }
            if (s == NSEG - 1) break;
            if (cw == 0) TR(3);
            if (wg == 0 || rank == 2) u_pass<2>(smem, sb, s, rank, wg, warp, lane);
            else                      u_pass<1>(smem, sb, s, rank, wg, warp, lane);
            if (cw == 0) TR(7);
            nbar_arrive(3, 384);
            }
            {
                const int sn = s + 1, sln = sn & 1;
                mbar_wait(sb + B_X + 8 * sln, (sn >> 1) & 1);
                float acc[2][16];
                wg_fence();
                #pragma unroll
                for (int mt = 0; mt < 2; mt++)
                    #pragma unroll
                    for (int kk = 0; kk < 20; kk++) {
                        uint64_t db = make_desc(sb + SM_XB + sln * 40960 + (5 * wg + (kk >> 2)) * 4096 + (kk & 3) * 32, 16, 1024);
                        wgmma_n32_rs(acc[mt], areg[mt][kk], db, kk > 0);
                    }
                wg_commit();
                if (cw == 0 && s >= 0) TR(14);
                wg_wait0();
                if (cw == 0 && s >= 0) TR(15);
                float4* red = reinterpret_cast<float4*>(smem + SM_RED);
                #pragma unroll
                for (int j = 0; j < 4; j++) {
                    red[((wg ^ 1) * 4 + j) * 128 + wtid] = make_float4(wg == 0 ? acc[1][4 * j] : acc[0][4 * j], wg == 0 ? acc[1][4 * j + 1] : acc[0][4 * j + 1],
                                                                       wg == 0 ? acc[1][4 * j + 2] : acc[0][4 * j + 2], wg == 0 ? acc[1][4 * j + 3] : acc[0][4 * j + 3]);
                }
                if (s >= 0) mbar_wait(sb + B_EXP, s & 1);
                nbar_sync(1, 256);
                uint32_t pk[8];
                #pragma unroll
                for (int j = 0; j < 4; j++) {
                    float4 r = red[(wg * 4 + j) * 128 + wtid];
                    pk[2 * j] = pack_bf16((wg == 0 ? acc[0][4 * j] : acc[1][4 * j]) + r.x, (wg == 0 ? acc[0][4 * j + 1] : acc[1][4 * j + 1]) + r.y);
                    pk[2 * j + 1] = pack_bf16((wg == 0 ? acc[0][4 * j + 2] : acc[1][4 * j + 2]) + r.z, (wg == 0 ? acc[0][4 * j + 3] : acc[1][4 * j + 3]) + r.w);
                }
                const uint32_t dst = (rank == 2) ? sb + SM_VT + sln * 10240 + wg * 5120 + 1024 : (wg == 0 ? sb + SM_QT : sb + SM_KT + sln * 5120 + 1024);
                #pragma unroll
                for (int jj = 0; jj < 2; jj++) {
                    int mi = lane >> 3, tok = 8 * (2 * jj + (mi >> 1)) + (lane & 7), chunk = 2 * warp + (mi & 1);
                    stsm4t(dst + tok * 128 + ((chunk ^ (tok & 7)) << 4), pk[4 * jj], pk[4 * jj + 1], pk[4 * jj + 2], pk[4 * jj + 3]);
                }
                fence_async();
                nbar_sync(1, 256);
                if (rank == 2 && lane == 0 && cw < 4 && sn < NSEG - 1) {
                    const uint32_t off = SM_VT + sln * 10240 + (cw & 1) * 5120 + 1024;
                    const uint32_t rb = mapa(sb, cw >> 1);
                    bulk_s2c(rb + off, sb + off, 4096, rb + B_V + 8 * sln);
                }
                if (cw == 0 && s >= 0) TR(13);
            }
        }
        nbar_arrive(3, 384);
        __syncwarp();
        cluster_sync_all();
    }
}

#define NAUX 36
__device__ __align__(1024) bf16 g_Oimg[16 * 64 * 128 * 64];
__device__ float    g_part[4 * SEQ * DM];
__device__ float    g_part31[3 * 16 * 64 * DM];
__device__ unsigned g_ocnt[32];
__device__ unsigned g_gcnt[32][2];
__device__ unsigned g_ssmcnt, g_auxdone, g_taskctr, g_gemmctr;
#define NATT 8
#define ATR(i) do {} while (0)
#define ATRID(i, id) do {} while (0)

__device__ __forceinline__ void wait_counter(const unsigned* p, unsigned target) {
    int guard = 0;
    while ((int)(ld_acquire(p) - target) < 0 && ++guard < (1 << 22)) __nanosleep(64);
}
__device__ __forceinline__ void fence_async_all() { asm volatile("fence.proxy.async;" ::: "memory"); }
template <int OFF>
__device__ __forceinline__ void wgmma_n192_tB(float (&d)[160], uint64_t da, uint64_t db) {
    asm volatile("wgmma.mma_async.sync.aligned.m64n192k16.f32.bf16.bf16 {%0,%1,%2,%3,%4,%5,%6,%7,%8,%9,%10,%11,%12,%13,%14,%15,%16,%17,%18,%19,%20,%21,%22,%23,%24,%25,%26,%27,%28,%29,%30,%31,%32,%33,%34,%35,%36,%37,%38,%39,%40,%41,%42,%43,%44,%45,%46,%47,%48,%49,%50,%51,%52,%53,%54,%55,%56,%57,%58,%59,%60,%61,%62,%63,%64,%65,%66,%67,%68,%69,%70,%71,%72,%73,%74,%75,%76,%77,%78,%79,%80,%81,%82,%83,%84,%85,%86,%87,%88,%89,%90,%91,%92,%93,%94,%95}, %96, %97, 1, 1, 1, 0, 1;\n"
        : "+f"(d[OFF + 0]), "+f"(d[OFF + 1]), "+f"(d[OFF + 2]), "+f"(d[OFF + 3]), "+f"(d[OFF + 4]), "+f"(d[OFF + 5]), "+f"(d[OFF + 6]), "+f"(d[OFF + 7]), "+f"(d[OFF + 8]), "+f"(d[OFF + 9]), "+f"(d[OFF + 10]), "+f"(d[OFF + 11]), "+f"(d[OFF + 12]), "+f"(d[OFF + 13]), "+f"(d[OFF + 14]), "+f"(d[OFF + 15]), "+f"(d[OFF + 16]), "+f"(d[OFF + 17]), "+f"(d[OFF + 18]), "+f"(d[OFF + 19]), "+f"(d[OFF + 20]), "+f"(d[OFF + 21]), "+f"(d[OFF + 22]), "+f"(d[OFF + 23]), "+f"(d[OFF + 24]), "+f"(d[OFF + 25]), "+f"(d[OFF + 26]), "+f"(d[OFF + 27]), "+f"(d[OFF + 28]), "+f"(d[OFF + 29]), "+f"(d[OFF + 30]), "+f"(d[OFF + 31]), "+f"(d[OFF + 32]), "+f"(d[OFF + 33]), "+f"(d[OFF + 34]), "+f"(d[OFF + 35]), "+f"(d[OFF + 36]), "+f"(d[OFF + 37]), "+f"(d[OFF + 38]), "+f"(d[OFF + 39]), "+f"(d[OFF + 40]), "+f"(d[OFF + 41]), "+f"(d[OFF + 42]), "+f"(d[OFF + 43]), "+f"(d[OFF + 44]), "+f"(d[OFF + 45]), "+f"(d[OFF + 46]), "+f"(d[OFF + 47]), "+f"(d[OFF + 48]), "+f"(d[OFF + 49]), "+f"(d[OFF + 50]), "+f"(d[OFF + 51]), "+f"(d[OFF + 52]), "+f"(d[OFF + 53]), "+f"(d[OFF + 54]), "+f"(d[OFF + 55]), "+f"(d[OFF + 56]), "+f"(d[OFF + 57]), "+f"(d[OFF + 58]), "+f"(d[OFF + 59]), "+f"(d[OFF + 60]), "+f"(d[OFF + 61]), "+f"(d[OFF + 62]), "+f"(d[OFF + 63]), "+f"(d[OFF + 64]), "+f"(d[OFF + 65]), "+f"(d[OFF + 66]), "+f"(d[OFF + 67]), "+f"(d[OFF + 68]), "+f"(d[OFF + 69]), "+f"(d[OFF + 70]), "+f"(d[OFF + 71]), "+f"(d[OFF + 72]), "+f"(d[OFF + 73]), "+f"(d[OFF + 74]), "+f"(d[OFF + 75]), "+f"(d[OFF + 76]), "+f"(d[OFF + 77]), "+f"(d[OFF + 78]), "+f"(d[OFF + 79]), "+f"(d[OFF + 80]), "+f"(d[OFF + 81]), "+f"(d[OFF + 82]), "+f"(d[OFF + 83]), "+f"(d[OFF + 84]), "+f"(d[OFF + 85]), "+f"(d[OFF + 86]), "+f"(d[OFF + 87]), "+f"(d[OFF + 88]), "+f"(d[OFF + 89]), "+f"(d[OFF + 90]), "+f"(d[OFF + 91]), "+f"(d[OFF + 92]), "+f"(d[OFF + 93]), "+f"(d[OFF + 94]), "+f"(d[OFF + 95])
        : "l"(da), "l"(db));
}
template <int OFF>
__device__ __forceinline__ void wgmma_n128_tB(float (&d)[160], uint64_t da, uint64_t db) {
    asm volatile("wgmma.mma_async.sync.aligned.m64n128k16.f32.bf16.bf16 {%0,%1,%2,%3,%4,%5,%6,%7,%8,%9,%10,%11,%12,%13,%14,%15,%16,%17,%18,%19,%20,%21,%22,%23,%24,%25,%26,%27,%28,%29,%30,%31,%32,%33,%34,%35,%36,%37,%38,%39,%40,%41,%42,%43,%44,%45,%46,%47,%48,%49,%50,%51,%52,%53,%54,%55,%56,%57,%58,%59,%60,%61,%62,%63}, %64, %65, 1, 1, 1, 0, 1;\n"
        : "+f"(d[OFF + 0]), "+f"(d[OFF + 1]), "+f"(d[OFF + 2]), "+f"(d[OFF + 3]), "+f"(d[OFF + 4]), "+f"(d[OFF + 5]), "+f"(d[OFF + 6]), "+f"(d[OFF + 7]), "+f"(d[OFF + 8]), "+f"(d[OFF + 9]), "+f"(d[OFF + 10]), "+f"(d[OFF + 11]), "+f"(d[OFF + 12]), "+f"(d[OFF + 13]), "+f"(d[OFF + 14]), "+f"(d[OFF + 15]), "+f"(d[OFF + 16]), "+f"(d[OFF + 17]), "+f"(d[OFF + 18]), "+f"(d[OFF + 19]), "+f"(d[OFF + 20]), "+f"(d[OFF + 21]), "+f"(d[OFF + 22]), "+f"(d[OFF + 23]), "+f"(d[OFF + 24]), "+f"(d[OFF + 25]), "+f"(d[OFF + 26]), "+f"(d[OFF + 27]), "+f"(d[OFF + 28]), "+f"(d[OFF + 29]), "+f"(d[OFF + 30]), "+f"(d[OFF + 31]), "+f"(d[OFF + 32]), "+f"(d[OFF + 33]), "+f"(d[OFF + 34]), "+f"(d[OFF + 35]), "+f"(d[OFF + 36]), "+f"(d[OFF + 37]), "+f"(d[OFF + 38]), "+f"(d[OFF + 39]), "+f"(d[OFF + 40]), "+f"(d[OFF + 41]), "+f"(d[OFF + 42]), "+f"(d[OFF + 43]), "+f"(d[OFF + 44]), "+f"(d[OFF + 45]), "+f"(d[OFF + 46]), "+f"(d[OFF + 47]), "+f"(d[OFF + 48]), "+f"(d[OFF + 49]), "+f"(d[OFF + 50]), "+f"(d[OFF + 51]), "+f"(d[OFF + 52]), "+f"(d[OFF + 53]), "+f"(d[OFF + 54]), "+f"(d[OFF + 55]), "+f"(d[OFF + 56]), "+f"(d[OFF + 57]), "+f"(d[OFF + 58]), "+f"(d[OFF + 59]), "+f"(d[OFF + 60]), "+f"(d[OFF + 61]), "+f"(d[OFF + 62]), "+f"(d[OFF + 63])
        : "l"(da), "l"(db));
}
__device__ __forceinline__ void stsm4(uint32_t addr, uint32_t r0, uint32_t r1, uint32_t r2, uint32_t r3) {
    asm volatile("stmatrix.sync.aligned.m8n8.x4.shared.b16 [%0], {%1,%2,%3,%4};" :: "r"(addr), "r"(r0), "r"(r1), "r"(r2), "r"(r3) : "memory");
}

#define AX_BAR   0
#define NST_G 4
#define AX_EMPTY (AX_BAR + 16 + 8 * NST_G)
#define AX_DONE  (AX_EMPTY + 8 * NST_G)
#define AX_DATA  1024
#define AX_UNIT  28672
#define AX_STAGE 57344
#define AX_TOTAL (AX_DATA + 8 * AX_UNIT)

__device__ __forceinline__ void attn_compute(unsigned char* smem, uint32_t sb, uint32_t buf, int warp, int lane);
__device__ __forceinline__ void attn_producer(unsigned char* smem, int hg, unsigned epoch) {
    const uint32_t sb = smem_u32(smem);
    const int lane = threadIdx.x & 31;
    {
        for (int s = 0; s < NSEG; s++) {
            const uint32_t buf = AX_DATA + (s & 1) * (4 * AX_UNIT), bar = sb + AX_BAR + 8 * (s & 1);
            if (lane < 4) wait_counter(&g_flag[s][4 * hg + lane], (epoch + 1) * 3u);
            if (lane == 4) mbar_wait_sleep(sb + AX_EMPTY + 8 * (s & 1), ((s >> 1) & 1) ^ 1);
            __syncwarp();
            if (lane == 0) mbar_expect_tx(bar, 4 * AX_UNIT);
            __syncwarp();
            if (lane < 24) {
                fence_async_all();
                const int u = lane / 6, r = lane % 6, hf = r & 1, kind = r >> 1;
                const uint32_t ub = sb + buf + u * AX_UNIT;
                const size_t img = ((size_t)(s * NH + 4 * hg + u) * 2) + hf;
                if (kind == 0) bulk_g2s(ub + hf * 4096, g_Qimg + img * 2048, 4096, bar);
                else if (kind == 1) bulk_g2s(ub + 8192 + hf * 5120, g_Kimg + img * 2560, 5120, bar);
                else bulk_g2s(ub + 18432 + hf * 5120, g_Vimg + img * 2560, 5120, bar);
            }
            __syncwarp();
        }
    }
}
__device__ __forceinline__ void attn_loop(unsigned char* smem, int hg, unsigned epoch) {
    const uint32_t sb = smem_u32(smem);
    const int tid = threadIdx.x, warp = tid >> 5, lane = tid & 31;
    for (int s = 0; s < NSEG; s++) {
        const uint32_t buf = AX_DATA + (s & 1) * (4 * AX_UNIT), bar = sb + AX_BAR + 8 * (s & 1);
        mbar_wait_sleep(bar, (s >> 1) & 1);
        if (s >= 36) ATR(2 + 2 * (s - 36));
        attn_compute(smem, sb, buf, warp, lane);
        if (s >= 36) ATR(3 + 2 * (s - 36));
        fence_async();
        __syncwarp();
        if (lane == 0) mbar_arrive(sb + AX_EMPTY + 16 + 8 * (s & 1));
    }
}
__device__ __forceinline__ void attn_storer(unsigned char* smem, int hg) {
    const uint32_t sb = smem_u32(smem);
    const int lane = threadIdx.x & 31;
    for (int s = 0; s < NSEG; s++) {
        const uint32_t buf = AX_DATA + (s & 1) * (4 * AX_UNIT);
        mbar_wait_sleep(sb + AX_EMPTY + 16 + 8 * (s & 1), (s >> 1) & 1);
        if (lane < 8) {
            const int uu = lane >> 1, hf = lane & 1, hh = 4 * hg + uu;
            bulk_s2g(g_Oimg + (((size_t)(s >> 2) * 64 + hh * 2 + hf) * 128 + (s & 3) * 32) * 64, sb + buf + uu * AX_UNIT + hf * 4096, 4096);
            bulk_commit();
            bulk_wait_read0();
            mbar_arrive(sb + AX_EMPTY + 8 * (s & 1));
            bulk_wait0();
            fence_async_all();
            __threadfence();
            atomicAdd(&g_ocnt[s >> 1], 1u);
        }
        __syncwarp();
    }
}
__device__ __forceinline__ void attn_compute(unsigned char* smem, uint32_t sb, uint32_t buf, int warp, int lane) {
    const int g = lane >> 2, t = lane & 3;
    const int u = warp >> 1, qh = warp & 1;
    const uint32_t ub = sb + buf + u * AX_UNIT;
    float sc[5][4];
    #pragma unroll
    for (int j = 0; j < 5; j++) { sc[j][0] = sc[j][1] = sc[j][2] = sc[j][3] = 0.f; }
    #pragma unroll
    for (int ks = 0; ks < 8; ks++) {
        const int hf = ks >> 2, c0 = (ks & 3) * 2;
        uint32_t a[4];
        { int mi = lane >> 3, row = 16 * qh + (mi & 1) * 8 + (lane & 7), chunk = c0 + (mi >> 1);
          ldsm4(a, ub + hf * 4096 + row * 128 + ((chunk ^ (row & 7)) << 4)); }
        #pragma unroll
        for (int jp = 0; jp < 3; jp++) {
            uint32_t b[4];
            int mi = lane >> 3, nt = 2 * jp + (mi >> 1); if (nt > 4) nt = 4;
            int row = 8 * nt + (lane & 7), chunk = c0 + (mi & 1);
            ldsm4(b, ub + 8192 + hf * 5120 + row * 128 + ((chunk ^ (row & 7)) << 4));
            mma_bf16(sc[2 * jp], a[0], a[1], a[2], a[3], b[0], b[1]);
            if (jp < 2) mma_bf16(sc[2 * jp + 1], a[0], a[1], a[2], a[3], b[2], b[3]);
        }
    }
    uint32_t pa[3][4];
    {
        const float sc2 = 0.08838834764831845f * 1.4426950408889634f;
        float mx0 = -3.0e38f, mx1 = -3.0e38f;
        const int q0 = 16 * qh + g, q1 = q0 + 8;
        #pragma unroll
        for (int j = 0; j < 5; j++)
            #pragma unroll
            for (int e = 0; e < 2; e++) {
                int key = 8 * j + 2 * t + e - 8;
                sc[j][e] = (key <= q0) ? sc[j][e] * sc2 : -3.0e38f;
                sc[j][2 + e] = (key <= q1) ? sc[j][2 + e] * sc2 : -3.0e38f;
                mx0 = fmaxf(mx0, sc[j][e]); mx1 = fmaxf(mx1, sc[j][2 + e]);
            }
        mx0 = fmaxf(mx0, __shfl_xor_sync(~0u, mx0, 1)); mx0 = fmaxf(mx0, __shfl_xor_sync(~0u, mx0, 2));
        mx1 = fmaxf(mx1, __shfl_xor_sync(~0u, mx1, 1)); mx1 = fmaxf(mx1, __shfl_xor_sync(~0u, mx1, 2));
        float s0 = 0.f, s1 = 0.f;
        #pragma unroll
        for (int j = 0; j < 5; j++)
            #pragma unroll
            for (int e = 0; e < 2; e++) {
                sc[j][e] = ex2_approx(sc[j][e] - mx0); sc[j][2 + e] = ex2_approx(sc[j][2 + e] - mx1);
                s0 += sc[j][e]; s1 += sc[j][2 + e];
            }
        s0 += __shfl_xor_sync(~0u, s0, 1); s0 += __shfl_xor_sync(~0u, s0, 2);
        s1 += __shfl_xor_sync(~0u, s1, 1); s1 += __shfl_xor_sync(~0u, s1, 2);
        const float i0 = __frcp_rn(s0), i1 = __frcp_rn(s1);
        #pragma unroll
        for (int k = 0; k < 3; k++) {
            pa[k][0] = pack_bf16(sc[2 * k][0] * i0, sc[2 * k][1] * i0);
            pa[k][1] = pack_bf16(sc[2 * k][2] * i1, sc[2 * k][3] * i1);
            if (k < 2) { pa[k][2] = pack_bf16(sc[2 * k + 1][0] * i0, sc[2 * k + 1][1] * i0); pa[k][3] = pack_bf16(sc[2 * k + 1][2] * i1, sc[2 * k + 1][3] * i1); }
            else { pa[k][2] = 0u; pa[k][3] = 0u; }
        }
    }
    __syncwarp();
    nbar_sync(5 + u, 64);
    #pragma unroll
    for (int np = 0; np < 8; np++) {
        const int hf = np >> 2, c0 = (np & 3) * 2;
        float o0[4] = {0, 0, 0, 0}, o1[4] = {0, 0, 0, 0};
        #pragma unroll
        for (int k = 0; k < 3; k++) {
            uint32_t b[4];
            int mi = lane >> 3;
            int row = 16 * k + (mi & 1) * 8 + (lane & 7); if (row > 39) row = 39 - 7 + (lane & 7);
            int chunk = c0 + (mi >> 1);
            ldsm4t(b, ub + 18432 + hf * 5120 + row * 128 + ((chunk ^ (row & 7)) << 4));
            mma_bf16(o0, pa[k][0], pa[k][1], pa[k][2], pa[k][3], b[0], k < 2 ? b[1] : 0u);
            mma_bf16(o1, pa[k][0], pa[k][1], pa[k][2], pa[k][3], b[2], k < 2 ? b[3] : 0u);
        }
        int mi = lane >> 3, row = 16 * qh + (mi & 1) * 8 + (lane & 7), chunk = c0 + (mi >> 1);
        stsm4(ub + hf * 4096 + row * 128 + ((chunk ^ (row & 7)) << 4), pack_bf16(o0[0], o0[1]), pack_bf16(o0[2], o0[3]), pack_bf16(o1[0], o1[1]), pack_bf16(o1[2], o1[3]));
    }
}

template <int V> struct IntC { static constexpr int value = V; };
struct Task { int type, rb, c, k0, nch, plane; };
#define NFINE 29
#define NKP 8
#define KPC (64 / NKP + (64 % NKP ? 1 : 0))
#define NGEMM (8 + 144 + 8 * 2 + 4 + 8 * 4 + 2 * NKP * 3 + 16 * 3)
__device__ __forceinline__ Task decode_task(int j) {
    Task t; t.type = 0; t.rb = 0; t.c = 0; t.k0 = 0; t.nch = 16; t.plane = 0;
    auto H = [&](int rb, int i) { t.type = 1; t.rb = rb; t.c = i & 1; t.plane = i >> 1; t.k0 = t.plane * 16; };
    auto CF = [&](int rb, int i) { t.type = 2; t.rb = rb; t.c = i & 1; t.k0 = rb * 64 + (i >> 1) * 16; t.nch = 16; };
    auto H13 = [&](int rb, int i) { t.type = 1; t.rb = rb; t.c = i & 1; t.plane = i >> 1; t.k0 = t.plane * KPC; t.nch = (t.plane == NKP - 1) ? 64 - (NKP - 1) * KPC : KPC; };
    auto C13 = [&](int rb, int i) { t.type = 2; t.rb = rb; t.c = i & 1; t.k0 = rb * 64 + (i >> 1) * 8; t.nch = 8; };
    if (j >= NGEMM) { t.type = 3; return t; }
    if (j < 8) { t.c = j & 1; t.plane = j >> 1; t.k0 = t.plane * 16; return t; }
    j -= 8;
    if (j < 144) {
        const int q = j / 12, r = j % 12;
        if (r < 8) { t.rb = 2 * (q + 1); t.c = r & 1; t.plane = r >> 1; t.k0 = t.plane * 16; }
        else { t.type = 2; t.rb = 2 * q + ((r - 8) >> 1); t.c = r & 1; t.k0 = t.rb * 64; t.nch = 64; }
        return t;
    }
    j -= 144;
    if (j < 8) { H(26, j); return t; }
    j -= 8;
    if (j < 8) { H(27, j); return t; }
    j -= 8;
    if (j < 4) { t.type = 2; t.rb = 24 + (j >> 1); t.c = j & 1; t.k0 = t.rb * 64; t.nch = 64; return t; }
    j -= 4;
    if (j < 8) { H(28, j); return t; }
    j -= 8;
    if (j < 8) { CF(26, j); return t; }
    j -= 8;
    if (j < 8) { CF(27, j); return t; }
    j -= 8;
    if (j < 2 * NKP) { H13(29, j); return t; }
    j -= 2 * NKP;
    if (j < 8) { CF(28, j); return t; }
    j -= 8;
    if (j < 2 * NKP) { H13(30, j); return t; }
    j -= 2 * NKP;
    if (j < 16) { C13(29, j); return t; }
    j -= 16;
    if (j < 2 * NKP) { H13(31, j); return t; }
    j -= 2 * NKP;
    if (j < 16) { C13(30, j); return t; }
    j -= 16;
    C13(31, j);
    return t;
}
__device__ __forceinline__ void gemm_producer(unsigned char* smem, const CUtensorMap* womap, unsigned epoch, volatile int* s_tasks) {
    const uint32_t sb = smem_u32(smem);
    uint32_t st = 0, ph = 1;
    for (int n = 0;; n++) {
        const int j = (int)(atomicAdd(&g_gemmctr, 1u) - epoch * (unsigned)(NGEMM + NAUX));
        const Task t = decode_task(j);
        if (t.type <= 1) {
            wait_counter(&g_ocnt[t.rb], (epoch + 1) * 128u);
            if (t.type == 0) wait_counter(&g_ocnt[t.rb + 1], (epoch + 1) * 128u);
            fence_async_all();
        } else if (t.type == 2) {
            wait_counter(&g_gcnt[t.rb][t.c], (epoch + 1) * (t.rb >= NFINE ? (unsigned)NKP : 4u));
            wait_counter(&g_ssmcnt, (epoch + 1) * 80u);
        }
        const int nch = (t.type <= 1) ? t.nch : 1;
        for (int kc = 0; kc < nch; kc++) {
            mbar_wait_sleep(sb + AX_EMPTY + 8 * st, ph);
            const uint32_t a = sb + AX_DATA + st * AX_STAGE, bar = sb + AX_BAR + 16 + 8 * st;
            if (kc == 0) s_tasks[n & 7] = j;
            if (t.type > 1) mbar_arrive(bar);
            else {
                const bf16* asrc = g_Oimg + ((size_t)(t.rb >> 1) * 64 + t.k0 + kc) * 8192 + (t.rb & 1) * 4096;
                if (t.type == 0) { mbar_expect_tx(bar, AX_STAGE); bulk_g2s(a, asrc, 8192, bar); bulk_g2s(a + 8192, asrc + 4096, 8192, bar); }
                else { mbar_expect_tx(bar, AX_STAGE - 8192); bulk_g2s(a, asrc, 8192, bar); }
                #pragma unroll
                for (int b = 0; b < 5; b++) tma_load_2d(a + 16384 + b * 8192, womap, t.c * 320 + b * 64, (t.k0 + kc) * 64, bar);
            }
            if (++st == NST_G) { st = 0; ph ^= 1; }
        }
        if (t.type == 3) break;
    }
}
__device__ __forceinline__ void gemm_signaller(unsigned char* smem, volatile int* s_done) {
    const uint32_t sb = smem_u32(smem);
    for (int n = 0;; n++) {
        mbar_wait_sleep(sb + AX_DONE + 8 * (n & 3), (n >> 2) & 1);
        const int j = s_done[n & 7];
        if (j < 0) break;
        if ((threadIdx.x & 31) == 0) {
            const Task t = decode_task(j);
            __threadfence();
            atomicAdd(&g_gcnt[t.rb][t.c], 1u);
            if (t.type == 0) atomicAdd(&g_gcnt[t.rb + 1][t.c], 1u);
        }
        __syncwarp();
    }
}
__device__ __forceinline__ void gemm_consumer(unsigned char* smem, bf16* __restrict__ out, volatile int* s_tasks, volatile int* s_done) {
    const uint32_t sb = smem_u32(smem);
    const int tid = threadIdx.x, lane = tid & 31;
    const int wg = __shfl_sync(~0u, tid >> 7, 0), warp = __shfl_sync(~0u, (tid >> 5) & 3, 0);
    uint32_t st = 0, ph = 0;
    int ndone = 0;
    for (int n = 0;; n++) {
        mbar_wait_sleep(sb + AX_BAR + 16 + 8 * st, ph);
        const Task t = decode_task(__shfl_sync(~0u, s_tasks[n & 7], 0));
        if (t.type > 1) {
            nbar_sync(1, 256);
            if ((tid & 127) == 0) mbar_arrive(sb + AX_EMPTY + 8 * st);
            if (++st == NST_G) { st = 0; ph ^= 1; }
            if (t.type == 3) break;
            const int np = (t.rb >= NFINE) ? NKP : 4;
            const float* pbase = (t.rb >= NFINE) ? g_part31 + (size_t)(t.rb - NFINE) * NKP * 64 * DM - (size_t)t.rb * 64 * DM : g_part;
            const size_t pstride = (t.rb >= NFINE) ? (size_t)64 * DM : (size_t)SEQ * DM;
            auto combine = [&](int i, auto NP) {
                const int r = t.k0 + i / 80, cc = t.c * 320 + (i % 80) * 4;
                float4 v[NP.value];
                #pragma unroll
                for (int q = 0; q < NP.value; q++) v[q] = __ldcg(reinterpret_cast<const float4*>(pbase + q * pstride + (size_t)r * DM + cc));
                const float gt = __ldcg(g_g + r);
                const uint2 bb = __ldcg(reinterpret_cast<const uint2*>(g_b + (size_t)r * DM + cc));
                float4 a = v[0];
                #pragma unroll
                for (int q = 1; q < NP.value; q++) { a.x += v[q].x; a.y += v[q].y; a.z += v[q].z; a.w += v[q].w; }
                const float b0 = __uint_as_float(bb.x << 16), b1 = __uint_as_float(bb.x & 0xffff0000u), b2 = __uint_as_float(bb.y << 16), b3 = __uint_as_float(bb.y & 0xffff0000u);
                uint2 o; o.x = pack_bf16(gt * a.x + (1.f - gt) * b0, gt * a.y + (1.f - gt) * b1); o.y = pack_bf16(gt * a.z + (1.f - gt) * b2, gt * a.w + (1.f - gt) * b3);
                *reinterpret_cast<uint2*>(out + (size_t)r * DM + cc) = o;
            };
            if (np == 4) {
                const int nit = t.nch * 80 / 256;
                for (int it0 = 0; it0 < nit; it0 += 5) {
                    #pragma unroll
                    for (int it = 0; it < 5; it++) combine(tid + 256 * (it0 + it), IntC<4>());
                }
            } else {
                #pragma unroll
                for (int it = 0; it < 3; it++) { const int i = tid + 256 * it; if (i < 640) combine(i, IntC<NKP>()); }
            }
            if (n < 56 && (blockIdx.x >= NATT || n < 4)) ATRID((blockIdx.x >= NATT ? 6 : 58) + n, s_tasks[n & 7]);
            continue;
        }
        const int g = lane >> 2, tq = lane & 3;
        if (t.type == 0) {
            float acc[160];
            #pragma unroll
            for (int i = 0; i < 160; i++) acc[i] = 0.f;
            uint32_t prev = 0;
            for (int kc = 0; kc < 16; kc++) {
                mbar_wait(sb + AX_BAR + 16 + 8 * st, ph);
                const uint32_t a = sb + AX_DATA + st * AX_STAGE;
                const uint64_t da = make_desc(a + wg * 8192, 16, 1024), db = make_desc(a + 16384, 8192, 1024);
                wg_fence();
                #pragma unroll
                for (int ks = 0; ks < 4; ks++) {
                    wgmma_n192_tB<0>(acc, da + ks * 2, db + ks * 128);
                    wgmma_n128_tB<96>(acc, da + ks * 2, db + ks * 128 + 3 * 512);
                }
                wg_commit();
                asm volatile("wgmma.wait_group.sync.aligned 1;" ::: "memory");
                if (kc > 0 && (tid & 127) == 0) mbar_arrive(sb + AX_EMPTY + 8 * prev);
                prev = st;
                if (++st == NST_G) { st = 0; ph ^= 1; }
            }
            wg_wait0();
            if ((tid & 127) == 0) mbar_arrive(sb + AX_EMPTY + 8 * prev);
            float* base = g_part + ((size_t)t.plane * SEQ + t.rb * 64 + wg * 64 + warp * 16 + g) * DM + t.c * 320 + 2 * tq;
            #pragma unroll
            for (int q = 0; q < 40; q++) {
                *reinterpret_cast<float2*>(base + q * 8) = make_float2(acc[4 * q], acc[4 * q + 1]);
                *reinterpret_cast<float2*>(base + 8 * DM + q * 8) = make_float2(acc[4 * q + 2], acc[4 * q + 3]);
            }
        } else {
            float* base = (t.rb >= NFINE ? g_part31 + (size_t)((t.rb - NFINE) * NKP + t.plane) * 64 * DM : g_part + ((size_t)t.plane * SEQ + t.rb * 64) * DM) + (size_t)(warp * 16 + g) * DM + t.c * 320 + 2 * tq;
            if (wg == 0) {
                float acc[160];
                #pragma unroll
                for (int i = 0; i < 96; i++) acc[i] = 0.f;
                uint32_t prev = 0;
                for (int kc = 0; kc < t.nch; kc++) {
                    mbar_wait(sb + AX_BAR + 16 + 8 * st, ph);
                    const uint32_t a = sb + AX_DATA + st * AX_STAGE;
                    const uint64_t da = make_desc(a, 16, 1024), db = make_desc(a + 16384, 8192, 1024);
                    wg_fence();
                    #pragma unroll
                    for (int ks = 0; ks < 4; ks++) wgmma_n192_tB<0>(acc, da + ks * 2, db + ks * 128);
                    wg_commit();
                    asm volatile("wgmma.wait_group.sync.aligned 1;" ::: "memory");
                    if (kc > 0 && (tid & 127) == 0) mbar_arrive(sb + AX_EMPTY + 8 * prev);
                    prev = st;
                    if (++st == NST_G) { st = 0; ph ^= 1; }
                }
                wg_wait0();
                if ((tid & 127) == 0) mbar_arrive(sb + AX_EMPTY + 8 * prev);
                #pragma unroll
                for (int q = 0; q < 24; q++) {
                    *reinterpret_cast<float2*>(base + q * 8) = make_float2(acc[4 * q], acc[4 * q + 1]);
                    *reinterpret_cast<float2*>(base + 8 * DM + q * 8) = make_float2(acc[4 * q + 2], acc[4 * q + 3]);
                }
            } else {
                float acc[160];
                #pragma unroll
                for (int i = 96; i < 160; i++) acc[i] = 0.f;
                uint32_t prev = 0;
                for (int kc = 0; kc < t.nch; kc++) {
                    mbar_wait(sb + AX_BAR + 16 + 8 * st, ph);
                    const uint32_t a = sb + AX_DATA + st * AX_STAGE;
                    const uint64_t da = make_desc(a, 16, 1024), db = make_desc(a + 16384, 8192, 1024);
                    wg_fence();
                    #pragma unroll
                    for (int ks = 0; ks < 4; ks++) wgmma_n128_tB<96>(acc, da + ks * 2, db + ks * 128 + 3 * 512);
                    wg_commit();
                    asm volatile("wgmma.wait_group.sync.aligned 1;" ::: "memory");
                    if (kc > 0 && (tid & 127) == 0) mbar_arrive(sb + AX_EMPTY + 8 * prev);
                    prev = st;
                    if (++st == NST_G) { st = 0; ph ^= 1; }
                }
                wg_wait0();
                if ((tid & 127) == 0) mbar_arrive(sb + AX_EMPTY + 8 * prev);
                #pragma unroll
                for (int q = 24; q < 40; q++) {
                    *reinterpret_cast<float2*>(base + q * 8) = make_float2(acc[4 * q], acc[4 * q + 1]);
                    *reinterpret_cast<float2*>(base + 8 * DM + q * 8) = make_float2(acc[4 * q + 2], acc[4 * q + 3]);
                }
            }
        }
        if (tid == 0) s_done[ndone & 7] = s_tasks[n & 7];
        __syncwarp();
        if (lane == 0) mbar_arrive(sb + AX_DONE + 8 * (ndone & 3));
        ndone++;
        if (n < 56 && (blockIdx.x >= NATT || n < 4)) ATRID((blockIdx.x >= NATT ? 6 : 58) + n, s_tasks[n & 7]);
    }
    if (tid == 0) s_done[ndone & 7] = -1;
    __syncwarp();
    if (lane == 0) mbar_arrive(sb + AX_DONE + 8 * (ndone & 3));
}

__global__ void __launch_bounds__(384, 1)
k_aux(const __grid_constant__ CUtensorMap womap, const bf16* __restrict__ x, const bf16* __restrict__ A_re, const bf16* __restrict__ A_im,
      const bf16* __restrict__ B_re, const bf16* __restrict__ B_im, const bf16* __restrict__ C_re, const bf16* __restrict__ C_im,
      const bf16* __restrict__ log_dt, const bf16* __restrict__ Dskip, const bf16* __restrict__ gw, bf16* __restrict__ out) {
    extern __shared__ __align__(1024) unsigned char smem[];
    const uint32_t sb = smem_u32(smem);
    const int tid = threadIdx.x, warp = tid >> 5, lane = tid & 31;
    __shared__ unsigned s_epoch;
    __shared__ int s_task, s_tasks[8], s_done[8];
    if (tid == 0) {
        for (int i = 0; i < 2 + NST_G; i++) mbar_init(sb + AX_BAR + 8 * i, 1);
        for (int i = 0; i < NST_G; i++) mbar_init(sb + AX_EMPTY + 8 * i, blockIdx.x < NATT ? 8 : 2);
        asm volatile("fence.mbarrier_init.release.cluster;" ::: "memory");
        s_epoch = *reinterpret_cast<volatile unsigned*>(&g_epoch);
    }
    __syncthreads();
    const unsigned epoch = s_epoch;
    ATR(0);
    const int wg = __shfl_sync(~0u, tid >> 7, 0);
    if (wg == 2) {
        asm volatile("setmaxnreg.dec.sync.aligned.u32 40;");
        if (blockIdx.x < NATT) { if (warp == 8) attn_producer(smem, blockIdx.x, epoch); else if (warp == 9) attn_storer(smem, blockIdx.x); __syncwarp(); }
        nbar_sync(3, 384);
        nbar_sync(3, 384);
        if (warp == 8) { if (lane == 0) gemm_producer(smem, &womap, epoch, s_tasks); }
        else if (warp == 9) gemm_signaller(smem, s_done);
        __syncwarp();
        nbar_sync(4, 384);
    } else {
        asm volatile("setmaxnreg.inc.sync.aligned.u32 232;");
        if (blockIdx.x < NATT) attn_loop(smem, blockIdx.x, epoch);
        else {
            int ntask = 0;
            for (;;) {
                nbar_sync(1, 256);
                if (tid == 0) s_task = (int)(atomicAdd(&g_taskctr, 1u) - epoch * (unsigned)(80 + NAUX - NATT));
                nbar_sync(1, 256);
                const int task = s_task;
                if (task >= 80) break;
                for (int r = task * 26 + warp; r < min(SEQ, task * 26 + 26); r += 8) {
                    float sum = 0.f;
                    for (int i = lane * 2; i < DM; i += 64) {
                        __nv_bfloat162 xv = *reinterpret_cast<const __nv_bfloat162*>(x + (size_t)r * DM + i), wv = *reinterpret_cast<const __nv_bfloat162*>(gw + i);
                        sum += bf2f(xv.x) * bf2f(wv.x) + bf2f(xv.y) * bf2f(wv.y);
                    }
                    #pragma unroll
                    for (int o = 16; o; o >>= 1) sum += __shfl_xor_sync(~0u, sum, o);
                    if (lane == 0) g_g[r] = 1.f / (1.f + expf(-sum));
                }
                ssm_group(smem + AX_DATA, task, x, A_re, A_im, B_re, B_im, C_re, C_im, log_dt, Dskip);
                nbar_sync(1, 256);
                if (tid == 0) { __threadfence(); atomicAdd(&g_ssmcnt, 1u); }
                if (ntask < 4) ATR(2 + ntask);
                ntask++;
            }
        }
        fence_async();
        nbar_sync(3, 384);
        if (tid == 0) {
            for (int i = 0; i < NST_G; i++) {
                asm volatile("mbarrier.inval.shared::cta.b64 [%0];" :: "r"(sb + AX_BAR + 16 + 8 * i) : "memory");
                asm volatile("mbarrier.inval.shared::cta.b64 [%0];" :: "r"(sb + AX_EMPTY + 8 * i) : "memory");
                mbar_init(sb + AX_BAR + 16 + 8 * i, 1); mbar_init(sb + AX_EMPTY + 8 * i, 2);
            }
            for (int i = 0; i < 4; i++) mbar_init(sb + AX_DONE + 8 * i, 8);
            asm volatile("fence.mbarrier_init.release.cluster;" ::: "memory");
        }
        nbar_sync(3, 384);
        gemm_consumer(smem, out, s_tasks, s_done);
        nbar_sync(4, 384);
        if (tid == 0) {
            __threadfence();
            unsigned old = atomicAdd(&g_auxdone, 1u);
            if (old == NAUX - 1) { g_auxdone = 0; __threadfence(); atomicAdd(&g_epoch, 1u); }
        }
    }
    asm volatile("griddepcontrol.wait;" ::: "memory");
}

extern "C" void kernel_launch(void* const* d_in, const int* in_sizes, int n_in, void* d_out, int out_size) {
    const bf16* x = (const bf16*)d_in[0];
    const bf16* mem0 = (const bf16*)d_in[1];
    const bf16* Wq = (const bf16*)d_in[2];
    const bf16* Wk = (const bf16*)d_in[3];
    const bf16* Wv = (const bf16*)d_in[4];
    const bf16* Wo = (const bf16*)d_in[5];
    const bf16 *A_re = (const bf16*)d_in[8], *A_im = (const bf16*)d_in[9], *B_re = (const bf16*)d_in[10], *B_im = (const bf16*)d_in[11];
    const bf16 *C_re = (const bf16*)d_in[12], *C_im = (const bf16*)d_in[13], *log_dt = (const bf16*)d_in[14], *Dskip = (const bf16*)d_in[15];
    const bf16* gw = (const bf16*)d_in[16];
    bf16* out = (bf16*)d_out;
    cudaStream_t st = cudaStreamPerThread;
    static bool init = false;
    static CUtensorMap xmap, womap, wqmap, wkmap, wvmap;
    static const void* xmap_ptr = nullptr; static const void* womap_ptr = nullptr; static const void* w_ptr[3] = {nullptr, nullptr, nullptr};
    if (!init) {
        cudaFuncSetAttribute(k_chain, cudaFuncAttributeMaxDynamicSharedMemorySize, SM_TOTAL);
        cudaFuncSetAttribute(k_aux, cudaFuncAttributeMaxDynamicSharedMemorySize, AX_TOTAL);
        init = true;
    }
    if (xmap_ptr != (const void*)x || womap_ptr != (const void*)Wo || w_ptr[0] != Wq || w_ptr[1] != Wk || w_ptr[2] != Wv) {
        void* fn = nullptr; cudaDriverEntryPointQueryResult qres;
        cudaGetDriverEntryPoint("cuTensorMapEncodeTiled", &fn, cudaEnableDefault, &qres);
        typedef CUresult (*EncFn)(CUtensorMap*, CUtensorMapDataType, cuuint32_t, void*, const cuuint64_t*, const cuuint64_t*, const cuuint32_t*, const cuuint32_t*,
                                  CUtensorMapInterleave, CUtensorMapSwizzle, CUtensorMapL2promotion, CUtensorMapFloatOOBfill);
        cuuint32_t es[2] = {1, 1};
        {
          cuuint64_t dims[3] = {64, SEQ, 10}; cuuint64_t strides[2] = {DM * 2, 128}; cuuint32_t box[3] = {64, 32, 10}; cuuint32_t es3[3] = {1, 1, 1};
          ((EncFn)fn)(&xmap, CU_TENSOR_MAP_DATA_TYPE_BFLOAT16, 3, (void*)x, dims, strides, box, es3, CU_TENSOR_MAP_INTERLEAVE_NONE, CU_TENSOR_MAP_SWIZZLE_128B,
                      CU_TENSOR_MAP_L2_PROMOTION_L2_128B, CU_TENSOR_MAP_FLOAT_OOB_FILL_NONE); }
        { cuuint64_t dims[2] = {DM, HD}; cuuint64_t strides[1] = {DM * 2}; cuuint32_t box[2] = {64, 64};
          ((EncFn)fn)(&womap, CU_TENSOR_MAP_DATA_TYPE_BFLOAT16, 2, (void*)Wo, dims, strides, box, es, CU_TENSOR_MAP_INTERLEAVE_NONE, CU_TENSOR_MAP_SWIZZLE_128B,
                      CU_TENSOR_MAP_L2_PROMOTION_L2_128B, CU_TENSOR_MAP_FLOAT_OOB_FILL_NONE); }
        { cuuint64_t dims[2] = {HD, DM}; cuuint64_t strides[1] = {HD * 2}; cuuint32_t box[2] = {64, 128};
          const bf16* ws[3] = {Wq, Wk, Wv}; CUtensorMap* ms[3] = {&wqmap, &wkmap, &wvmap};
          for (int i = 0; i < 3; i++)
              ((EncFn)fn)(ms[i], CU_TENSOR_MAP_DATA_TYPE_BFLOAT16, 2, (void*)ws[i], dims, strides, box, es, CU_TENSOR_MAP_INTERLEAVE_NONE, CU_TENSOR_MAP_SWIZZLE_128B,
                          CU_TENSOR_MAP_L2_PROMOTION_L2_128B, CU_TENSOR_MAP_FLOAT_OOB_FILL_NONE); }
        xmap_ptr = (const void*)x; womap_ptr = (const void*)Wo; w_ptr[0] = Wq; w_ptr[1] = Wk; w_ptr[2] = Wv;
    }
    k_chain<<<96, 384, SM_TOTAL, st>>>(xmap, wqmap, wkmap, wvmap, womap, x, mem0);
    {
        cudaLaunchConfig_t cfg = {};
        cfg.gridDim = dim3(NAUX); cfg.blockDim = dim3(384); cfg.dynamicSmemBytes = AX_TOTAL; cfg.stream = st;
        cudaLaunchAttribute at[1];
        at[0].id = cudaLaunchAttributeProgrammaticStreamSerialization; at[0].val.programmaticStreamSerializationAllowed = 1;
        cfg.attrs = at; cfg.numAttrs = 1;
        cudaLaunchKernelEx(&cfg, k_aux, womap, x, A_re, A_im, B_re, B_im, C_re, C_im, log_dt, Dskip, gw, out);
    }
}
```
